```python
import torch

def _softmax(x, axis=-1):
    return torch.softmax(x, dim=axis)

def _gelu(x):
    return torch.nn.functional.gelu(x, approximate='tanh')

def _silu(x):
    return torch.nn.functional.silu(x)

def _sigmoid(x):
    return torch.sigmoid(x)

def _layernorm(x, axis=-1, eps=1e-05):
    m = x.mean(dim=axis, keepdim=True)
    v = x.var(dim=axis, keepdim=True, unbiased=False)
    return (x - m) / torch.sqrt(v + eps)

def _scatter_add(tgt, idx, src, axis=0):
    return tgt.clone().index_add_(axis, idx, src)

def _segment_sum(src, seg, n):
    out = torch.zeros((n,) + src.shape[1:], dtype=src.dtype)
    return out.index_add_(0, seg, src)

def _pad(x, pw):
    flat = tuple((v for pair in reversed(pw) for v in pair))
    return torch.nn.functional.pad(x, flat)
kernel_name = 'adaLN_cond__gqa_block_cached__glu_gated_swiglu__decode'

def setup_inputs():

    _w = lambda a: (lambda t: t.to(torch.bfloat16) if t.is_floating_point() else t)(torch.as_tensor(a))

    def _A_setup():
        B, Sq, D = (1, 1, 640)
        Hq, Hkv, Sk, Dh = (32, 32, 8192, 192)
        assert Hq % Hkv == 0, (Hq, Hkv)
        return {'x': _w((lambda *s: torch.randn(*s, dtype=torch.bfloat16) * 0.1)(B, Sq, D)), 'k_cache': _w((lambda *s: torch.randn(*s, dtype=torch.bfloat16) * 0.8)(B, Hkv, Sk, Dh)), 'v_cache': _w((lambda *s: torch.randn(*s, dtype=torch.bfloat16) * 3.2)(B, Hkv, Sk, Dh)), 'wq': _w((lambda *s: torch.randn(*s, dtype=torch.bfloat16) * 0.8)(D, Hq * Dh) * D ** (-0.5)), 'wo': _w((lambda *s: torch.randn(*s, dtype=torch.bfloat16) * 3.2)(Hq * Dh, D) * (Hq * Dh) ** (-0.5))}
    _A_in = _A_setup()

    def _B_setup():
        B, S, D, F = (1, 1, 640, 1536)
        return {'x': _w((lambda *s: torch.randn(*s, dtype=torch.bfloat16) * 0.1)(B, S, D)), 'w1': _w((lambda *s: torch.randn(*s, dtype=torch.bfloat16) * 3.2)(D, F) * (2.0 / D) ** 0.5), 'w3': _w((lambda *s: torch.randn(*s, dtype=torch.bfloat16) * 3.2)(D, F) * (2.0 / D) ** 0.5), 'w2': _w((lambda *s: torch.randn(*s, dtype=torch.bfloat16) * 3.2)(F, D) * (2.0 / F) ** 0.5)}
    _B_in = _B_setup()
    return {'A_x': _A_in['x'], 'A_k_cache': _A_in['k_cache'], 'A_v_cache': _A_in['v_cache'], 'A_wq': _A_in['wq'], 'A_wo': _A_in['wo'], 'B_x': _B_in['x'], 'B_w1': _B_in['w1'], 'B_w3': _B_in['w3'], 'B_w2': _B_in['w2'], 'c': _w((lambda *s: torch.randn(*s, dtype=torch.bfloat16) * 0.4)(1, 640) * 8.0), 'w_mod': _w((lambda *s: torch.randn(*s, dtype=torch.bfloat16) * 0.4)(640, 6 * 640) * 640 ** (-0.5) * 8.0)}

def reference(A_x, A_k_cache, A_v_cache, A_wq, A_wo, B_x, B_w1, B_w3, B_w2, c, w_mod):

    def _A_ref(x, k_cache, v_cache, wq, wo):
        B, Sq, D = x.shape
        Hq, Dh = (32, 192)
        Hkv = k_cache.shape[1]
        rep = Hq // Hkv
        q = (lambda x, *d: x.permute(*d))((x @ wq).reshape(B, Sq, Hq, Dh), 0, 2, 1, 3)
        k = (lambda x, n, axis: torch.repeat_interleave(x, n, dim=axis))(k_cache, rep, axis=1)
        v = (lambda x, n, axis: torch.repeat_interleave(x, n, dim=axis))(v_cache, rep, axis=1)
        scores = torch.einsum('bhqd,bhkd->bhqk', q, k) * Dh ** (-0.5)
        p = _softmax(scores, axis=-1)
        o = torch.einsum('bhqk,bhkd->bhqd', p, v)
        return (lambda x, *d: x.permute(*d))(o, 0, 2, 1, 3).reshape(B, Sq, Hq * Dh) @ wo

    def _B_ref(x, w1, w3, w2):
        gate = torch.einsum('bsd,df->bsf', x, w1)
        up = torch.einsum('bsd,df->bsf', x, w3)
        h = _silu(gate) * up
        out = torch.einsum('bsf,fd->bsd', h, w2)
        return out
    x = A_x
    mod = (_silu(c) @ w_mod).reshape(c.shape[0], 6, 1, -1)
    sa, ca, ga, sb, cb, gb = (mod[:, 0].clone(), mod[:, 1].clone(), mod[:, 2].clone(), mod[:, 3].clone(), mod[:, 4].clone(), mod[:, 5].clone())
    h = _layernorm(x, axis=-1) * (1 + ca) + sa
    x = x + ga * _A_ref(h, A_k_cache, A_v_cache, A_wq, A_wo)
    h = _layernorm(x, axis=-1) * (1 + cb) + sb
    x = x + gb * _B_ref(h, B_w1, B_w3, B_w2)
    return x
```

```cpp
#include <cuda_runtime.h>
#include <cuda_bf16.h>
#include <cuda.h>
#include <stdint.h>

namespace {

constexpr int D = 640, NH = 32, SK = 8192, DH = 192, FF = 1536;
constexpr int NG = 4;
constexpr int HPG = NH / NG;
constexpr int TILE = 32;
constexpr int TPH = SK / TILE;
constexpr int TICKETS = HPG * TPH;
constexpr int CHUNK = TILE * DH * 2;
constexpr int NSLOT = 7;
constexpr int WIN = 4;
constexpr int MAXR = 40;
constexpr int NTHREADS = 288;
constexpr int NPK = 65;

constexpr int SM_W = 0;
constexpr int SM_WMOD = 0;
constexpr int SM_WQ = 40960;
constexpr int SM_WO = 0;
constexpr int SM_W1 = 61440;
constexpr int SM_W3 = 81920;
constexpr int SM_W2 = 102400;
constexpr int SM_RING = 122880;
constexpr int SM_MISC = SM_RING + NSLOT * CHUNK;
constexpr int SM_BARS = SM_MISC;
constexpr int SM_META = SM_BARS + 512;
constexpr int SM_Q = SM_META + 64;
constexpr int SM_SC = SM_Q + HPG * DH * 2;
constexpr int SM_H = SM_SC + 1280;
constexpr int SM_X = SM_H + 1280;
constexpr int SM_CB = SM_X + 1280;
constexpr int SM_SB = SM_CB + 1280;
constexpr int SM_OWN = SM_SB + 1280;
constexpr int SM_RED = SM_OWN + 128;
constexpr int SM_MERGE = SM_RED + 2048;
constexpr int SM_STAGE = SM_MERGE + 3200;
constexpr int SM_X2 = SM_STAGE + 2560;
constexpr int SM_OS = SM_X2 + 2560;
constexpr int SM_TOTAL = SM_OS + 128;
static_assert(SM_TOTAL <= 232448, "shared memory budget");

constexpr int B_FULL = 0;
constexpr int B_EMPTY = 8;
constexpr int B_MOD = 16;
constexpr int B_WQ = 20;
constexpr int B_WO = 25;
constexpr int B_W1 = 30;
constexpr int B_W3 = 32;
constexpr int B_W2 = 34;
constexpr int B_FLF = 36, B_FLE = 37, B_COMB = 38, B_PRO = 39, B_DUMMY = 40;

__device__ unsigned g_epoch;
__device__ unsigned g_ctr[2][NG * 32];
__device__ __align__(128) unsigned long long g_mod[1920];
__device__ __align__(128) unsigned long long g_q[3072];
__device__ __align__(128) uint4 g_part[NH][MAXR][NPK + 1];
__device__ __align__(128) uint4 g_h1[128][128][2];
__device__ __align__(128) uint4 g_x2[128];
__device__ __align__(128) uint4 g_h3[128][96][2];

#define TS(k) do {} while (0)

__device__ __forceinline__ uint32_t smem_u32(const void* p) { return (uint32_t)__cvta_generic_to_shared(p); }
__device__ __forceinline__ void mbar_init(uint32_t bar, uint32_t cnt) {
    asm volatile("mbarrier.init.shared::cta.b64 [%0], %1;" ::"r"(bar), "r"(cnt) : "memory");
}
__device__ __forceinline__ void mbar_expect_tx(uint32_t bar, uint32_t bytes) {
    asm volatile("mbarrier.arrive.expect_tx.shared::cta.b64 _, [%0], %1;" ::"r"(bar), "r"(bytes) : "memory");
}
__device__ __forceinline__ void mbar_arrive(uint32_t bar) {
    asm volatile("mbarrier.arrive.shared::cta.b64 _, [%0];" ::"r"(bar) : "memory");
}
__device__ __forceinline__ bool mbar_try(uint32_t bar, uint32_t parity) {
    uint32_t ok;
    asm volatile(
        "{\n.reg .pred p;\nmbarrier.try_wait.parity.shared::cta.b64 p, [%1], %2;\nselp.u32 %0, 1, 0, p;\n}"
        : "=r"(ok)
        : "r"(bar), "r"(parity)
        : "memory");
    return ok != 0;
}
constexpr long long WAIT_LIMIT = 4000000000LL;
__device__ __forceinline__ void mbar_wait(uint32_t bar, uint32_t parity) {
    if (mbar_try(bar, parity)) return;
    long long t0 = clock64();
    while (!mbar_try(bar, parity)) {
        if (clock64() - t0 > WAIT_LIMIT) __trap();
    }
}
__device__ __forceinline__ void tma2d(uint32_t dst, const CUtensorMap* tm, int c0, int c1, uint32_t bar) {
    asm volatile(
        "cp.async.bulk.tensor.2d.shared::cluster.global.mbarrier::complete_tx::bytes [%0], [%1, {%3, %4}], [%2];" ::"r"(dst),
        "l"(tm), "r"(bar), "r"(c0), "r"(c1)
        : "memory");
}
__device__ __forceinline__ void tma2d_hint(uint32_t dst, const CUtensorMap* tm, int c0, int c1, uint32_t bar, uint64_t pol) {
    asm volatile(
        "cp.async.bulk.tensor.2d.shared::cluster.global.mbarrier::complete_tx::bytes.L2::cache_hint [%0], [%1, {%3, %4}], [%2], %5;" ::"r"(dst),
        "l"(tm), "r"(bar), "r"(c0), "r"(c1), "l"(pol)
        : "memory");
}
__device__ __forceinline__ void prefetch_tm(const CUtensorMap* tm) {
    asm volatile("prefetch.tensormap [%0];" ::"l"(tm) : "memory");
}
__device__ __forceinline__ void ldsm4(uint32_t (&r)[4], uint32_t addr) {
    asm volatile("ldmatrix.sync.aligned.m8n8.x4.shared.b16 {%0,%1,%2,%3}, [%4];"
                 : "=r"(r[0]), "=r"(r[1]), "=r"(r[2]), "=r"(r[3])
                 : "r"(addr)
                 : "memory");
}
__device__ __forceinline__ void ldsm4t(uint32_t (&r)[4], uint32_t addr) {
    asm volatile("ldmatrix.sync.aligned.m8n8.x4.trans.shared.b16 {%0,%1,%2,%3}, [%4];"
                 : "=r"(r[0]), "=r"(r[1]), "=r"(r[2]), "=r"(r[3])
                 : "r"(addr)
                 : "memory");
}
__device__ __forceinline__ void mma16816(float (&d)[4], const uint32_t (&a)[4], uint32_t b0, uint32_t b1) {
    asm volatile(
        "mma.sync.aligned.m16n8k16.row.col.f32.bf16.bf16.f32 {%0,%1,%2,%3}, {%4,%5,%6,%7}, {%8,%9}, {%0,%1,%2,%3};"
        : "+f"(d[0]), "+f"(d[1]), "+f"(d[2]), "+f"(d[3])
        : "r"(a[0]), "r"(a[1]), "r"(a[2]), "r"(a[3]), "r"(b0), "r"(b1));
}
__device__ __forceinline__ void bar_cons() { asm volatile("bar.sync 1, 256;" ::: "memory"); }

__device__ __forceinline__ float bfr(float x) { return __bfloat162float(__float2bfloat16_rn(x)); }
__device__ __forceinline__ uint32_t pack_bf(float lo, float hi) {
    __nv_bfloat162 t = __floats2bfloat162_rn(lo, hi);
    return *reinterpret_cast<uint32_t*>(&t);
}
__device__ __forceinline__ float bf_lo(uint32_t v) { return __uint_as_float(v << 16); }
__device__ __forceinline__ float bf_hi(uint32_t v) { return __uint_as_float(v & 0xffff0000u); }

__device__ __forceinline__ void st_pk8(unsigned long long* p, uint32_t v, uint32_t tag) {
    unsigned long long w = ((unsigned long long)tag << 32) | v;
    asm volatile("st.relaxed.gpu.global.b64 [%0], %1;" ::"l"(p), "l"(w) : "memory");
}
__device__ __forceinline__ uint32_t ld_pk8(const unsigned long long* p, uint32_t tag) {
    unsigned long long w;
    asm volatile("ld.relaxed.gpu.global.b64 %0, [%1];" : "=l"(w) : "l"(p) : "memory");
    if ((uint32_t)(w >> 32) != tag) {
        long long t0 = clock64();
        do {
            asm volatile("ld.relaxed.gpu.global.b64 %0, [%1];" : "=l"(w) : "l"(p) : "memory");
            if (clock64() - t0 > WAIT_LIMIT) __trap();
        } while ((uint32_t)(w >> 32) != tag);
    }
    return (uint32_t)w;
}
__device__ __forceinline__ void st_pk16(uint4* p, uint32_t a, uint32_t b, uint32_t c, uint32_t tag) {
    asm volatile(
        "{\n.reg .b128 t;\n.reg .b64 lo, hi;\nmov.b64 lo, {%1, %2};\nmov.b64 hi, {%3, %4};\nmov.b128 t, {lo, hi};\n"
        "st.relaxed.gpu.global.b128 [%0], t;\n}" ::"l"(p), "r"(a), "r"(b), "r"(c), "r"(tag)
        : "memory");
}
__device__ __forceinline__ uint4 ld_raw16(const uint4* p) {
    uint4 v;
    asm volatile(
        "{\n.reg .b128 t;\n.reg .b64 lo, hi;\nld.relaxed.gpu.global.b128 t, [%4];\nmov.b128 {lo, hi}, t;\n"
        "mov.b64 {%0, %1}, lo;\nmov.b64 {%2, %3}, hi;\n}"
        : "=r"(v.x), "=r"(v.y), "=r"(v.z), "=r"(v.w)
        : "l"(p)
        : "memory");
    return v;
}
__device__ __forceinline__ void fix_pk16(uint4& v, const uint4* p, uint32_t tag) {
    if (v.w != tag) {
        long long t0 = clock64();
        do {
            v = ld_raw16(p);
            if (clock64() - t0 > WAIT_LIMIT) __trap();
        } while (v.w != tag);
    }
}
__device__ __forceinline__ float warp_sum(float v) {
#pragma unroll
    for (int o = 16; o > 0; o >>= 1) v += __shfl_xor_sync(0xffffffffu, v, o);
    return v;
}

__device__ __forceinline__ void ln_stats(const float (&v)[20], float& mean_b, float& den_b) {
    float s = 0.f;
#pragma unroll
    for (int i = 0; i < 20; i++) s += v[i];
    s = warp_sum(s);
    float mean = s * (1.0f / 640.0f);
    float q = 0.f;
#pragma unroll
    for (int i = 0; i < 20; i++) { float d = v[i] - mean; q += d * d; }
    q = warp_sum(q);
    float var_b = bfr(q * (1.0f / 640.0f));
    mean_b = bfr(mean);
    den_b = bfr(sqrtf(bfr(var_b + 1e-5f)));
}

struct Window {
    uint32_t bar[WIN];
    uint32_t par[WIN];
    __device__ __forceinline__ void init(uint32_t dummy) {
#pragma unroll
        for (int i = 0; i < WIN; i++) { bar[i] = dummy; par[i] = 1; }
    }
    __device__ __forceinline__ void push(uint32_t b, uint32_t p) {
        mbar_wait(bar[0], par[0]);
#pragma unroll
        for (int i = 0; i + 1 < WIN; i++) { bar[i] = bar[i + 1]; par[i] = par[i + 1]; }
        bar[WIN - 1] = b; par[WIN - 1] = p;
    }
};

__global__ void __launch_bounds__(NTHREADS, 1)
fused_decode_kernel(const __grid_constant__ CUtensorMap tmK, const __grid_constant__ CUtensorMap tmV,
                    const __grid_constant__ CUtensorMap tmMod, const __grid_constant__ CUtensorMap tmWq,
                    const __grid_constant__ CUtensorMap tmWo, const __grid_constant__ CUtensorMap tmW1,
                    const __grid_constant__ CUtensorMap tmW3, const __grid_constant__ CUtensorMap tmW2,
                    const __nv_bfloat16* __restrict__ x_in, const __nv_bfloat16* __restrict__ c_in,
                    __nv_bfloat16* __restrict__ out) {
    extern __shared__ __align__(1024) uint8_t smem[];
    const uint32_t sb = smem_u32(smem);
    const int tid = threadIdx.x, wid = tid >> 5, lane = tid & 31;
    const int cta = blockIdx.x, G = gridDim.x;
    const int grp = cta % NG;
    const uint32_t bars = sb + SM_BARS;
    auto BAR = [&](int i) { return bars + 8u * i; };
    volatile uint32_t* meta = reinterpret_cast<volatile uint32_t*>(smem + SM_META);

    if (wid == 8) {
        Window win;
        unsigned epoch = 0;
        if (lane == 0) {
            TS(0);
            if (sb & 1023u) __trap();
            asm volatile("ld.relaxed.gpu.global.u32 %0, [%1];" : "=r"(epoch) : "l"(&g_epoch) : "memory");
            prefetch_tm(&tmMod); prefetch_tm(&tmWq); prefetch_tm(&tmK); prefetch_tm(&tmV);
            for (int i = 0; i < NSLOT; i++) { mbar_init(BAR(B_FULL + i), 1); mbar_init(BAR(B_EMPTY + i), 2); }
            for (int i = B_MOD; i < B_FLF; i++) mbar_init(BAR(i), 1);
            mbar_init(BAR(B_FLF), 4); mbar_init(BAR(B_FLE), 1); mbar_init(BAR(B_COMB), 1); mbar_init(BAR(B_PRO), 1);
            mbar_init(BAR(B_DUMMY), 1);
            asm volatile("fence.mbarrier_init.release.cluster;" ::: "memory");
            asm volatile("fence.proxy.async.shared::cta;" ::: "memory");
            win.init(BAR(B_DUMMY));
            if (cta < 120) {
                for (int i = 0; i < 4; i++) {
                    win.push(BAR(B_MOD + i), 0);
                    mbar_expect_tx(BAR(B_MOD + i), 10240);
                    tma2d(sb + SM_WMOD + i * 10240, &tmMod, cta * 32, i * 160, BAR(B_MOD + i));
                }
            }
        }
        __syncwarp();
        __syncthreads();
        if (lane == 0) {
            prefetch_tm(&tmWo); prefetch_tm(&tmW1); prefetch_tm(&tmW3); prefetch_tm(&tmW2);
            unsigned* ctr = &g_ctr[epoch & 1][grp * 32];
            if (cta == 0) {
                for (int g = 0; g < NG; g++) g_ctr[(epoch + 1) & 1][g * 32] = 0;
            }
            unsigned t_cur = atomicAdd(ctr, 1);
            unsigned t_nxt = atomicAdd(ctr, 1);
            if (cta < 128) {
                for (int i = 0; i < 5; i++) {
                    win.push(BAR(B_WQ + i), 0);
                    mbar_expect_tx(BAR(B_WQ + i), 12288);
                    tma2d(sb + SM_WQ + i * 12288, &tmWq, cta * 48, i * 128, BAR(B_WQ + i));
                }
            }
            uint64_t pol;
            asm volatile("createpolicy.fractional.L2::evict_first.b64 %0, 1.0;" : "=l"(pol));
            int s = 0; uint32_t par = 0;
            while (t_cur < (unsigned)TICKETS) {
                unsigned t = t_cur;
                t_cur = t_nxt;
                t_nxt = (t_cur < (unsigned)TICKETS) ? atomicAdd(ctr, 1) : (unsigned)TICKETS;
                int pos = t / TPH, tile = t % TPH;
                int line0 = ((grp * HPG + pos) * SK + tile * TILE) * 3;
                win.push(BAR(B_FULL + s), par);
                mbar_wait(BAR(B_EMPTY + s), par ^ 1);
                meta[s] = pos;
                mbar_expect_tx(BAR(B_FULL + s), CHUNK);
                tma2d_hint(sb + SM_RING + s * CHUNK, &tmK, 0, line0, BAR(B_FULL + s), pol);
                if (++s == NSLOT) { s = 0; par ^= 1; }
                win.push(BAR(B_FULL + s), par);
                mbar_wait(BAR(B_EMPTY + s), par ^ 1);
                mbar_expect_tx(BAR(B_FULL + s), CHUNK);
                tma2d_hint(sb + SM_RING + s * CHUNK, &tmV, 0, line0, BAR(B_FULL + s), pol);
                if (++s == NSLOT) { s = 0; par ^= 1; }
            }
            TS(4);
            for (int e = 0; e < 2; e++) {
                mbar_wait(BAR(B_EMPTY + s), par ^ 1);
                meta[s] = HPG;
                mbar_arrive(BAR(B_FULL + s));
                if (++s == NSLOT) { s = 0; par ^= 1; }
                if (++s == NSLOT) { s = 0; par ^= 1; }
            }
            if (cta < 128) {
                mbar_wait(BAR(B_PRO), 0);
                for (int i = 0; i < 5; i++) {
                    win.push(BAR(B_WO + i), 0);
                    mbar_expect_tx(BAR(B_WO + i), 12288);
                    tma2d(sb + SM_WO + (2 * i) * 6144, &tmWo, (2 * i) * 64, cta * 48, BAR(B_WO + i));
                    tma2d(sb + SM_WO + (2 * i + 1) * 6144, &tmWo, (2 * i + 1) * 64, cta * 48, BAR(B_WO + i));
                }
                if (cta < 96) {
                    for (int i = 0; i < 2; i++) {
                        win.push(BAR(B_W1 + i), 0);
                        mbar_expect_tx(BAR(B_W1 + i), 10240);
                        tma2d(sb + SM_W1 + i * 10240, &tmW1, cta * 16, i * 320, BAR(B_W1 + i));
                        tma2d(sb + SM_W1 + i * 10240 + 5120, &tmW1, cta * 16, i * 320 + 160, BAR(B_W1 + i));
                        win.push(BAR(B_W3 + i), 0);
                        mbar_expect_tx(BAR(B_W3 + i), 10240);
                        tma2d(sb + SM_W3 + i * 10240, &tmW3, cta * 16, i * 320, BAR(B_W3 + i));
                        tma2d(sb + SM_W3 + i * 10240 + 5120, &tmW3, cta * 16, i * 320 + 160, BAR(B_W3 + i));
                    }
                    for (int i = 0; i < 2; i++) {
                        win.push(BAR(B_W2 + i), 0);
                        mbar_expect_tx(BAR(B_W2 + i), 10240);
                        for (int b = 0; b < 5; b++)
                            tma2d(sb + SM_W2 + (5 * i + b) * 2048, &tmW2, (5 * i + b) * 64, cta * 16, BAR(B_W2 + i));
                    }
                }
            }
            TS(5);
        }
        return;
    }

    const int g4 = lane >> 2, j4 = lane & 3, mi = lane >> 3, l8 = lane & 7;
    uint32_t* sc32 = reinterpret_cast<uint32_t*>(smem + SM_SC);
    uint32_t* h32 = reinterpret_cast<uint32_t*>(smem + SM_H);
    uint32_t* x32 = reinterpret_cast<uint32_t*>(smem + SM_X);
    uint32_t* q32 = reinterpret_cast<uint32_t*>(smem + SM_Q);
    float* red = reinterpret_cast<float*>(smem + SM_RED);
    float* stage = reinterpret_cast<float*>(smem + SM_STAGE);
    float* own = reinterpret_cast<float*>(smem + SM_OWN);

    {
        const uint32_t* cg = reinterpret_cast<const uint32_t*>(c_in);
        const uint32_t* xg = reinterpret_cast<const uint32_t*>(x_in);
        uint32_t c0 = cg[tid], x0 = xg[tid], c1 = 0, x1 = 0;
        if (tid < 64) { c1 = cg[256 + tid]; x1 = xg[256 + tid]; }
        unsigned epoch = 0;
        if (tid == 0) asm volatile("ld.relaxed.gpu.global.u32 %0, [%1];" : "=r"(epoch) : "l"(&g_epoch) : "memory");
        auto silu2 = [](uint32_t v) {
            float a = bf_lo(v), b = bf_hi(v);
            return pack_bf(a / (1.0f + __expf(-a)), b / (1.0f + __expf(-b)));
        };
        sc32[tid] = silu2(c0); x32[tid] = x0;
        if (tid < 64) { sc32[256 + tid] = silu2(c1); x32[256 + tid] = x1; }
        if (tid == 0) meta[8] = epoch + 1;
    }
    __syncthreads();
    const uint32_t tag = meta[8];

    if (cta < 120) {
        float acc[2][4] = {};
        mbar_wait(BAR(B_MOD + (wid >> 1)), 0);
        const uint32_t base = sb + SM_WMOD + (wid >> 1) * 10240;
#pragma unroll
        for (int ks = 0; ks < 5; ks++) {
            const int rl = (wid & 1) * 80 + ks * 16;
            const int r = rl + l8 + 8 * (mi >> 1);
            const int r0 = wid * 80 + ks * 16;
            uint32_t b0 = sc32[(r0 >> 1) + j4], b1 = sc32[(r0 >> 1) + 4 + j4];
#pragma unroll
            for (int mt = 0; mt < 2; mt++) {
                uint32_t a[4];
                int cc = 2 * mt + (mi & 1);
                ldsm4t(a, base + r * 64 + ((cc ^ ((r >> 1) & 3)) << 4));
                mma16816(acc[mt], a, b0, b1);
            }
        }
        if (j4 == 0) {
#pragma unroll
            for (int mt = 0; mt < 2; mt++) { red[wid * 64 + mt * 16 + g4] = acc[mt][0]; red[wid * 64 + mt * 16 + 8 + g4] = acc[mt][2]; }
        }
        bar_cons();
        if (wid == 0) {
            float v = 0.f;
#pragma unroll
            for (int w = 0; w < 8; w++) v += red[w * 64 + lane];
            float o = __shfl_down_sync(0xffffffffu, v, 1);
            if (!(lane & 1)) st_pk8(&g_mod[cta * 16 + (lane >> 1)], pack_bf(v, o), tag);
        }
    }
    TS(1);

    if (cta < 128) {
        float xv[20];
#pragma unroll
        for (int i = 0; i < 10; i++) { uint32_t v = x32[lane + 32 * i]; xv[2 * i] = bf_lo(v); xv[2 * i + 1] = bf_hi(v); }
        float mean_b, den_b;
        ln_stats(xv, mean_b, den_b);
#pragma unroll
        for (int rep = 0; rep < 2; rep++) {
            int p = tid + rep * 256;
            if (p < 320) {
                uint32_t sa = ld_pk8(&g_mod[p], tag), ca = ld_pk8(&g_mod[320 + p], tag);
                uint32_t xx = x32[p];
                float n0 = bfr(bfr(bf_lo(xx) - mean_b) / den_b), n1 = bfr(bfr(bf_hi(xx) - mean_b) / den_b);
                float h0 = bfr(n0 * bfr(1.0f + bf_lo(ca))) + bf_lo(sa);
                float h1 = bfr(n1 * bfr(1.0f + bf_hi(ca))) + bf_hi(sa);
                h32[p] = pack_bf(h0, h1);
            }
        }
        bar_cons();
        TS(2);
        float acc[3][4] = {};
#pragma unroll
        for (int ks = 0; ks < 5; ks++) {
            const int r0 = wid * 80 + ks * 16;
            const int ch = r0 >> 7;
            mbar_wait(BAR(B_WQ + ch), 0);
            const int r = (r0 & 127) + l8 + 8 * (mi >> 1);
            uint32_t b0 = h32[(r0 >> 1) + j4], b1 = h32[(r0 >> 1) + 4 + j4];
#pragma unroll
            for (int mt = 0; mt < 3; mt++) {
                uint32_t a[4];
                ldsm4t(a, sb + SM_WQ + ch * 12288 + r * 96 + ((2 * mt + (mi & 1)) << 4));
                mma16816(acc[mt], a, b0, b1);
            }
        }
        if (j4 == 0) {
#pragma unroll
            for (int mt = 0; mt < 3; mt++) { red[wid * 64 + mt * 16 + g4] = acc[mt][0]; red[wid * 64 + mt * 16 + 8 + g4] = acc[mt][2]; }
        }
        bar_cons();
        if (tid < 64) {
            float v = 0.f;
            if (tid < 48) {
#pragma unroll
                for (int w = 0; w < 8; w++) v += red[w * 64 + tid];
            }
            float o = __shfl_down_sync(0xffffffffu, v, 1);
            if (tid < 48 && !(tid & 1)) st_pk8(&g_q[cta * 24 + (tid >> 1)], pack_bf(v, o), tag);
        }
    }
#pragma unroll
    for (int rep = 0; rep < 3; rep++) {
        int i = tid + rep * 256;
        q32[i] = ld_pk8(&g_q[grp * (HPG * DH / 2) + i], tag);
    }
    bar_cons();
    if (tid == 0) mbar_arrive(BAR(B_PRO));
    TS(3);

    if (wid < 4) {
        const int pair = wid >> 1, half = wid & 1;
        const int rowK = half * 16 + l8 + 8 * (mi & 1), hiK = mi >> 1;
        const int rowV = half * 16 + l8 + 8 * (mi >> 1), hiV = mi & 1;
        float acc[12][4];
#pragma unroll
        for (int i = 0; i < 12; i++) { acc[i][0] = acc[i][1] = acc[i][2] = acc[i][3] = 0.f; }
        float m_run = -3.402823466e38f, l_run = 0.f;
        uint32_t qf[12][2];
        int cur = -1, flushed = 0;
        int s = 2 * pair; uint32_t par = 0;
        float* mb = reinterpret_cast<float*>(smem + SM_MERGE) + wid * 200;
        while (true) {
            mbar_wait(BAR(B_FULL + s), par);
            const int pos = (int)meta[s];
            if (pos != cur) {
                while (flushed < pos) {
                    mbar_wait(BAR(B_FLE), (flushed & 1) ^ 1);
                    if (flushed == cur) {
                        float v[24];
#pragma unroll
                        for (int i = 0; i < 12; i++) { v[2 * i] = acc[i][0] + acc[i][1]; v[2 * i + 1] = acc[i][2] + acc[i][3]; }
                        float u[12];
                        const bool o1 = j4 & 1, o2 = j4 & 2;
#pragma unroll
                        for (int i = 0; i < 12; i++) {
                            float send = o1 ? v[i] : v[i + 12], keep = o1 ? v[i + 12] : v[i];
                            u[i] = keep + __shfl_xor_sync(0xffffffffu, send, 1);
                        }
#pragma unroll
                        for (int i = 0; i < 6; i++) {
                            float send = o2 ? u[i] : u[i + 6], keep = o2 ? u[i + 6] : u[i];
                            float w = keep + __shfl_xor_sync(0xffffffffu, send, 2);
                            int idx = (o1 ? 12 : 0) + (o2 ? 6 : 0) + i;
                            mb[4 + 16 * (idx >> 1) + 8 * (idx & 1) + g4] = w;
                        }
                        float l = l_run;
                        l += __shfl_xor_sync(0xffffffffu, l, 4);
                        l += __shfl_xor_sync(0xffffffffu, l, 8);
                        l += __shfl_xor_sync(0xffffffffu, l, 16);
                        if (lane == 0) { mb[0] = m_run; mb[1] = l; }
                    } else {
#pragma unroll
                        for (int i = 0; i < 6; i++) mb[4 + lane + 32 * i] = 0.f;
                        if (lane == 0) { mb[0] = -3.402823466e38f; mb[1] = 0.f; }
                    }
                    __syncwarp();
                    if (lane == 0) mbar_arrive(BAR(B_FLF));
                    flushed++;
                }
                if (pos >= HPG) break;
                cur = pos;
#pragma unroll
                for (int i = 0; i < 12; i++) { acc[i][0] = acc[i][1] = acc[i][2] = acc[i][3] = 0.f; }
                m_run = -3.402823466e38f; l_run = 0.f;
#pragma unroll
                for (int ks = 0; ks < 12; ks++) {
                    qf[ks][0] = q32[pos * 96 + ks * 8 + j4];
                    qf[ks][1] = q32[pos * 96 + ks * 8 + 4 + j4];
                }
            }
            const uint32_t kb = sb + SM_RING + s * CHUNK;
            float sc0[4] = {0.f, 0.f, 0.f, 0.f}, sc1[4] = {0.f, 0.f, 0.f, 0.f}, sc2[4] = {0.f, 0.f, 0.f, 0.f};
#pragma unroll
            for (int kk = 0; kk < 4; kk++) {
                uint32_t a[4];
                const int c = 2 * kk + hiK;
                const int ln = rowK * 3;
                ldsm4(a, kb + (ln + 0) * 128 + ((c ^ ((ln + 0) & 7)) << 4));
                mma16816(sc0, a, qf[kk][0], qf[kk][1]);
                ldsm4(a, kb + (ln + 1) * 128 + ((c ^ ((ln + 1) & 7)) << 4));
                mma16816(sc1, a, qf[4 + kk][0], qf[4 + kk][1]);
                ldsm4(a, kb + (ln + 2) * 128 + ((c ^ ((ln + 2) & 7)) << 4));
                mma16816(sc2, a, qf[8 + kk][0], qf[8 + kk][1]);
            }
            __syncwarp();
            if (lane == 0) mbar_arrive(BAR(B_EMPTY + s));
            int sv = s + 1; uint32_t parv = par;
            if (sv == NSLOT) { sv = 0; parv ^= 1; }
            const float scale = 0.07216878364870322f;
            float s0 = bfr(bfr(sc0[0] + sc1[0] + sc2[0]) * scale);
            float s1 = bfr(bfr(sc0[2] + sc1[2] + sc2[2]) * scale);
            float tm = fmaxf(s0, s1);
            tm = fmaxf(tm, __shfl_xor_sync(0xffffffffu, tm, 4));
            tm = fmaxf(tm, __shfl_xor_sync(0xffffffffu, tm, 8));
            tm = fmaxf(tm, __shfl_xor_sync(0xffffffffu, tm, 16));
            if (tm > m_run) {
                float alpha = exp2f((m_run - tm) * 1.4426950408889634f);
                l_run *= alpha;
#pragma unroll
                for (int i = 0; i < 12; i++) { acc[i][0] *= alpha; acc[i][1] *= alpha; acc[i][2] *= alpha; acc[i][3] *= alpha; }
                m_run = tm;
            }
            float p0 = exp2f((s0 - m_run) * 1.4426950408889634f);
            float p1 = exp2f((s1 - m_run) * 1.4426950408889634f);
            l_run += p0 + p1;
            uint32_t b0 = 0, b1 = 0;
            if (j4 == (g4 >> 1)) {
                uint32_t e0 = pack_bf(p0, 0.f) & 0xffffu, e1 = pack_bf(p1, 0.f) & 0xffffu;
                b0 = (g4 & 1) ? (e0 << 16) : e0;
                b1 = (g4 & 1) ? (e1 << 16) : e1;
            }
            mbar_wait(BAR(B_FULL + sv), parv);
            const uint32_t vb = sb + SM_RING + sv * CHUNK;
#pragma unroll
            for (int t = 0; t < 3; t++) {
                const int ln = rowV * 3 + t;
#pragma unroll
                for (int kk = 0; kk < 4; kk++) {
                    uint32_t a[4];
                    const int c = 2 * kk + hiV;
                    ldsm4t(a, vb + ln * 128 + ((c ^ (ln & 7)) << 4));
                    mma16816(acc[t * 4 + kk], a, b0, b1);
                }
            }
            __syncwarp();
            if (lane == 0) mbar_arrive(BAR(B_EMPTY + sv));
            s += 4;
            if (s >= NSLOT) { s -= NSLOT; par ^= 1; }
        }
        TS(6);
    } else if (wid == 4) {
        const float* mb = reinterpret_cast<const float*>(smem + SM_MERGE);
        const int rank = cta / NG;
        const int own_pos = (cta < 128) ? ((cta >> 2) % HPG) : -1;
        for (int f = 0; f < HPG; f++) {
            mbar_wait(BAR(B_FLF), f & 1);
            float m0 = mb[0], m1 = mb[200], m2 = mb[400], m3 = mb[600];
            float M = fmaxf(fmaxf(m0, m1), fmaxf(m2, m3));
            float w0 = exp2f((m0 - M) * 1.4426950408889634f), w1 = exp2f((m1 - M) * 1.4426950408889634f);
            float w2 = exp2f((m2 - M) * 1.4426950408889634f), w3 = exp2f((m3 - M) * 1.4426950408889634f);
            uint4* dst = &g_part[grp * HPG + f][rank][0];
            float o[6];
#pragma unroll
            for (int i = 0; i < 6; i++) {
                int d = 4 + (i < 3 ? 3 * lane + i : 96 + 3 * lane + (i - 3));
                o[i] = w0 * mb[d] + w1 * mb[200 + d] + w2 * mb[400 + d] + w3 * mb[600 + d];
            }
            float L = w0 * mb[1] + w1 * mb[201] + w2 * mb[401] + w3 * mb[601];
            __syncwarp();
            if (lane == 0) mbar_arrive(BAR(B_FLE));
            st_pk16(dst + 1 + lane, __float_as_uint(o[0]), __float_as_uint(o[1]), __float_as_uint(o[2]), tag);
            st_pk16(dst + 33 + lane, __float_as_uint(o[3]), __float_as_uint(o[4]), __float_as_uint(o[5]), tag);
            if (lane == 0) {
                st_pk16(dst, __float_as_uint(M), __float_as_uint(L), 0u, tag);
                if (f == own_pos) mbar_arrive(BAR(B_COMB));
            }
        }
        TS(7);
    } else if (wid == 5) {
        if (cta < 128) {
            const int h = cta >> 2, js = cta & 3;
            const int gh = h / HPG;
            const int np = (G - gh + NG - 1) / NG;
            mbar_wait(BAR(B_COMB), 0);
            const uint4* src = &g_part[h][0][0];
            uint4 s0 = make_uint4(0, 0, 0, tag), s1 = make_uint4(0, 0, 0, tag);
            if (lane < np) s0 = ld_raw16(src + lane * (NPK + 1));
            if (lane + 32 < np) s1 = ld_raw16(src + (lane + 32) * (NPK + 1));
            const int k = lane & 15, rh = lane >> 4;
            uint4 dv[MAXR / 2];
#pragma unroll
            for (int i = 0; i < MAXR / 2; i++) {
                int r = 2 * i + rh;
                if (r < np) dv[i] = ld_raw16(src + r * (NPK + 1) + 1 + 16 * js + k);
            }
            if (lane < np) fix_pk16(s0, src + lane * (NPK + 1), tag);
            if (lane + 32 < np) fix_pk16(s1, src + (lane + 32) * (NPK + 1), tag);
            float ma = lane < np ? __uint_as_float(s0.x) : -3.402823466e38f;
            float mbv = lane + 32 < np ? __uint_as_float(s1.x) : -3.402823466e38f;
            float M = fmaxf(ma, mbv);
#pragma unroll
            for (int o = 16; o > 0; o >>= 1) M = fmaxf(M, __shfl_xor_sync(0xffffffffu, M, o));
            float wa = lane < np ? exp2f((ma - M) * 1.4426950408889634f) : 0.f;
            float wb = lane + 32 < np ? exp2f((mbv - M) * 1.4426950408889634f) : 0.f;
            float L = warp_sum(wa * __uint_as_float(s0.y) + wb * __uint_as_float(s1.y));
            float a0 = 0.f, a1 = 0.f, a2 = 0.f;
#pragma unroll
            for (int i = 0; i < MAXR / 2; i++) {
                int r = 2 * i + rh;
                float w = __shfl_sync(0xffffffffu, (2 * i < 32) ? wa : wb, r & 31);
                if (r < np) {
                    fix_pk16(dv[i], src + r * (NPK + 1) + 1 + 16 * js + k, tag);
                    a0 += w * __uint_as_float(dv[i].x); a1 += w * __uint_as_float(dv[i].y); a2 += w * __uint_as_float(dv[i].z);
                }
            }
            a0 += __shfl_xor_sync(0xffffffffu, a0, 16);
            a1 += __shfl_xor_sync(0xffffffffu, a1, 16);
            a2 += __shfl_xor_sync(0xffffffffu, a2, 16);
            if (lane < 16) {
                __nv_bfloat16* os = reinterpret_cast<__nv_bfloat16*>(smem + SM_OS);
                float inv = 1.0f / L;
                os[3 * k] = __float2bfloat16_rn(a0 * inv);
                os[3 * k + 1] = __float2bfloat16_rn(a1 * inv);
                os[3 * k + 2] = __float2bfloat16_rn(a2 * inv);
            }
        }
        TS(8);
    } else {
        if (cta < 128) {
            const int t = tid - 192;
            uint32_t* cb32 = reinterpret_cast<uint32_t*>(smem + SM_CB);
            uint32_t* sb32 = reinterpret_cast<uint32_t*>(smem + SM_SB);
#pragma unroll
            for (int rep = 0; rep < 5; rep++) {
                int p = t + 64 * rep;
                uint32_t sv = ld_pk8(&g_mod[960 + p], tag), cv = ld_pk8(&g_mod[1280 + p], tag);
                sb32[p] = sv;
                cb32[p] = pack_bf(1.0f + bf_lo(cv), 1.0f + bf_hi(cv));
            }
            if (t < 5) {
                int col = cta * 5 + t;
                uint32_t ga = ld_pk8(&g_mod[(1280 + col) >> 1], tag), gb = ld_pk8(&g_mod[(3200 + col) >> 1], tag);
                own[t] = (col & 1) ? bf_hi(ga) : bf_lo(ga);
                own[8 + t] = (col & 1) ? bf_hi(gb) : bf_lo(gb);
                uint32_t xx = x32[col >> 1];
                own[16 + t] = (col & 1) ? bf_hi(xx) : bf_lo(xx);
            }
        }
    }
    if (cta >= 128) return;

    bar_cons();
    TS(9);
    {
        const uint32_t* os32 = reinterpret_cast<const uint32_t*>(smem + SM_OS);
        float acc[5][4] = {};
        uint32_t b[3][2];
#pragma unroll
        for (int ks = 0; ks < 3; ks++) { b[ks][0] = os32[ks * 8 + j4]; b[ks][1] = os32[ks * 8 + 4 + j4]; }
#pragma unroll
        for (int i = 0; i < 5; i++) {
            const int mt = wid * 5 + i;
            const int box = mt >> 2;
            mbar_wait(BAR(B_WO + (box >> 1)), 0);
            const int cc = 2 * (mt & 3) + (mi & 1);
#pragma unroll
            for (int ks = 0; ks < 3; ks++) {
                const int r = ks * 16 + l8 + 8 * (mi >> 1);
                uint32_t a[4];
                ldsm4t(a, sb + SM_WO + box * 6144 + r * 128 + ((cc ^ (r & 7)) << 4));
                mma16816(acc[i], a, b[ks][0], b[ks][1]);
            }
        }
        if (j4 == 0) {
#pragma unroll
            for (int i = 0; i < 5; i++) { stage[(wid * 5 + i) * 16 + g4] = acc[i][0]; stage[(wid * 5 + i) * 16 + 8 + g4] = acc[i][2]; }
        }
        bar_cons();
        const int o = tid >> 1, k = tid & 1;
        const float* sp = stage + o * 5 + k * 3;
        st_pk16(&g_h1[o][cta][k], __float_as_uint(sp[0]), __float_as_uint(sp[1]), k ? 0u : __float_as_uint(sp[2]), tag);
    }
    TS(10);
    {
        const uint4* p = &g_h1[cta][tid >> 1][tid & 1];
        uint4 v = ld_raw16(p);
        fix_pk16(v, p, tag);
        float a0 = __uint_as_float(v.x), a1 = __uint_as_float(v.y), a2 = __uint_as_float(v.z);
#pragma unroll
        for (int o = 2; o <= 16; o <<= 1) {
            a0 += __shfl_xor_sync(0xffffffffu, a0, o);
            a1 += __shfl_xor_sync(0xffffffffu, a1, o);
            a2 += __shfl_xor_sync(0xffffffffu, a2, o);
        }
        if (lane < 2) { red[wid * 8 + lane * 3] = a0; red[wid * 8 + lane * 3 + 1] = a1; if (lane == 0) red[wid * 8 + 2] = a2; }
        bar_cons();
        if (wid == 0) {
            float sum = 0.f;
            if (lane < 5) {
#pragma unroll
                for (int w = 0; w < 8; w++) sum += red[w * 8 + lane];
            }
            float x2 = 0.f;
            if (lane < 5) { x2 = bfr(own[16 + lane] + bfr(own[lane] * bfr(sum))); own[24 + lane] = x2; }
            float y1 = __shfl_sync(0xffffffffu, x2, 1), y2 = __shfl_sync(0xffffffffu, x2, 2);
            float y3 = __shfl_sync(0xffffffffu, x2, 3), y4 = __shfl_sync(0xffffffffu, x2, 4);
            if (lane == 0) st_pk16(&g_x2[cta], pack_bf(x2, y1), pack_bf(y2, y3), pack_bf(y4, 0.f), tag);
        }
    }
    TS(11);
    if (cta < 96) {
        float* x2s = reinterpret_cast<float*>(smem + SM_X2);
        if (tid < 128) {
            const uint4* p = &g_x2[tid];
            uint4 v = ld_raw16(p);
            fix_pk16(v, p, tag);
            float* d = x2s + tid * 5;
            d[0] = bf_lo(v.x); d[1] = bf_hi(v.x); d[2] = bf_lo(v.y); d[3] = bf_hi(v.y); d[4] = bf_lo(v.z);
        }
        bar_cons();
        TS(12);
        float xv[20];
#pragma unroll
        for (int i = 0; i < 20; i++) xv[i] = x2s[lane + 32 * i];
        float mean_b, den_b;
        ln_stats(xv, mean_b, den_b);
        const uint32_t* cb32 = reinterpret_cast<const uint32_t*>(smem + SM_CB);
        const uint32_t* sb32 = reinterpret_cast<const uint32_t*>(smem + SM_SB);
        for (int p = lane; p < 40; p += 32) {
            int pp = wid * 40 + p;
            float v0 = x2s[2 * pp], v1 = x2s[2 * pp + 1];
            uint32_t cv = cb32[pp], sv = sb32[pp];
            float n0 = bfr(bfr(v0 - mean_b) / den_b), n1 = bfr(bfr(v1 - mean_b) / den_b);
            h32[pp] = pack_bf(bfr(n0 * bf_lo(cv)) + bf_lo(sv), bfr(n1 * bf_hi(cv)) + bf_hi(sv));
        }
        __syncwarp();
        float ag[4] = {}, au[4] = {};
        mbar_wait(BAR(B_W1 + (wid >> 2)), 0);
        mbar_wait(BAR(B_W3 + (wid >> 2)), 0);
#pragma unroll
        for (int ks = 0; ks < 5; ks++) {
            const int r0 = wid * 80 + ks * 16;
            const int r = r0 + l8 + 8 * (mi >> 1);
            uint32_t b0 = h32[(r0 >> 1) + j4], b1 = h32[(r0 >> 1) + 4 + j4];
            const uint32_t off = r * 32 + (((mi & 1) ^ ((r >> 2) & 1)) << 4);
            uint32_t a[4];
            ldsm4t(a, sb + SM_W1 + off);
            mma16816(ag, a, b0, b1);
            ldsm4t(a, sb + SM_W3 + off);
            mma16816(au, a, b0, b1);
        }
        if (j4 == 0) {
            red[wid * 64 + g4] = ag[0]; red[wid * 64 + 8 + g4] = ag[2];
            red[wid * 64 + 16 + g4] = au[0]; red[wid * 64 + 24 + g4] = au[2];
        }
        bar_cons();
        float v = 0.f;
#pragma unroll
        for (int w = 0; w < 8; w++) v += red[w * 64 + lane];
        v = bfr(v);
        float up = __shfl_down_sync(0xffffffffu, v, 16);
        float hact = bfr(bfr(v / (1.0f + __expf(-v))) * up);
        float e0 = __shfl_sync(0xffffffffu, hact, 2 * j4), e1 = __shfl_sync(0xffffffffu, hact, 2 * j4 + 1);
        float e2 = __shfl_sync(0xffffffffu, hact, 2 * j4 + 8), e3 = __shfl_sync(0xffffffffu, hact, 2 * j4 + 9);
        const uint32_t b0 = pack_bf(e0, e1), b1 = pack_bf(e2, e3);
        mbar_wait(BAR(B_W2 + 0), 0);
        mbar_wait(BAR(B_W2 + 1), 0);
#pragma unroll
        for (int i = 0; i < 5; i++) {
            const int mt = wid * 5 + i;
            const int box = mt >> 2;
            const int cc = 2 * (mt & 3) + (mi & 1);
            const int r = l8 + 8 * (mi >> 1);
            float acc[4] = {};
            uint32_t a[4];
            ldsm4t(a, sb + SM_W2 + box * 2048 + r * 128 + ((cc ^ (r & 7)) << 4));
            mma16816(acc, a, b0, b1);
            if (j4 == 0) { stage[mt * 16 + g4] = acc[0]; stage[mt * 16 + 8 + g4] = acc[2]; }
        }
        bar_cons();
        const int o = tid >> 1, k = tid & 1;
        const float* sp = stage + o * 5 + k * 3;
        st_pk16(&g_h3[o][cta][k], __float_as_uint(sp[0]), __float_as_uint(sp[1]), k ? 0u : __float_as_uint(sp[2]), tag);
    }
    TS(13);
    {
        float a0 = 0.f, a1 = 0.f, a2 = 0.f;
        if (tid < 192) {
            const uint4* p = &g_h3[cta][tid >> 1][tid & 1];
            uint4 v = ld_raw16(p);
            fix_pk16(v, p, tag);
            a0 = __uint_as_float(v.x); a1 = __uint_as_float(v.y); a2 = __uint_as_float(v.z);
        }
#pragma unroll
        for (int o = 2; o <= 16; o <<= 1) {
            a0 += __shfl_xor_sync(0xffffffffu, a0, o);
            a1 += __shfl_xor_sync(0xffffffffu, a1, o);
            a2 += __shfl_xor_sync(0xffffffffu, a2, o);
        }
        bar_cons();
        if (lane < 2) { red[wid * 8 + lane * 3] = a0; red[wid * 8 + lane * 3 + 1] = a1; if (lane == 0) red[wid * 8 + 2] = a2; }
        bar_cons();
        if (tid < 5) {
            float sum = 0.f;
#pragma unroll
            for (int w = 0; w < 6; w++) sum += red[w * 8 + tid];
            float y = own[24 + tid] + bfr(own[8 + tid] * bfr(sum));
            out[cta * 5 + tid] = __float2bfloat16_rn(y);
        }
        if (cta == 0 && tid == 0) g_epoch = tag;
    }
    TS(14);
}

typedef CUresult (*EncodeFn)(CUtensorMap*, CUtensorMapDataType, cuuint32_t, void*, const cuuint64_t*, const cuuint64_t*,
                             const cuuint32_t*, const cuuint32_t*, CUtensorMapInterleave, CUtensorMapSwizzle,
                             CUtensorMapL2promotion, CUtensorMapFloatOOBfill);

void make_map(EncodeFn enc, CUtensorMap* tm, const void* ptr, uint64_t cols, uint64_t rows, uint32_t box_c, uint32_t box_r,
              CUtensorMapSwizzle sw, CUtensorMapL2promotion prom) {
    cuuint64_t dims[2] = {cols, rows};
    cuuint64_t strides[1] = {cols * 2};
    cuuint32_t box[2] = {box_c, box_r};
    cuuint32_t es[2] = {1, 1};
    enc(tm, CU_TENSOR_MAP_DATA_TYPE_BFLOAT16, 2, const_cast<void*>(ptr), dims, strides, box, es,
        CU_TENSOR_MAP_INTERLEAVE_NONE, sw, prom, CU_TENSOR_MAP_FLOAT_OOB_FILL_NONE);
}

}

extern "C" void kernel_launch(void* const* d_in, const int* in_sizes, int n_in, void* d_out, int out_size) {
    (void)in_sizes; (void)n_in; (void)out_size;
    static EncodeFn enc = nullptr;
    static int num_sms = 0;
    if (!enc) {
        void* fn = nullptr;
        cudaDriverEntryPointQueryResult qr;
        cudaGetDriverEntryPoint("cuTensorMapEncodeTiled", &fn, cudaEnableDefault, &qr);
        enc = (EncodeFn)fn;
        cudaDeviceGetAttribute(&num_sms, cudaDevAttrMultiProcessorCount, 0);
        cudaFuncSetAttribute(fused_decode_kernel, cudaFuncAttributeMaxDynamicSharedMemorySize, SM_TOTAL);
    }
    CUtensorMap tmK, tmV, tmMod, tmWq, tmWo, tmW1, tmW3, tmW2;
    const uint64_t kv_lines = (uint64_t)NH * SK * 3;
    make_map(enc, &tmK, d_in[1], 64, kv_lines, 64, 96, CU_TENSOR_MAP_SWIZZLE_128B, CU_TENSOR_MAP_L2_PROMOTION_L2_128B);
    make_map(enc, &tmV, d_in[2], 64, kv_lines, 64, 96, CU_TENSOR_MAP_SWIZZLE_128B, CU_TENSOR_MAP_L2_PROMOTION_L2_128B);
    make_map(enc, &tmWq, d_in[3], NH * DH, D, 48, 128, CU_TENSOR_MAP_SWIZZLE_NONE, CU_TENSOR_MAP_L2_PROMOTION_L2_128B);
    make_map(enc, &tmWo, d_in[4], D, NH * DH, 64, 48, CU_TENSOR_MAP_SWIZZLE_128B, CU_TENSOR_MAP_L2_PROMOTION_L2_128B);
    make_map(enc, &tmW1, d_in[6], FF, D, 16, 160, CU_TENSOR_MAP_SWIZZLE_32B, CU_TENSOR_MAP_L2_PROMOTION_L2_128B);
    make_map(enc, &tmW3, d_in[7], FF, D, 16, 160, CU_TENSOR_MAP_SWIZZLE_32B, CU_TENSOR_MAP_L2_PROMOTION_L2_128B);
    make_map(enc, &tmW2, d_in[8], D, FF, 64, 16, CU_TENSOR_MAP_SWIZZLE_128B, CU_TENSOR_MAP_L2_PROMOTION_L2_128B);
    make_map(enc, &tmMod, d_in[10], 6 * D, D, 32, 160, CU_TENSOR_MAP_SWIZZLE_64B, CU_TENSOR_MAP_L2_PROMOTION_L2_128B);
    int grid = num_sms < NG * MAXR ? num_sms : NG * MAXR;
    fused_decode_kernel<<<grid, NTHREADS, SM_TOTAL, cudaStreamPerThread>>>(
        tmK, tmV, tmMod, tmWq, tmWo, tmW1, tmW3, tmW2, (const __nv_bfloat16*)d_in[0], (const __nv_bfloat16*)d_in[9],
        (__nv_bfloat16*)d_out);
}
```

```cpp
#include <cuda_runtime.h>
#include <cuda_bf16.h>
#include <cuda.h>
#include <stdint.h>

namespace {

constexpr int D = 640, NH = 32, SK = 8192, DH = 192, FF = 1536;
constexpr int NG = 4;
constexpr int HPG = NH / NG;
constexpr int TILE = 32;
constexpr int TPH = SK / TILE;
constexpr int TICKETS = HPG * TPH;
constexpr int CHUNK = TILE * DH * 2;
#define P_NSLOT 7
#define P_WIN 4
constexpr int NSLOT = P_NSLOT;
constexpr int WIN = P_WIN;
constexpr int MAXR = 40;
constexpr int NTHREADS = 288;
constexpr int NPK = 65;

constexpr int SM_WMOD = 0;
constexpr int SM_WQ = 40960;
constexpr int SM_WO = 0;
constexpr int SM_W1 = 61440;
constexpr int SM_W3 = 81920;
constexpr int SM_W2 = 102400;
constexpr int SM_RING = 122880;
constexpr int SM_MISC = SM_RING + NSLOT * CHUNK;
constexpr int SM_BARS = SM_MISC;
constexpr int SM_META = SM_BARS + 512;
constexpr int SM_Q = SM_META + 64;
constexpr int SM_SC = SM_Q + HPG * DH * 2;
constexpr int SM_H = SM_SC + 1280;
constexpr int SM_X = SM_H + 1280;
constexpr int SM_CB = SM_X + 1280;
constexpr int SM_SB = SM_CB + 1280;
constexpr int SM_OWN = SM_SB + 1280;
constexpr int SM_RED = SM_OWN + 128;
constexpr int SM_MERGE = SM_RED + 2048;
constexpr int SM_STAGE = SM_MERGE + 3200;
constexpr int SM_X2 = SM_STAGE + 2560;
constexpr int SM_OS = SM_X2 + 2560;
constexpr int SM_FIN = SM_OS + 128;
constexpr int SM_TOTAL = SM_FIN + 256;
static_assert(SM_TOTAL <= 232448, "shared memory budget");

constexpr int B_FULL = 0;
constexpr int B_EMPTY = 8;
constexpr int B_MOD = 16;
constexpr int B_WQ = 20;
constexpr int B_WO = 25;
constexpr int B_W1 = 30;
constexpr int B_W3 = 32;
constexpr int B_W2 = 34;
constexpr int B_FLF = 36, B_FLE = 37, B_COMB = 38, B_PRO = 39, B_DUMMY = 40, B_COUNT = 41;
static_assert(NSLOT <= 8, "barrier map");

__device__ unsigned g_epoch;
__device__ unsigned g_ctr[2][NG * 32];
__device__ __align__(128) unsigned long long g_mod[1920];
__device__ __align__(128) unsigned long long g_q[3072];
__device__ __align__(128) uint4 g_part[NH][MAXR][NPK + 1];
__device__ __align__(128) uint4 g_h1[128][128][2];
__device__ __align__(128) uint4 g_x2[128];
__device__ __align__(128) uint4 g_h3[128][96][2];

#define TS(k) do {} while (0)

__device__ __forceinline__ uint32_t smem_u32(const void* p) { return (uint32_t)__cvta_generic_to_shared(p); }
__device__ __forceinline__ void mbar_init(uint32_t bar, uint32_t cnt) {
    asm volatile("mbarrier.init.shared::cta.b64 [%0], %1;" ::"r"(bar), "r"(cnt) : "memory");
}
__device__ __forceinline__ void mbar_expect_tx(uint32_t bar, uint32_t bytes) {
    asm volatile("mbarrier.arrive.expect_tx.shared::cta.b64 _, [%0], %1;" ::"r"(bar), "r"(bytes) : "memory");
}
__device__ __forceinline__ void mbar_arrive(uint32_t bar) {
    asm volatile("mbarrier.arrive.shared::cta.b64 _, [%0];" ::"r"(bar) : "memory");
}
constexpr uint32_t SPIN_LIMIT = 1u << 22;
__device__ __forceinline__ void mbar_wait(uint32_t bar, uint32_t parity) {
    asm volatile(
        "{\n.reg .pred p;\n.reg .u32 c;\nmov.u32 c, 0;\n"
        "LW:\nmbarrier.try_wait.parity.shared::cta.b64 p, [%0], %1;\n@p bra LD;\n"
        "add.u32 c, c, 1;\nsetp.lt.u32 p, c, 0x400000;\n@p bra LW;\ntrap;\nLD:\n}" ::"r"(bar), "r"(parity)
        : "memory");
}
__device__ __forceinline__ void tma2d(uint32_t dst, const CUtensorMap* tm, int c0, int c1, uint32_t bar) {
    asm volatile(
        "cp.async.bulk.tensor.2d.shared::cluster.global.mbarrier::complete_tx::bytes [%0], [%1, {%3, %4}], [%2];" ::"r"(dst),
        "l"(tm), "r"(bar), "r"(c0), "r"(c1)
        : "memory");
}
__device__ __forceinline__ void tma2d_hint(uint32_t dst, const CUtensorMap* tm, int c0, int c1, uint32_t bar, uint64_t pol) {
    asm volatile(
        "cp.async.bulk.tensor.2d.shared::cluster.global.mbarrier::complete_tx::bytes.L2::cache_hint [%0], [%1, {%3, %4}], [%2], %5;" ::"r"(dst),
        "l"(tm), "r"(bar), "r"(c0), "r"(c1), "l"(pol)
        : "memory");
}
__device__ __forceinline__ void prefetch_tm(const CUtensorMap* tm) {
    asm volatile("prefetch.tensormap [%0];" ::"l"(tm) : "memory");
}
__device__ __forceinline__ void ldsm4(uint32_t (&r)[4], uint32_t addr) {
    asm volatile("ldmatrix.sync.aligned.m8n8.x4.shared.b16 {%0,%1,%2,%3}, [%4];"
                 : "=r"(r[0]), "=r"(r[1]), "=r"(r[2]), "=r"(r[3])
                 : "r"(addr)
                 : "memory");
}
__device__ __forceinline__ void ldsm4t(uint32_t (&r)[4], uint32_t addr) {
    asm volatile("ldmatrix.sync.aligned.m8n8.x4.trans.shared.b16 {%0,%1,%2,%3}, [%4];"
                 : "=r"(r[0]), "=r"(r[1]), "=r"(r[2]), "=r"(r[3])
                 : "r"(addr)
                 : "memory");
}
__device__ __forceinline__ void mma16816(float (&d)[4], const uint32_t (&a)[4], uint32_t b0, uint32_t b1) {
    asm volatile(
        "mma.sync.aligned.m16n8k16.row.col.f32.bf16.bf16.f32 {%0,%1,%2,%3}, {%4,%5,%6,%7}, {%8,%9}, {%0,%1,%2,%3};"
        : "+f"(d[0]), "+f"(d[1]), "+f"(d[2]), "+f"(d[3])
        : "r"(a[0]), "r"(a[1]), "r"(a[2]), "r"(a[3]), "r"(b0), "r"(b1));
}
__device__ __forceinline__ void bar_cons() { asm volatile("bar.sync 1, 256;" ::: "memory"); }

__device__ __forceinline__ float bfr(float x) { return __bfloat162float(__float2bfloat16_rn(x)); }
__device__ __forceinline__ uint32_t pack_bf(float lo, float hi) {
    __nv_bfloat162 t = __floats2bfloat162_rn(lo, hi);
    return *reinterpret_cast<uint32_t*>(&t);
}
__device__ __forceinline__ float bf_lo(uint32_t v) { return __uint_as_float(v << 16); }
__device__ __forceinline__ float bf_hi(uint32_t v) { return __uint_as_float(v & 0xffff0000u); }

__device__ __forceinline__ void st_pk8(unsigned long long* p, uint32_t v, uint32_t tag) {
    unsigned long long w = ((unsigned long long)tag << 32) | v;
    asm volatile("st.relaxed.gpu.global.b64 [%0], %1;" ::"l"(p), "l"(w) : "memory");
}
__device__ __forceinline__ unsigned long long ld_raw8(const unsigned long long* p) {
    unsigned long long w;
    asm volatile("ld.relaxed.gpu.global.b64 %0, [%1];" : "=l"(w) : "l"(p) : "memory");
    return w;
}
template <int N>
__device__ __forceinline__ void poll8(const unsigned long long* base, const int (&off)[N], uint32_t (&val)[N], uint32_t tag, bool live = true) {
    unsigned long long w[N];
#pragma unroll
    for (int i = 0; i < N; i++) w[i] = 0;
    uint32_t it = 0;
    while (true) {
        bool ok = true;
#pragma unroll
        for (int i = 0; i < N; i++)
            if (off[i] >= 0 && (uint32_t)(w[i] >> 32) != tag) w[i] = ld_raw8(base + off[i]);
#pragma unroll
        for (int i = 0; i < N; i++) ok = ok && (off[i] < 0 || (uint32_t)(w[i] >> 32) == tag);
        if (ok || !live) break;
        if (++it > SPIN_LIMIT) __trap();
    }
#pragma unroll
    for (int i = 0; i < N; i++) val[i] = (uint32_t)w[i];
}
__device__ __forceinline__ void st_pk16(uint4* p, uint32_t a, uint32_t b, uint32_t c, uint32_t tag) {
    asm volatile(
        "{\n.reg .b128 t;\n.reg .b64 lo, hi;\nmov.b64 lo, {%1, %2};\nmov.b64 hi, {%3, %4};\nmov.b128 t, {lo, hi};\n"
        "st.relaxed.gpu.global.b128 [%0], t;\n}" ::"l"(p), "r"(a), "r"(b), "r"(c), "r"(tag)
        : "memory");
}
__device__ __forceinline__ uint4 ld_raw16(const uint4* p) {
    uint4 v;
    asm volatile(
        "{\n.reg .b128 t;\n.reg .b64 lo, hi;\nld.relaxed.gpu.global.b128 t, [%4];\nmov.b128 {lo, hi}, t;\n"
        "mov.b64 {%0, %1}, lo;\nmov.b64 {%2, %3}, hi;\n}"
        : "=r"(v.x), "=r"(v.y), "=r"(v.z), "=r"(v.w)
        : "l"(p)
        : "memory");
    return v;
}
__device__ __forceinline__ uint4 poll16(const uint4* p, uint32_t tag, bool live) {
    uint4 v = ld_raw16(p);
    uint32_t it = 0;
    while (live && v.w != tag) {
        v = ld_raw16(p);
        if (++it > SPIN_LIMIT) __trap();
    }
    return v;
}
__device__ __forceinline__ float ex2(float x) {
    float y;
    asm("ex2.approx.ftz.f32 %0, %1;" : "=f"(y) : "f"(x));
    return y;
}
__device__ __forceinline__ float fsqrt(float x) {
    float y;
    asm("sqrt.approx.f32 %0, %1;" : "=f"(y) : "f"(x));
    return y;
}
constexpr float LOG2E = 1.4426950408889634f;
__device__ __forceinline__ float silu(float a) { return __fdividef(a, 1.0f + ex2(-a * LOG2E)); }
__device__ __forceinline__ float warp_sum(float v) {
#pragma unroll
    for (int o = 16; o > 0; o >>= 1) v += __shfl_xor_sync(0xffffffffu, v, o);
    return v;
}

__device__ __forceinline__ void ln_stats(const float (&v)[20], float& mean_b, float& den_b) {
    float s = 0.f;
#pragma unroll
    for (int i = 0; i < 20; i++) s += v[i];
    s = warp_sum(s);
    float mean = s * (1.0f / 640.0f);
    float q = 0.f;
#pragma unroll
    for (int i = 0; i < 20; i++) { float d = v[i] - mean; q += d * d; }
    q = warp_sum(q);
    float var_b = bfr(q * (1.0f / 640.0f));
    mean_b = bfr(mean);
    den_b = bfr(fsqrt(bfr(var_b + 1e-5f)));
}

struct Window {
    uint32_t bar[WIN];
    uint32_t par[WIN];
    __device__ __forceinline__ void init(uint32_t dummy) {
#pragma unroll
        for (int i = 0; i < WIN; i++) { bar[i] = dummy; par[i] = 1; }
    }
    __device__ __forceinline__ void push(uint32_t b, uint32_t p) {
        mbar_wait(bar[0], par[0]);
#pragma unroll
        for (int i = 0; i + 1 < WIN; i++) { bar[i] = bar[i + 1]; par[i] = par[i + 1]; }
        bar[WIN - 1] = b; par[WIN - 1] = p;
    }
};

__global__ void __launch_bounds__(NTHREADS, 1)
fused_decode_kernel(const __grid_constant__ CUtensorMap tmK, const __grid_constant__ CUtensorMap tmV,
                    const __grid_constant__ CUtensorMap tmMod, const __grid_constant__ CUtensorMap tmWq,
                    const __grid_constant__ CUtensorMap tmWo, const __grid_constant__ CUtensorMap tmW1,
                    const __grid_constant__ CUtensorMap tmW3, const __grid_constant__ CUtensorMap tmW2,
                    const __nv_bfloat16* __restrict__ x_in, const __nv_bfloat16* __restrict__ c_in,
                    __nv_bfloat16* __restrict__ out) {
    extern __shared__ __align__(1024) uint8_t smem[];
    const uint32_t sb = smem_u32(smem);
    const int tid = threadIdx.x, wid = tid >> 5, lane = tid & 31;
    const int cta = blockIdx.x, G = gridDim.x;
    const int grp = cta % NG;
    const uint32_t bars = sb + SM_BARS;
    auto BAR = [&](int i) { return bars + 8u * i; };
    volatile uint32_t* meta = reinterpret_cast<volatile uint32_t*>(smem + SM_META);

    if (wid == 8) {
        Window win;
        unsigned epoch = 0;
        if (lane == 0) {
            TS(0);
            if (sb & 1023u) __trap();
            asm volatile("ld.relaxed.gpu.global.u32 %0, [%1];" : "=r"(epoch) : "l"(&g_epoch) : "memory");
            prefetch_tm(&tmMod); prefetch_tm(&tmWq); prefetch_tm(&tmK); prefetch_tm(&tmV);
#pragma unroll 1
            for (int i = 0; i < B_COUNT; i++) {
                int cnt = (i >= B_EMPTY && i < B_MOD) ? 2 : (i == B_FLF ? 4 : 1);
                mbar_init(BAR(i), cnt);
            }
            asm volatile("fence.mbarrier_init.release.cluster;" ::: "memory");
            asm volatile("fence.proxy.async.shared::cta;" ::: "memory");
            win.init(BAR(B_DUMMY));
            if (cta < 120) {
#pragma unroll 1
                for (int i = 0; i < 4; i++) {
                    win.push(BAR(B_MOD + i), 0);
                    mbar_expect_tx(BAR(B_MOD + i), 10240);
                    tma2d(sb + SM_WMOD + i * 10240, &tmMod, cta * 32, i * 160, BAR(B_MOD + i));
                }
            }
        }
        __syncwarp();
        __syncthreads();
        if (lane == 0) {
            prefetch_tm(&tmWo); prefetch_tm(&tmW1); prefetch_tm(&tmW3); prefetch_tm(&tmW2);
            unsigned* ctr = &g_ctr[epoch & 1][grp * 32];
            if (cta == 0) {
                for (int g = 0; g < NG; g++) g_ctr[(epoch + 1) & 1][g * 32] = 0;
            }
            unsigned t_cur = atomicAdd(ctr, 1);
            unsigned t_nxt = atomicAdd(ctr, 1);
            if (cta < 128) {
#pragma unroll 1
                for (int i = 0; i < 5; i++) {
                    win.push(BAR(B_WQ + i), 0);
                    mbar_expect_tx(BAR(B_WQ + i), 12288);
                    tma2d(sb + SM_WQ + i * 12288, &tmWq, cta * 48, i * 128, BAR(B_WQ + i));
                }
            }
            uint64_t pol;
            asm volatile("createpolicy.fractional.L2::evict_first.b64 %0, 1.0;" : "=l"(pol));
            int s = 0; uint32_t par = 0;
            int ntiles = 0;
#pragma unroll 1
            while (t_cur < (unsigned)TICKETS) {
                ntiles++;
                unsigned t = t_cur;
                t_cur = t_nxt;
                t_nxt = (t_cur < (unsigned)TICKETS) ? atomicAdd(ctr, 1) : (unsigned)TICKETS;
                int pos = t / TPH, tile = t % TPH;
                int line0 = ((grp * HPG + pos) * SK + tile * TILE) * 3;
#pragma unroll 1
                for (int kv = 0; kv < 2; kv++) {
                    win.push(BAR(B_FULL + s), par);
                    mbar_wait(BAR(B_EMPTY + s), par ^ 1);
                    meta[s] = pos;
                    mbar_expect_tx(BAR(B_FULL + s), CHUNK);
                    tma2d_hint(sb + SM_RING + s * CHUNK, kv ? &tmV : &tmK, 0, line0, BAR(B_FULL + s), pol);
                    if (++s == NSLOT) { s = 0; par ^= 1; }
                }
            }
            TS(5);
#pragma unroll 1
            for (int e = 0; e < 2; e++) {
                mbar_wait(BAR(B_EMPTY + s), par ^ 1);
                meta[s] = HPG;
                mbar_arrive(BAR(B_FULL + s));
                if (++s == NSLOT) { s = 0; par ^= 1; }
                if (++s == NSLOT) { s = 0; par ^= 1; }
            }
            if (cta < 128) {
                mbar_wait(BAR(B_PRO), 0);
#pragma unroll 1
                for (int i = 0; i < 5; i++) {
                    win.push(BAR(B_WO + i), 0);
                    mbar_expect_tx(BAR(B_WO + i), 12288);
                    tma2d(sb + SM_WO + (2 * i) * 6144, &tmWo, (2 * i) * 64, cta * 48, BAR(B_WO + i));
                    tma2d(sb + SM_WO + (2 * i + 1) * 6144, &tmWo, (2 * i + 1) * 64, cta * 48, BAR(B_WO + i));
                }
                if (cta < 96) {
#pragma unroll 1
                    for (int i = 0; i < 4; i++) {
                        const int m = i & 1, hf = i >> 1;
                        const uint32_t bar = BAR((m ? B_W3 : B_W1) + hf);
                        const uint32_t dst = sb + (m ? SM_W3 : SM_W1) + hf * 10240;
                        const CUtensorMap* tm = m ? &tmW3 : &tmW1;
                        win.push(bar, 0);
                        mbar_expect_tx(bar, 10240);
                        tma2d(dst, tm, cta * 16, hf * 320, bar);
                        tma2d(dst + 5120, tm, cta * 16, hf * 320 + 160, bar);
                    }
#pragma unroll 1
                    for (int i = 0; i < 2; i++) {
                        win.push(BAR(B_W2 + i), 0);
                        mbar_expect_tx(BAR(B_W2 + i), 10240);
#pragma unroll 1
                        for (int b = 0; b < 5; b++)
                            tma2d(sb + SM_W2 + (5 * i + b) * 2048, &tmW2, (5 * i + b) * 64, cta * 16, BAR(B_W2 + i));
                    }
                }
            }
            TS(6);
        }
        return;
    }

    const int g4 = lane >> 2, j4 = lane & 3, mi = lane >> 3, l8 = lane & 7;
    uint32_t* sc32 = reinterpret_cast<uint32_t*>(smem + SM_SC);
    uint32_t* h32 = reinterpret_cast<uint32_t*>(smem + SM_H);
    uint32_t* x32 = reinterpret_cast<uint32_t*>(smem + SM_X);
    uint32_t* q32 = reinterpret_cast<uint32_t*>(smem + SM_Q);
    float* red = reinterpret_cast<float*>(smem + SM_RED);
    float* stage = reinterpret_cast<float*>(smem + SM_STAGE);
    float* own = reinterpret_cast<float*>(smem + SM_OWN);

    {
        const uint32_t* cg = reinterpret_cast<const uint32_t*>(c_in);
        const uint32_t* xg = reinterpret_cast<const uint32_t*>(x_in);
        uint32_t c0 = cg[tid], x0 = xg[tid], c1 = 0, x1 = 0;
        if (tid < 64) { c1 = cg[256 + tid]; x1 = xg[256 + tid]; }
        unsigned epoch = 0;
        if (tid == 0) asm volatile("ld.relaxed.gpu.global.u32 %0, [%1];" : "=r"(epoch) : "l"(&g_epoch) : "memory");
        sc32[tid] = pack_bf(silu(bf_lo(c0)), silu(bf_hi(c0))); x32[tid] = x0;
        if (tid < 64) { sc32[256 + tid] = pack_bf(silu(bf_lo(c1)), silu(bf_hi(c1))); x32[256 + tid] = x1; }
        if (tid == 0) meta[8] = epoch + 1;
    }
    __syncthreads();
    const uint32_t tag = meta[8];

    float mean_x = 0.f, den_x = 1.f;
    if (cta < 128) {
        float xv[20];
#pragma unroll
        for (int i = 0; i < 10; i++) { uint32_t v = x32[lane + 32 * i]; xv[2 * i] = bf_lo(v); xv[2 * i + 1] = bf_hi(v); }
        ln_stats(xv, mean_x, den_x);
    }

    if (cta < 120) {
        float acc[2][4] = {};
        mbar_wait(BAR(B_MOD + (wid >> 1)), 0);
        const uint32_t base = sb + SM_WMOD + (wid >> 1) * 10240;
#pragma unroll
        for (int ks = 0; ks < 5; ks++) {
            const int rl = (wid & 1) * 80 + ks * 16;
            const int r = rl + l8 + 8 * (mi >> 1);
            const int r0 = wid * 80 + ks * 16;
            uint32_t b0 = sc32[(r0 >> 1) + j4], b1 = sc32[(r0 >> 1) + 4 + j4];
#pragma unroll
            for (int mt = 0; mt < 2; mt++) {
                uint32_t a[4];
                int cc = 2 * mt + (mi & 1);
                ldsm4t(a, base + r * 64 + ((cc ^ ((r >> 1) & 3)) << 4));
                mma16816(acc[mt], a, b0, b1);
            }
        }
        if (j4 == 0) {
#pragma unroll
            for (int mt = 0; mt < 2; mt++) { red[wid * 64 + mt * 16 + g4] = acc[mt][0]; red[wid * 64 + mt * 16 + 8 + g4] = acc[mt][2]; }
        }
        bar_cons();
        if (wid == 0) {
            float v = 0.f;
#pragma unroll
            for (int w = 0; w < 8; w++) v += red[w * 64 + lane];
            float o = __shfl_down_sync(0xffffffffu, v, 1);
            if (!(lane & 1)) st_pk8(&g_mod[cta * 16 + (lane >> 1)], pack_bf(v, o), tag);
        }
    }
    TS(1);

    if (cta < 128) {
        {
            const int off[4] = {tid, 320 + tid, tid < 64 ? 256 + tid : -1, tid < 64 ? 576 + tid : -1};
            uint32_t val[4];
            poll8<4>(g_mod, off, val, tag);
            const float rden = den_x;
#pragma unroll
            for (int rep = 0; rep < 2; rep++) {
                int p = tid + rep * 256;
                if (p < 320) {
                    uint32_t sa = val[2 * rep], ca = val[2 * rep + 1];
                    uint32_t xx = x32[p];
                    float n0 = bfr(__fdividef(bfr(bf_lo(xx) - mean_x), rden)), n1 = bfr(__fdividef(bfr(bf_hi(xx) - mean_x), rden));
                    float h0 = bfr(n0 * bfr(1.0f + bf_lo(ca))) + bf_lo(sa);
                    float h1 = bfr(n1 * bfr(1.0f + bf_hi(ca))) + bf_hi(sa);
                    h32[p] = pack_bf(h0, h1);
                }
            }
        }
        bar_cons();
        TS(2);
        float acc[3][4] = {};
#pragma unroll
        for (int ks = 0; ks < 5; ks++) {
            const int r0 = wid * 80 + ks * 16;
            const int ch = r0 >> 7;
            mbar_wait(BAR(B_WQ + ch), 0);
            const int r = (r0 & 127) + l8 + 8 * (mi >> 1);
            uint32_t b0 = h32[(r0 >> 1) + j4], b1 = h32[(r0 >> 1) + 4 + j4];
#pragma unroll
            for (int mt = 0; mt < 3; mt++) {
                uint32_t a[4];
                ldsm4t(a, sb + SM_WQ + ch * 12288 + r * 96 + ((2 * mt + (mi & 1)) << 4));
                mma16816(acc[mt], a, b0, b1);
            }
        }
        if (j4 == 0) {
#pragma unroll
            for (int mt = 0; mt < 3; mt++) { red[wid * 64 + mt * 16 + g4] = acc[mt][0]; red[wid * 64 + mt * 16 + 8 + g4] = acc[mt][2]; }
        }
        bar_cons();
        if (tid < 64) {
            float v = 0.f;
            if (tid < 48) {
#pragma unroll
                for (int w = 0; w < 8; w++) v += red[w * 64 + tid];
            }
            float o = __shfl_down_sync(0xffffffffu, v, 1);
            if (tid < 48 && !(tid & 1)) st_pk8(&g_q[cta * 24 + (tid >> 1)], pack_bf(v, o), tag);
        }
        TS(3);
    }
    {
        const int off[3] = {tid, tid + 256, tid + 512};
        uint32_t val[3];
        poll8<3>(g_q + grp * (HPG * DH / 2), off, val, tag);
        q32[tid] = val[0]; q32[tid + 256] = val[1]; q32[tid + 512] = val[2];
    }
    bar_cons();
    if (tid == 0) mbar_arrive(BAR(B_PRO));
    TS(4);

    bool live = true;
    if (wid < 4) {
        const int pair = wid >> 1, half = wid & 1;
        const int rowK = half * 16 + l8 + 8 * (mi & 1), hiK = mi >> 1;
        const int rowV = half * 16 + l8 + 8 * (mi >> 1), hiV = mi & 1;
        float acc[12][4];
#pragma unroll
        for (int i = 0; i < 12; i++) { acc[i][0] = acc[i][1] = acc[i][2] = acc[i][3] = 0.f; }
        float m_run = -3.402823466e38f, l_run = 0.f;
        uint32_t qf[12][2];
#pragma unroll
        for (int i = 0; i < 12; i++) { qf[i][0] = qf[i][1] = 0; }
        int cur = -1, flushed = 0;
        int s = 2 * pair; uint32_t par = 0;
        float* mb = reinterpret_cast<float*>(smem + SM_MERGE) + wid * 200;
#pragma unroll 1
        while (true) {
            mbar_wait(BAR(B_FULL + s), par);
            const int pos = (int)meta[s];
            if (pos != cur) {
#pragma unroll 1
                while (flushed < pos) {
                    if (flushed != cur) {
#pragma unroll
                        for (int i = 0; i < 12; i++) { acc[i][0] = acc[i][1] = acc[i][2] = acc[i][3] = 0.f; }
                        m_run = -3.402823466e38f; l_run = 0.f;
                    }
                    mbar_wait(BAR(B_FLE), (flushed & 1) ^ 1);
                    float v[24];
#pragma unroll
                    for (int i = 0; i < 12; i++) { v[2 * i] = acc[i][0] + acc[i][1]; v[2 * i + 1] = acc[i][2] + acc[i][3]; }
                    float u[12];
                    const bool o1 = j4 & 1, o2 = j4 & 2;
#pragma unroll
                    for (int i = 0; i < 12; i++) {
                        float send = o1 ? v[i] : v[i + 12], keep = o1 ? v[i + 12] : v[i];
                        u[i] = keep + __shfl_xor_sync(0xffffffffu, send, 1);
                    }
#pragma unroll
                    for (int i = 0; i < 6; i++) {
                        float send = o2 ? u[i] : u[i + 6], keep = o2 ? u[i + 6] : u[i];
                        float w = keep + __shfl_xor_sync(0xffffffffu, send, 2);
                        int idx = (o1 ? 12 : 0) + (o2 ? 6 : 0) + i;
                        mb[4 + 16 * (idx >> 1) + 8 * (idx & 1) + g4] = w;
                    }
                    float l = l_run;
                    l += __shfl_xor_sync(0xffffffffu, l, 4);
                    l += __shfl_xor_sync(0xffffffffu, l, 8);
                    l += __shfl_xor_sync(0xffffffffu, l, 16);
                    if (lane == 0) { mb[0] = m_run; mb[1] = l; }
                    __syncwarp();
                    if (lane == 0) mbar_arrive(BAR(B_FLF));
                    flushed++;
                    cur = -1;
                }
                if (pos >= HPG) break;
                cur = pos;
#pragma unroll
                for (int i = 0; i < 12; i++) { acc[i][0] = acc[i][1] = acc[i][2] = acc[i][3] = 0.f; }
                m_run = -3.402823466e38f; l_run = 0.f;
#pragma unroll
                for (int ks = 0; ks < 12; ks++) {
                    qf[ks][0] = q32[pos * 96 + ks * 8 + j4];
                    qf[ks][1] = q32[pos * 96 + ks * 8 + 4 + j4];
                }
            }
            const uint32_t kb = sb + SM_RING + s * CHUNK;
            float sc0[4] = {0.f, 0.f, 0.f, 0.f}, sc1[4] = {0.f, 0.f, 0.f, 0.f}, sc2[4] = {0.f, 0.f, 0.f, 0.f};
#pragma unroll
            for (int kk = 0; kk < 4; kk++) {
                uint32_t a[4];
                const int c = 2 * kk + hiK;
                const int ln = rowK * 3;
                ldsm4(a, kb + (ln + 0) * 128 + ((c ^ ((ln + 0) & 7)) << 4));
                mma16816(sc0, a, qf[kk][0], qf[kk][1]);
                ldsm4(a, kb + (ln + 1) * 128 + ((c ^ ((ln + 1) & 7)) << 4));
                mma16816(sc1, a, qf[4 + kk][0], qf[4 + kk][1]);
                ldsm4(a, kb + (ln + 2) * 128 + ((c ^ ((ln + 2) & 7)) << 4));
                mma16816(sc2, a, qf[8 + kk][0], qf[8 + kk][1]);
            }
            __syncwarp();
            if (lane == 0) mbar_arrive(BAR(B_EMPTY + s));
            int sv = s + 1; uint32_t parv = par;
            if (sv == NSLOT) { sv = 0; parv ^= 1; }
            const float scale = 0.07216878364870322f;
            float s0 = bfr(bfr(sc0[0] + sc1[0] + sc2[0]) * scale);
            float s1 = bfr(bfr(sc0[2] + sc1[2] + sc2[2]) * scale);
            float tm = fmaxf(s0, s1);
            tm = fmaxf(tm, __shfl_xor_sync(0xffffffffu, tm, 4));
            tm = fmaxf(tm, __shfl_xor_sync(0xffffffffu, tm, 8));
            tm = fmaxf(tm, __shfl_xor_sync(0xffffffffu, tm, 16));
            if (tm > m_run) {
                float alpha = ex2((m_run - tm) * LOG2E);
                l_run *= alpha;
#pragma unroll
                for (int i = 0; i < 12; i++) { acc[i][0] *= alpha; acc[i][1] *= alpha; acc[i][2] *= alpha; acc[i][3] *= alpha; }
                m_run = tm;
            }
            float p0 = ex2((s0 - m_run) * LOG2E);
            float p1 = ex2((s1 - m_run) * LOG2E);
            l_run += p0 + p1;
            uint32_t b0 = 0, b1 = 0;
            if (j4 == (g4 >> 1)) {
                uint32_t e0 = pack_bf(p0, 0.f) & 0xffffu, e1 = pack_bf(p1, 0.f) & 0xffffu;
                b0 = (g4 & 1) ? (e0 << 16) : e0;
                b1 = (g4 & 1) ? (e1 << 16) : e1;
            }
            mbar_wait(BAR(B_FULL + sv), parv);
            const uint32_t vb = sb + SM_RING + sv * CHUNK;
#pragma unroll
            for (int t = 0; t < 3; t++) {
                const int ln = rowV * 3 + t;
#pragma unroll
                for (int kk = 0; kk < 4; kk++) {
                    uint32_t a[4];
                    const int c = 2 * kk + hiV;
                    ldsm4t(a, vb + ln * 128 + ((c ^ (ln & 7)) << 4));
                    mma16816(acc[t * 4 + kk], a, b0, b1);
                }
            }
            __syncwarp();
            if (lane == 0) mbar_arrive(BAR(B_EMPTY + sv));
            s += 4;
            if (s >= NSLOT) { s -= NSLOT; par ^= 1; }
        }
        TS(7);
    } else if (wid == 4) {
        const float* mb = reinterpret_cast<const float*>(smem + SM_MERGE);
        const int rank = cta / NG;
        const int own_pos = (cta < 128) ? ((cta >> 2) % HPG) : -1;
#pragma unroll 1
        for (int f = 0; f < HPG; f++) {
            mbar_wait(BAR(B_FLF), f & 1);
            float m0 = mb[0], m1 = mb[200], m2 = mb[400], m3 = mb[600];
            float M = fmaxf(fmaxf(m0, m1), fmaxf(m2, m3));
            float w0 = ex2((m0 - M) * LOG2E), w1 = ex2((m1 - M) * LOG2E);
            float w2 = ex2((m2 - M) * LOG2E), w3 = ex2((m3 - M) * LOG2E);
            uint4* dst = &g_part[grp * HPG + f][rank][0];
            float o[6];
#pragma unroll
            for (int i = 0; i < 6; i++) {
                int d = 4 + (i < 3 ? 3 * lane + i : 96 + 3 * lane + (i - 3));
                o[i] = w0 * mb[d] + w1 * mb[200 + d] + w2 * mb[400 + d] + w3 * mb[600 + d];
            }
            float L = w0 * mb[1] + w1 * mb[201] + w2 * mb[401] + w3 * mb[601];
            st_pk16(dst + 1 + lane, __float_as_uint(o[0]), __float_as_uint(o[1]), __float_as_uint(o[2]), tag);
            st_pk16(dst + 33 + lane, __float_as_uint(o[3]), __float_as_uint(o[4]), __float_as_uint(o[5]), tag);
            if (lane == 0) st_pk16(dst, __float_as_uint(M), __float_as_uint(L), 0u, tag);
            __syncwarp();
            if (lane == 0) {
                mbar_arrive(BAR(B_FLE));
                if (f == own_pos) mbar_arrive(BAR(B_COMB));
            }
        }
        TS(8);
    } else if (wid == 5) {
        if (cta < 128) {
            const int h = cta >> 2, js = cta & 3;
            const int gh = h / HPG;
            const int np = (G - gh + NG - 1) / NG;
            const uint4* src = &g_part[h][0][0];
            const int k = lane & 15, rh = lane >> 4;
#pragma unroll 1
            for (int pass = 0; pass < 2; pass++) {
                const bool lv = pass == 1;
                if (lv) mbar_wait(BAR(B_COMB), 0);
                uint4 hd[2], dv[MAXR / 2];
                hd[0].w = hd[1].w = tag - 1;
#pragma unroll
                for (int i = 0; i < MAXR / 2; i++) dv[i].w = tag - 1;
                uint32_t it = 0;
                while (true) {
                    bool ok = true;
#pragma unroll
                    for (int i = 0; i < 2; i++)
                        if (lane + 32 * i < np && hd[i].w != tag) hd[i] = ld_raw16(src + (lane + 32 * i) * (NPK + 1));
#pragma unroll
                    for (int i = 0; i < MAXR / 2; i++)
                        if (2 * i + rh < np && dv[i].w != tag) dv[i] = ld_raw16(src + (2 * i + rh) * (NPK + 1) + 1 + 16 * js + k);
#pragma unroll
                    for (int i = 0; i < 2; i++) ok = ok && (lane + 32 * i >= np || hd[i].w == tag);
#pragma unroll
                    for (int i = 0; i < MAXR / 2; i++) ok = ok && (2 * i + rh >= np || dv[i].w == tag);
                    if (__all_sync(0xffffffffu, ok) || !lv) break;
                    if (++it > SPIN_LIMIT) __trap();
                }
                float ma = lane < np ? __uint_as_float(hd[0].x) : -3.402823466e38f;
                float mbv = lane + 32 < np ? __uint_as_float(hd[1].x) : -3.402823466e38f;
                float M = fmaxf(ma, mbv);
#pragma unroll
                for (int o = 16; o > 0; o >>= 1) M = fmaxf(M, __shfl_xor_sync(0xffffffffu, M, o));
                float wa = lane < np ? ex2((ma - M) * LOG2E) : 0.f;
                float wb = lane + 32 < np ? ex2((mbv - M) * LOG2E) : 0.f;
                float L = warp_sum((lane < np ? wa * __uint_as_float(hd[0].y) : 0.f) + (lane + 32 < np ? wb * __uint_as_float(hd[1].y) : 0.f));
                float a0 = 0.f, a1 = 0.f, a2 = 0.f;
#pragma unroll
                for (int i = 0; i < MAXR / 2; i++) {
                    float w = __shfl_sync(0xffffffffu, (2 * i < 32) ? wa : wb, (2 * i + rh) & 31);
                    if (2 * i + rh < np) {
                        a0 += w * __uint_as_float(dv[i].x); a1 += w * __uint_as_float(dv[i].y); a2 += w * __uint_as_float(dv[i].z);
                    }
                }
                a0 += __shfl_xor_sync(0xffffffffu, a0, 16);
                a1 += __shfl_xor_sync(0xffffffffu, a1, 16);
                a2 += __shfl_xor_sync(0xffffffffu, a2, 16);
                if (lv && lane < 16) {
                    __nv_bfloat16* os = reinterpret_cast<__nv_bfloat16*>(smem + SM_OS);
                    float inv = __fdividef(1.0f, L);
                    os[3 * k] = __float2bfloat16_rn(a0 * inv);
                    os[3 * k + 1] = __float2bfloat16_rn(a1 * inv);
                    os[3 * k + 2] = __float2bfloat16_rn(a2 * inv);
                }
            }
        }
        TS(9);
    } else {
        if (cta < 128) {
            const int t = tid - 192;
            uint32_t* cb32 = reinterpret_cast<uint32_t*>(smem + SM_CB);
            uint32_t* sb32 = reinterpret_cast<uint32_t*>(smem + SM_SB);
            const int col = cta * 5 + t;
            int off[12];
            uint32_t val[12];
#pragma unroll
            for (int rep = 0; rep < 5; rep++) { off[2 * rep] = 960 + t + 64 * rep; off[2 * rep + 1] = 1280 + t + 64 * rep; }
            off[10] = t < 5 ? (1280 + col) >> 1 : -1;
            off[11] = t < 5 ? (3200 + col) >> 1 : -1;
            poll8<12>(g_mod, off, val, tag);
#pragma unroll
            for (int rep = 0; rep < 5; rep++) {
                sb32[t + 64 * rep] = val[2 * rep];
                cb32[t + 64 * rep] = pack_bf(1.0f + bf_lo(val[2 * rep + 1]), 1.0f + bf_hi(val[2 * rep + 1]));
            }
            if (t < 5) {
                own[t] = (col & 1) ? bf_hi(val[10]) : bf_lo(val[10]);
                own[8 + t] = (col & 1) ? bf_hi(val[11]) : bf_lo(val[11]);
                uint32_t xx = x32[col >> 1];
                own[16 + t] = (col & 1) ? bf_hi(xx) : bf_lo(xx);
            }
        }
        live = false;
    }
    if (cta >= 128) return;

#pragma unroll 1
    while (true) {
        if (live) bar_cons();
        if (live) TS(10);
        {
            const uint32_t* os32 = reinterpret_cast<const uint32_t*>(smem + SM_OS);
            float acc[5][4] = {};
            uint32_t b[3][2];
#pragma unroll
            for (int ks = 0; ks < 3; ks++) { b[ks][0] = os32[ks * 8 + j4]; b[ks][1] = os32[ks * 8 + 4 + j4]; }
#pragma unroll
            for (int i = 0; i < 5; i++) {
                const int mt = wid * 5 + i;
                const int box = mt >> 2;
                if (live) mbar_wait(BAR(B_WO + (box >> 1)), 0);
                const int cc = 2 * (mt & 3) + (mi & 1);
#pragma unroll
                for (int ks = 0; ks < 3; ks++) {
                    const int r = ks * 16 + l8 + 8 * (mi >> 1);
                    uint32_t a[4];
                    ldsm4t(a, sb + SM_WO + box * 6144 + r * 128 + ((cc ^ (r & 7)) << 4));
                    mma16816(acc[i], a, b[ks][0], b[ks][1]);
                }
            }
            if (live && j4 == 0) {
#pragma unroll
                for (int i = 0; i < 5; i++) { stage[(wid * 5 + i) * 16 + g4] = acc[i][0]; stage[(wid * 5 + i) * 16 + 8 + g4] = acc[i][2]; }
            }
            if (live) bar_cons();
            const int o = tid >> 1, k = tid & 1;
            const float* sp = stage + o * 5 + k * 3;
            float v0 = sp[0], v1 = sp[1], v2 = k ? 0.f : sp[2];
            if (live) st_pk16(&g_h1[o][cta][k], __float_as_uint(v0), __float_as_uint(v1), __float_as_uint(v2), tag);
        }
        if (live) TS(11);
        {
            uint4 v = poll16(&g_h1[cta][tid >> 1][tid & 1], tag, live);
            float a0 = __uint_as_float(v.x), a1 = __uint_as_float(v.y), a2 = __uint_as_float(v.z);
#pragma unroll
            for (int o = 2; o <= 16; o <<= 1) {
                a0 += __shfl_xor_sync(0xffffffffu, a0, o);
                a1 += __shfl_xor_sync(0xffffffffu, a1, o);
                a2 += __shfl_xor_sync(0xffffffffu, a2, o);
            }
            if (live && lane < 2) { red[wid * 8 + lane * 3] = a0; red[wid * 8 + lane * 3 + 1] = a1; if (lane == 0) red[wid * 8 + 2] = a2; }
            if (live) bar_cons();
            if (live) TS(12);
            if (wid == 0 || !live) {
                float sum = 0.f;
                const int l5 = lane < 5 ? lane : 0;
#pragma unroll
                for (int w = 0; w < 8; w++) sum += red[w * 8 + l5];
                float x2 = bfr(own[16 + l5] + bfr(own[l5] * bfr(sum)));
                if (live && lane < 5) own[24 + lane] = x2;
                float y1 = __shfl_sync(0xffffffffu, x2, 1), y2 = __shfl_sync(0xffffffffu, x2, 2);
                float y3 = __shfl_sync(0xffffffffu, x2, 3), y4 = __shfl_sync(0xffffffffu, x2, 4);
                if (live && lane == 0) st_pk16(&g_x2[cta], pack_bf(x2, y1), pack_bf(y2, y3), pack_bf(y4, 0.f), tag);
            }
        }
        if (live) TS(13);
        if (cta < 96) {
            float* x2s = reinterpret_cast<float*>(smem + SM_X2);
            if (tid < 128 || !live) {
                uint4 v = poll16(&g_x2[tid & 127], tag, live);
                float* d = x2s + (tid & 127) * 5;
                if (live) { d[0] = bf_lo(v.x); d[1] = bf_hi(v.x); d[2] = bf_lo(v.y); d[3] = bf_hi(v.y); d[4] = bf_lo(v.z); }
            }
            if (live) bar_cons();
            if (live) TS(14);
            float xv[20];
#pragma unroll
            for (int i = 0; i < 20; i++) xv[i] = x2s[lane + 32 * i];
            float mean_b, den_b;
            ln_stats(xv, mean_b, den_b);
            const uint32_t* cb32 = reinterpret_cast<const uint32_t*>(smem + SM_CB);
            const uint32_t* sb32 = reinterpret_cast<const uint32_t*>(smem + SM_SB);
#pragma unroll
            for (int rep = 0; rep < 2; rep++) {
                const int p = lane + 32 * rep;
                if (p < 40) {
                    int pp = wid * 40 + p;
                    float v0 = x2s[2 * pp], v1 = x2s[2 * pp + 1];
                    uint32_t cv = cb32[pp], sv = sb32[pp];
                    float n0 = bfr(__fdividef(bfr(v0 - mean_b), den_b)), n1 = bfr(__fdividef(bfr(v1 - mean_b), den_b));
                    uint32_t hv = pack_bf(bfr(n0 * bf_lo(cv)) + bf_lo(sv), bfr(n1 * bf_hi(cv)) + bf_hi(sv));
                    if (live) h32[pp] = hv;
                }
            }
            __syncwarp();
            float ag[4] = {}, au[4] = {};
            if (live) { mbar_wait(BAR(B_W1 + (wid >> 2)), 0); mbar_wait(BAR(B_W3 + (wid >> 2)), 0); }
#pragma unroll
            for (int ks = 0; ks < 5; ks++) {
                const int r0 = wid * 80 + ks * 16;
                const int r = r0 + l8 + 8 * (mi >> 1);
                uint32_t b0 = h32[(r0 >> 1) + j4], b1 = h32[(r0 >> 1) + 4 + j4];
                const uint32_t off = r * 32 + (((mi & 1) ^ ((r >> 2) & 1)) << 4);
                uint32_t a[4];
                ldsm4t(a, sb + SM_W1 + off);
                mma16816(ag, a, b0, b1);
                ldsm4t(a, sb + SM_W3 + off);
                mma16816(au, a, b0, b1);
            }
            if (live && j4 == 0) {
                red[wid * 64 + g4] = ag[0]; red[wid * 64 + 8 + g4] = ag[2];
                red[wid * 64 + 16 + g4] = au[0]; red[wid * 64 + 24 + g4] = au[2];
            }
            if (live) bar_cons();
            if (live) TS(15);
            float v = 0.f;
#pragma unroll
            for (int w = 0; w < 8; w++) v += red[w * 64 + lane];
            v = bfr(v);
            float up = __shfl_down_sync(0xffffffffu, v, 16);
            float hact = bfr(bfr(silu(v)) * up);
            float e0 = __shfl_sync(0xffffffffu, hact, 2 * j4), e1 = __shfl_sync(0xffffffffu, hact, 2 * j4 + 1);
            float e2 = __shfl_sync(0xffffffffu, hact, 2 * j4 + 8), e3 = __shfl_sync(0xffffffffu, hact, 2 * j4 + 9);
            const uint32_t b0 = pack_bf(e0, e1), b1 = pack_bf(e2, e3);
            if (live) { mbar_wait(BAR(B_W2 + 0), 0); mbar_wait(BAR(B_W2 + 1), 0); }
#pragma unroll
            for (int i = 0; i < 5; i++) {
                const int mt = wid * 5 + i;
                const int box = mt >> 2;
                const int cc = 2 * (mt & 3) + (mi & 1);
                const int r = l8 + 8 * (mi >> 1);
                float acc[4] = {};
                uint32_t a[4];
                ldsm4t(a, sb + SM_W2 + box * 2048 + r * 128 + ((cc ^ (r & 7)) << 4));
                mma16816(acc, a, b0, b1);
                if (live && j4 == 0) { stage[mt * 16 + g4] = acc[0]; stage[mt * 16 + 8 + g4] = acc[2]; }
            }
            if (live) bar_cons();
            const int o = tid >> 1, k = tid & 1;
            const float* sp = stage + o * 5 + k * 3;
            float v0 = sp[0], v1 = sp[1], v2 = k ? 0.f : sp[2];
            if (live) st_pk16(&g_h3[o][cta][k], __float_as_uint(v0), __float_as_uint(v1), __float_as_uint(v2), tag);
        }
        if (live) TS(16);
        {
            float a0 = 0.f, a1 = 0.f, a2 = 0.f;
            if (tid < 192 || !live) {
                const int t2 = tid < 192 ? tid : tid - 128;
                uint4 v = poll16(&g_h3[cta][t2 >> 1][t2 & 1], tag, live);
                a0 = __uint_as_float(v.x); a1 = __uint_as_float(v.y); a2 = __uint_as_float(v.z);
            }
#pragma unroll
            for (int o = 2; o <= 16; o <<= 1) {
                a0 += __shfl_xor_sync(0xffffffffu, a0, o);
                a1 += __shfl_xor_sync(0xffffffffu, a1, o);
                a2 += __shfl_xor_sync(0xffffffffu, a2, o);
            }
            float* fin = reinterpret_cast<float*>(smem + SM_FIN);
            if (live && lane < 2) { fin[wid * 8 + lane * 3] = a0; fin[wid * 8 + lane * 3 + 1] = a1; if (lane == 0) fin[wid * 8 + 2] = a2; }
            if (live) bar_cons();
            if (live) TS(17);
            if (wid == 0 || !live) {
                const int l5 = lane < 5 ? lane : 0;
                float sum = 0.f;
#pragma unroll
                for (int w = 0; w < 6; w++) sum += fin[w * 8 + l5];
                float y = own[24 + l5] + bfr(own[8 + l5] * bfr(sum));
                if (live && lane < 5) out[cta * 5 + lane] = __float2bfloat16_rn(y);
            }
            if (live && cta == 0 && tid == 0) g_epoch = tag;
        }
        if (live) { TS(18); break; }
        live = true;
    }
}

typedef CUresult (*EncodeFn)(CUtensorMap*, CUtensorMapDataType, cuuint32_t, void*, const cuuint64_t*, const cuuint64_t*,
                             const cuuint32_t*, const cuuint32_t*, CUtensorMapInterleave, CUtensorMapSwizzle,
                             CUtensorMapL2promotion, CUtensorMapFloatOOBfill);

void make_map(EncodeFn enc, CUtensorMap* tm, const void* ptr, uint64_t cols, uint64_t rows, uint32_t box_c, uint32_t box_r,
              CUtensorMapSwizzle sw, CUtensorMapL2promotion prom) {
    cuuint64_t dims[2] = {cols, rows};
    cuuint64_t strides[1] = {cols * 2};
    cuuint32_t box[2] = {box_c, box_r};
    cuuint32_t es[2] = {1, 1};
    enc(tm, CU_TENSOR_MAP_DATA_TYPE_BFLOAT16, 2, const_cast<void*>(ptr), dims, strides, box, es,
        CU_TENSOR_MAP_INTERLEAVE_NONE, sw, prom, CU_TENSOR_MAP_FLOAT_OOB_FILL_NONE);
}

}

extern "C" void kernel_launch(void* const* d_in, const int* in_sizes, int n_in, void* d_out, int out_size) {
    (void)in_sizes; (void)n_in; (void)out_size;
    static EncodeFn enc = nullptr;
    static int num_sms = 0;
    if (!enc) {
        void* fn = nullptr;
        cudaDriverEntryPointQueryResult qr;
        cudaGetDriverEntryPoint("cuTensorMapEncodeTiled", &fn, cudaEnableDefault, &qr);
        enc = (EncodeFn)fn;
        cudaDeviceGetAttribute(&num_sms, cudaDevAttrMultiProcessorCount, 0);
        cudaFuncSetAttribute(fused_decode_kernel, cudaFuncAttributeMaxDynamicSharedMemorySize, SM_TOTAL);
    }
    CUtensorMap tmK, tmV, tmMod, tmWq, tmWo, tmW1, tmW3, tmW2;
    const uint64_t kv_lines = (uint64_t)NH * SK * 3;
    make_map(enc, &tmK, d_in[1], 64, kv_lines, 64, 96, CU_TENSOR_MAP_SWIZZLE_128B, CU_TENSOR_MAP_L2_PROMOTION_L2_128B);
    make_map(enc, &tmV, d_in[2], 64, kv_lines, 64, 96, CU_TENSOR_MAP_SWIZZLE_128B, CU_TENSOR_MAP_L2_PROMOTION_L2_128B);
    make_map(enc, &tmWq, d_in[3], NH * DH, D, 48, 128, CU_TENSOR_MAP_SWIZZLE_NONE, CU_TENSOR_MAP_L2_PROMOTION_L2_128B);
    make_map(enc, &tmWo, d_in[4], D, NH * DH, 64, 48, CU_TENSOR_MAP_SWIZZLE_128B, CU_TENSOR_MAP_L2_PROMOTION_L2_128B);
    make_map(enc, &tmW1, d_in[6], FF, D, 16, 160, CU_TENSOR_MAP_SWIZZLE_32B, CU_TENSOR_MAP_L2_PROMOTION_L2_128B);
    make_map(enc, &tmW3, d_in[7], FF, D, 16, 160, CU_TENSOR_MAP_SWIZZLE_32B, CU_TENSOR_MAP_L2_PROMOTION_L2_128B);
    make_map(enc, &tmW2, d_in[8], D, FF, 64, 16, CU_TENSOR_MAP_SWIZZLE_128B, CU_TENSOR_MAP_L2_PROMOTION_L2_128B);
    make_map(enc, &tmMod, d_in[10], 6 * D, D, 32, 160, CU_TENSOR_MAP_SWIZZLE_64B, CU_TENSOR_MAP_L2_PROMOTION_L2_128B);
    int grid = num_sms < NG * MAXR ? num_sms : NG * MAXR;
    fused_decode_kernel<<<grid, NTHREADS, SM_TOTAL, cudaStreamPerThread>>>(
        tmK, tmV, tmMod, tmWq, tmWo, tmW1, tmW3, tmW2, (const __nv_bfloat16*)d_in[0], (const __nv_bfloat16*)d_in[9],
        (__nv_bfloat16*)d_out);
}
```

```cpp
#include <cuda_runtime.h>
#include <cuda_bf16.h>
#include <cuda.h>
#include <stdint.h>

namespace {

constexpr int D = 640, NH = 32, SK = 8192, DH = 192, FF = 1536;
constexpr int NG = 4;
constexpr int GH = 7;
constexpr int NGLOB = NH - NG * GH;
constexpr int NQH = GH + NGLOB;
constexpr int TILE = 32;
constexpr int TPH = SK / TILE;
constexpr int GT = GH * TPH;
constexpr int PT = NGLOB * TPH;
constexpr int CHUNK = TILE * DH * 2;
#define P_NSLOT 7
#define P_WIN 4
#define P_DLY 450
constexpr int NSLOT = P_NSLOT;
constexpr int WIN = P_WIN;
constexpr int MAXG = 144;
constexpr int NTHREADS = 288;
constexpr float NEG_BIG = -3.402823466e38f;

constexpr int SM_WMOD = 0;
constexpr int SM_WQ = 40960;
constexpr int SM_WO = 0;
constexpr int SM_W1 = 61440;
constexpr int SM_W3 = 81920;
constexpr int SM_W2 = 102400;
constexpr int SM_RING = 122880;
constexpr int SM_MISC = SM_RING + NSLOT * CHUNK;
constexpr int SM_BARS = SM_MISC;
constexpr int SM_META = SM_BARS + 512;
constexpr int SM_Q = SM_META + 128;
constexpr int SM_SC = SM_Q + NQH * DH * 2;
constexpr int SM_H = SM_SC + 1280;
constexpr int SM_X = SM_H + 1280;
constexpr int SM_CB = SM_X + 1280;
constexpr int SM_SB = SM_CB + 1280;
constexpr int SM_OWN = SM_SB + 1280;
constexpr int SM_RED = SM_OWN + 128;
constexpr int SM_MERGE = SM_RED + 2048;
constexpr int SM_STAGE = SM_MERGE + 3200;
constexpr int SM_X2 = SM_STAGE + 2560;
constexpr int SM_FIN = SM_X2 + 2560;
constexpr int SM_TOTAL = SM_FIN + 256;
static_assert(SM_TOTAL <= 232448, "shared memory budget");

constexpr int B_FULL = 0;
constexpr int B_EMPTY = 8;
constexpr int B_MOD = 16;
constexpr int B_WQ = 20;
constexpr int B_WO = 25;
constexpr int B_W1 = 30;
constexpr int B_W3 = 32;
constexpr int B_W2 = 34;
constexpr int B_FLF = 36, B_FLE = 37, B_PRO = 38, B_DUMMY = 39, B_COUNT = 40;
static_assert(NSLOT <= 8, "barrier map");
constexpr uint32_t META_END = 0x10000u;

__device__ unsigned g_epoch;
__device__ unsigned g_ctr[2][(NG + 1) * 32];
__device__ __align__(128) unsigned long long g_mod[1920];
__device__ __align__(128) unsigned long long g_q[3072];
__device__ __align__(128) uint4 g_hdr[NH][MAXG];
__device__ __align__(128) uint4 g_dat[NH][MAXG][64];
__device__ __align__(128) uint4 g_h1[128][128][2];
__device__ __align__(128) uint4 g_x2[128][2];
__device__ __align__(128) uint4 g_h3[128][96][2];

#define TS(k) do {} while (0)
#define DBG(k) do {} while (0)
#define CLK(k) do {} while (0)

__device__ __forceinline__ uint32_t smem_u32(const void* p) { return (uint32_t)__cvta_generic_to_shared(p); }
__device__ __forceinline__ void mbar_init(uint32_t bar, uint32_t cnt) {
    asm volatile("mbarrier.init.shared::cta.b64 [%0], %1;" ::"r"(bar), "r"(cnt) : "memory");
}
__device__ __forceinline__ void mbar_expect_tx(uint32_t bar, uint32_t bytes) {
    asm volatile("mbarrier.arrive.expect_tx.shared::cta.b64 _, [%0], %1;" ::"r"(bar), "r"(bytes) : "memory");
}
__device__ __forceinline__ void mbar_arrive(uint32_t bar) {
    asm volatile("mbarrier.arrive.shared::cta.b64 _, [%0];" ::"r"(bar) : "memory");
}
constexpr uint32_t SPIN_LIMIT = 1u << 22;
__device__ __forceinline__ void mbar_wait(uint32_t bar, uint32_t parity) {
    asm volatile(
        "{\n.reg .pred p;\n.reg .u32 c;\nmov.u32 c, 0;\n"
        "LW:\nmbarrier.try_wait.parity.shared::cta.b64 p, [%0], %1;\n@p bra LD;\n"
        "add.u32 c, c, 1;\nsetp.lt.u32 p, c, 0x400000;\n@p bra LW;\ntrap;\nLD:\n}" ::"r"(bar), "r"(parity)
        : "memory");
}
__device__ __forceinline__ void tma2d(uint32_t dst, const CUtensorMap* tm, int c0, int c1, uint32_t bar) {
    asm volatile(
        "cp.async.bulk.tensor.2d.shared::cluster.global.mbarrier::complete_tx::bytes [%0], [%1, {%3, %4}], [%2];" ::"r"(dst),
        "l"(tm), "r"(bar), "r"(c0), "r"(c1)
        : "memory");
}
__device__ __forceinline__ void tma2d_hint(uint32_t dst, const CUtensorMap* tm, int c0, int c1, uint32_t bar, uint64_t pol) {
    asm volatile(
        "cp.async.bulk.tensor.2d.shared::cluster.global.mbarrier::complete_tx::bytes.L2::cache_hint [%0], [%1, {%3, %4}], [%2], %5;" ::"r"(dst),
        "l"(tm), "r"(bar), "r"(c0), "r"(c1), "l"(pol)
        : "memory");
}
__device__ __forceinline__ void prefetch_tm(const CUtensorMap* tm) {
    asm volatile("prefetch.tensormap [%0];" ::"l"(tm) : "memory");
}
__device__ __forceinline__ void ldsm4(uint32_t (&r)[4], uint32_t addr) {
    asm volatile("ldmatrix.sync.aligned.m8n8.x4.shared.b16 {%0,%1,%2,%3}, [%4];"
                 : "=r"(r[0]), "=r"(r[1]), "=r"(r[2]), "=r"(r[3])
                 : "r"(addr));
}
__device__ __forceinline__ void ldsm4t(uint32_t (&r)[4], uint32_t addr) {
    asm volatile("ldmatrix.sync.aligned.m8n8.x4.trans.shared.b16 {%0,%1,%2,%3}, [%4];"
                 : "=r"(r[0]), "=r"(r[1]), "=r"(r[2]), "=r"(r[3])
                 : "r"(addr));
}
__device__ __forceinline__ void mma16816(float (&d)[4], const uint32_t (&a)[4], uint32_t b0, uint32_t b1) {
    asm volatile(
        "mma.sync.aligned.m16n8k16.row.col.f32.bf16.bf16.f32 {%0,%1,%2,%3}, {%4,%5,%6,%7}, {%8,%9}, {%0,%1,%2,%3};"
        : "+f"(d[0]), "+f"(d[1]), "+f"(d[2]), "+f"(d[3])
        : "r"(a[0]), "r"(a[1]), "r"(a[2]), "r"(a[3]), "r"(b0), "r"(b1));
}
__device__ __forceinline__ void bar_cons() { asm volatile("bar.sync 1, 256;" ::: "memory"); }
__device__ __forceinline__ bool bar_cons_or(bool p) {
    uint32_t r;
    asm volatile("{\n.reg .pred p, q;\nsetp.ne.u32 p, %1, 0;\nbar.red.or.pred q, 1, 256, p;\nselp.u32 %0, 1, 0, q;\n}"
                 : "=r"(r) : "r"((uint32_t)p) : "memory");
    return r != 0;
}
__device__ __forceinline__ void spin(int cycles) {
    long long t0 = clock64();
    while (clock64() - t0 < cycles) {}
}

__device__ __forceinline__ float bfr(float x) { return __bfloat162float(__float2bfloat16_rn(x)); }
__device__ __forceinline__ uint32_t pack_bf(float lo, float hi) {
    __nv_bfloat162 t = __floats2bfloat162_rn(lo, hi);
    return *reinterpret_cast<uint32_t*>(&t);
}
__device__ __forceinline__ float bf_lo(uint32_t v) { return __uint_as_float(v << 16); }
__device__ __forceinline__ float bf_hi(uint32_t v) { return __uint_as_float(v & 0xffff0000u); }

__device__ __forceinline__ void st_pk8(unsigned long long* p, uint32_t v, uint32_t tag) {
    unsigned long long w = ((unsigned long long)tag << 32) | v;
    asm volatile("st.relaxed.gpu.global.b64 [%0], %1;" ::"l"(p), "l"(w) : "memory");
}
__device__ __forceinline__ unsigned long long ld_raw8(const unsigned long long* p) {
    unsigned long long w;
    asm volatile("ld.relaxed.gpu.global.b64 %0, [%1];" : "=l"(w) : "l"(p) : "memory");
    return w;
}
template <int N>
__device__ __forceinline__ void poll8(const unsigned long long* base, const int (&off)[N], uint32_t (&val)[N], uint32_t tag) {
    uint32_t it = 0;
    while (true) {
        unsigned long long w[N];
#pragma unroll
        for (int i = 0; i < N; i++) w[i] = ld_raw8(base + off[i]);
        bool ok = true;
#pragma unroll
        for (int i = 0; i < N; i++) { ok = ok && ((uint32_t)(w[i] >> 32) == tag); val[i] = (uint32_t)w[i]; }
        if (ok) break;
        if (++it > SPIN_LIMIT) __trap();
    }
}
__device__ __forceinline__ void st_pk16(uint4* p, uint32_t a, uint32_t b, uint32_t c, uint32_t tag) {
    asm volatile(
        "{\n.reg .b128 t;\n.reg .b64 lo, hi;\nmov.b64 lo, {%1, %2};\nmov.b64 hi, {%3, %4};\nmov.b128 t, {lo, hi};\n"
        "st.relaxed.gpu.global.b128 [%0], t;\n}" ::"l"(p), "r"(a), "r"(b), "r"(c), "r"(tag)
        : "memory");
}
__device__ __forceinline__ uint4 ld_raw16p(const uint4* p, uint32_t on) {
    uint4 v;
    asm volatile(
        "{\n.reg .b128 t;\n.reg .b64 lo, hi;\n.reg .pred q;\nsetp.ne.u32 q, %5, 0;\n"
        "@q ld.relaxed.gpu.global.b128 t, [%4];\nmov.b128 {lo, hi}, t;\n"
        "mov.b64 {%0, %1}, lo;\nmov.b64 {%2, %3}, hi;\n}"
        : "=r"(v.x), "=r"(v.y), "=r"(v.z), "=r"(v.w)
        : "l"(p), "r"(on)
        : "memory");
    return v;
}
__device__ __forceinline__ uint4 poll16(const uint4* p, uint32_t tag, bool live) {
    uint32_t it = 0;
    uint4 v;
    while (true) {
        v = ld_raw16p(p, live);
        if (!live || v.w == tag) break;
        if (++it > SPIN_LIMIT) __trap();
    }
    return v;
}
__device__ __forceinline__ void st_zero16(void* p) {
    asm volatile("st.relaxed.gpu.global.v4.u32 [%0], {%1, %1, %1, %1};" ::"l"(p), "r"(0u) : "memory");
}
__device__ __forceinline__ float ex2(float x) {
    float y;
    asm("ex2.approx.ftz.f32 %0, %1;" : "=f"(y) : "f"(x));
    return y;
}
__device__ __forceinline__ float fsqrt(float x) {
    float y;
    asm("sqrt.approx.f32 %0, %1;" : "=f"(y) : "f"(x));
    return y;
}
constexpr float LOG2E = 1.4426950408889634f;
__device__ __forceinline__ float silu(float a) { return __fdividef(a, 1.0f + ex2(-a * LOG2E)); }
__device__ __forceinline__ float warp_sum(float v) {
#pragma unroll
    for (int o = 16; o > 0; o >>= 1) v += __shfl_xor_sync(0xffffffffu, v, o);
    return v;
}

__device__ __forceinline__ void ln_stats(const float (&v)[20], float& mean_b, float& den_b) {
    float s = 0.f;
#pragma unroll
    for (int i = 0; i < 20; i++) s += v[i];
    s = warp_sum(s);
    float mean = s * (1.0f / 640.0f);
    float q = 0.f;
#pragma unroll
    for (int i = 0; i < 20; i++) { float d = v[i] - mean; q += d * d; }
    q = warp_sum(q);
    float var_b = bfr(q * (1.0f / 640.0f));
    mean_b = bfr(mean);
    den_b = bfr(fsqrt(bfr(var_b + 1e-5f)));
}

struct Window {
    uint32_t bar[WIN];
    uint32_t par[WIN];
    __device__ __forceinline__ void init(uint32_t dummy) {
#pragma unroll
        for (int i = 0; i < WIN; i++) { bar[i] = dummy; par[i] = 1; }
    }
    __device__ __forceinline__ void push(uint32_t b, uint32_t p) {
        mbar_wait(bar[0], par[0]);
#pragma unroll
        for (int i = 0; i + 1 < WIN; i++) { bar[i] = bar[i + 1]; par[i] = par[i + 1]; }
        bar[WIN - 1] = b; par[WIN - 1] = p;
    }
};

__global__ void __launch_bounds__(NTHREADS, 1)
fused_decode_kernel(const __grid_constant__ CUtensorMap tmK, const __grid_constant__ CUtensorMap tmV,
                    const __grid_constant__ CUtensorMap tmMod, const __grid_constant__ CUtensorMap tmWq,
                    const __grid_constant__ CUtensorMap tmWo, const __grid_constant__ CUtensorMap tmW1,
                    const __grid_constant__ CUtensorMap tmW3, const __grid_constant__ CUtensorMap tmW2,
                    const __nv_bfloat16* __restrict__ x_in, const __nv_bfloat16* __restrict__ c_in,
                    __nv_bfloat16* __restrict__ out) {
    extern __shared__ __align__(1024) uint8_t smem[];
    const uint32_t sb = smem_u32(smem);
    const int tid = threadIdx.x, wid = tid >> 5, lane = tid & 31;
    const int cta = blockIdx.x, G = gridDim.x;
    const int grp = cta % NG, rank = cta / NG;
    const uint32_t bars = sb + SM_BARS;
    auto BAR = [&](int i) { return bars + 8u * i; };
    volatile uint32_t* meta = reinterpret_cast<volatile uint32_t*>(smem + SM_META);

    if (wid == 8) {
        Window win;
        unsigned epoch = 0;
        if (lane == 0) {
            TS(0);
            if (sb & 1023u) __trap();
            asm volatile("ld.relaxed.gpu.global.u32 %0, [%1];" : "=r"(epoch) : "l"(&g_epoch) : "memory");
            prefetch_tm(&tmMod); prefetch_tm(&tmWq); prefetch_tm(&tmK); prefetch_tm(&tmV);
#pragma unroll 1
            for (int i = 0; i < B_COUNT; i++) {
                int cnt = (i >= B_EMPTY && i < B_MOD) ? 2 : (i == B_FLF ? 4 : 1);
                mbar_init(BAR(i), cnt);
            }
            asm volatile("fence.mbarrier_init.release.cluster;" ::: "memory");
            asm volatile("fence.proxy.async.shared::cta;" ::: "memory");
            win.init(BAR(B_DUMMY));
            if (cta < 120) {
#pragma unroll 1
                for (int i = 0; i < 4; i++) {
                    win.push(BAR(B_MOD + i), 0);
                    mbar_expect_tx(BAR(B_MOD + i), 10240);
                    tma2d(sb + SM_WMOD + i * 10240, &tmMod, cta * 32, i * 160, BAR(B_MOD + i));
                }
            }
        }
        __syncwarp();
        __syncthreads();
        if (lane == 0) {
            prefetch_tm(&tmWo); prefetch_tm(&tmW1); prefetch_tm(&tmW3); prefetch_tm(&tmW2);
            unsigned* ctr = &g_ctr[epoch & 1][grp * 32];
            unsigned* gctr = &g_ctr[epoch & 1][NG * 32];
            if (cta == 0) {
                for (int g = 0; g <= NG; g++) g_ctr[(epoch + 1) & 1][g * 32] = 0;
            }
            unsigned pend = atomicAdd(ctr, 1);
            if (cta < 128) {
#pragma unroll 1
                for (int i = 0; i < 5; i++) {
                    win.push(BAR(B_WQ + i), 0);
                    mbar_expect_tx(BAR(B_WQ + i), 12288);
                    tma2d(sb + SM_WQ + i * 12288, &tmWq, cta * 48, i * 128, BAR(B_WQ + i));
                }
            }
            uint64_t pol;
            asm volatile("createpolicy.fractional.L2::evict_first.b64 %0, 1.0;" : "=l"(pol));
            int s = 0; uint32_t par = 0;
            int ntiles = 0, run = -1, last_head = -1;
            bool glob = false;
#pragma unroll 1
            while (true) {
                unsigned t = pend;
                if (!glob && t >= (unsigned)GT) { glob = true; t = atomicAdd(gctr, 1); }
                if (glob && t >= (unsigned)PT) break;
                pend = atomicAdd(glob ? gctr : ctr, 1);
                ntiles++;
                const int hl = t / TPH, tile = t % TPH;
                const int head = glob ? NG * GH + hl : grp * GH + hl;
                const int qidx = glob ? GH + hl : hl;
                if (head != last_head) { last_head = head; run++; meta[16 + run] = head; }
                const int line0 = (head * SK + tile * TILE) * 3;
#pragma unroll 1
                for (int kv = 0; kv < 2; kv++) {
                    win.push(BAR(B_FULL + s), par);
                    mbar_wait(BAR(B_EMPTY + s), par ^ 1);
                    meta[s] = run | (qidx << 8);
                    mbar_expect_tx(BAR(B_FULL + s), CHUNK);
                    tma2d_hint(sb + SM_RING + s * CHUNK, kv ? &tmV : &tmK, 0, line0, BAR(B_FULL + s), pol);
                    if (++s == NSLOT) { s = 0; par ^= 1; }
                }
            }
            TS(5);
            meta[16 + run + 1] = 0xFFu;
#pragma unroll 1
            for (int e = 0; e < 2; e++) {
                mbar_wait(BAR(B_EMPTY + s), par ^ 1);
                meta[s] = (run + 1) | META_END;
                mbar_arrive(BAR(B_FULL + s));
                if (++s == NSLOT) { s = 0; par ^= 1; }
                if (++s == NSLOT) { s = 0; par ^= 1; }
            }
            if (cta < 128) {
                mbar_wait(BAR(B_PRO), 0);
#pragma unroll 1
                for (int i = 0; i < 5; i++) {
                    win.push(BAR(B_WO + i), 0);
                    mbar_expect_tx(BAR(B_WO + i), 12288);
                    tma2d(sb + SM_WO + (2 * i) * 6144, &tmWo, (2 * i) * 64, cta * 48, BAR(B_WO + i));
                    tma2d(sb + SM_WO + (2 * i + 1) * 6144, &tmWo, (2 * i + 1) * 64, cta * 48, BAR(B_WO + i));
                }
                if (cta < 96) {
#pragma unroll 1
                    for (int i = 0; i < 4; i++) {
                        const int m = i & 1, hf = i >> 1;
                        const uint32_t bar = BAR((m ? B_W3 : B_W1) + hf);
                        const uint32_t dst = sb + (m ? SM_W3 : SM_W1) + hf * 10240;
                        const CUtensorMap* tm = m ? &tmW3 : &tmW1;
                        win.push(bar, 0);
                        mbar_expect_tx(bar, 10240);
                        tma2d(dst, tm, cta * 16, hf * 320, bar);
                        tma2d(dst + 5120, tm, cta * 16, hf * 320 + 160, bar);
                    }
#pragma unroll 1
                    for (int i = 0; i < 2; i++) {
                        win.push(BAR(B_W2 + i), 0);
                        mbar_expect_tx(BAR(B_W2 + i), 10240);
#pragma unroll 1
                        for (int b = 0; b < 5; b++)
                            tma2d(sb + SM_W2 + (5 * i + b) * 2048, &tmW2, (5 * i + b) * 64, cta * 16, BAR(B_W2 + i));
                    }
                }
            }
            TS(6);
        }
        return;
    }

    const int g4 = lane >> 2, j4 = lane & 3, mi = lane >> 3, l8 = lane & 7;
    uint32_t* sc32 = reinterpret_cast<uint32_t*>(smem + SM_SC);
    uint32_t* h32 = reinterpret_cast<uint32_t*>(smem + SM_H);
    uint32_t* x32 = reinterpret_cast<uint32_t*>(smem + SM_X);
    uint32_t* q32 = reinterpret_cast<uint32_t*>(smem + SM_Q);
    float* red = reinterpret_cast<float*>(smem + SM_RED);
    float* stage = reinterpret_cast<float*>(smem + SM_STAGE);
    float* own = reinterpret_cast<float*>(smem + SM_OWN);

    {
        const uint32_t* cg = reinterpret_cast<const uint32_t*>(c_in);
        const uint32_t* xg = reinterpret_cast<const uint32_t*>(x_in);
        uint32_t c0 = cg[tid], x0 = xg[tid], c1 = 0, x1 = 0;
        if (tid < 64) { c1 = cg[256 + tid]; x1 = xg[256 + tid]; }
        unsigned epoch = 0;
        if (tid == 0) asm volatile("ld.relaxed.gpu.global.u32 %0, [%1];" : "=r"(epoch) : "l"(&g_epoch) : "memory");
        if (cta < 120 && tid < 8) st_zero16(reinterpret_cast<uint4*>(&g_mod[cta * 16]) + tid);
        if (cta < 128 && tid >= 32 && tid < 44) st_zero16(reinterpret_cast<uint4*>(&g_q[cta * 24]) + (tid - 32));
        if (cta < 128) {
            if (tid >= 64 && tid < 66) st_zero16(&g_x2[cta][tid - 64]);
            st_zero16(&g_h1[tid >> 1][cta][tid & 1]);
            if (cta < 96) st_zero16(&g_h3[tid >> 1][cta][tid & 1]);
        }
#pragma unroll 1
        for (int f = tid >> 6; f < NQH; f += 4) {
            const int head = f < GH ? grp * GH + f : NG * GH + (f - GH);
            const int idx = f < GH ? rank : cta;
            st_zero16(&g_dat[head][idx][tid & 63]);
            if ((tid & 63) == 0) st_zero16(&g_hdr[head][idx]);
        }
        sc32[tid] = pack_bf(silu(bf_lo(c0)), silu(bf_hi(c0))); x32[tid] = x0;
        if (tid < 64) { sc32[256 + tid] = pack_bf(silu(bf_lo(c1)), silu(bf_hi(c1))); x32[256 + tid] = x1; }
        if (tid == 0) meta[8] = epoch + 1;
    }
    __syncthreads();
    const uint32_t tag = meta[8];

    float mean_x = 0.f, rden_x = 1.f;
    if (cta < 128) {
        float xv[20];
#pragma unroll
        for (int i = 0; i < 10; i++) { uint32_t v = x32[lane + 32 * i]; xv[2 * i] = bf_lo(v); xv[2 * i + 1] = bf_hi(v); }
        float den;
        ln_stats(xv, mean_x, den);
        rden_x = __fdividef(1.0f, den);
    }

    if (cta < 120) {
        float acc[2][4] = {};
        uint32_t a[5][2][4], bb[5][2];
        const uint32_t base = sb + SM_WMOD + (wid >> 1) * 10240;
#pragma unroll
        for (int ks = 0; ks < 5; ks++) {
            const int r0 = wid * 80 + ks * 16;
            bb[ks][0] = sc32[(r0 >> 1) + j4]; bb[ks][1] = sc32[(r0 >> 1) + 4 + j4];
        }
        mbar_wait(BAR(B_MOD + (wid >> 1)), 0);
#pragma unroll
        for (int ks = 0; ks < 5; ks++) {
            const int r = (wid & 1) * 80 + ks * 16 + l8 + 8 * (mi >> 1);
#pragma unroll
            for (int mt = 0; mt < 2; mt++) ldsm4t(a[ks][mt], base + r * 64 + (((2 * mt + (mi & 1)) ^ ((r >> 1) & 3)) << 4));
        }
#pragma unroll
        for (int ks = 0; ks < 5; ks++) { mma16816(acc[0], a[ks][0], bb[ks][0], bb[ks][1]); mma16816(acc[1], a[ks][1], bb[ks][0], bb[ks][1]); }
        if (j4 == 0) {
#pragma unroll
            for (int mt = 0; mt < 2; mt++) { red[wid * 64 + mt * 16 + g4] = acc[mt][0]; red[wid * 64 + mt * 16 + 8 + g4] = acc[mt][2]; }
        }
        bar_cons();
        if (wid == 0) {
            float v = 0.f;
#pragma unroll
            for (int w = 0; w < 8; w++) v += red[w * 64 + lane];
            float o = __shfl_down_sync(0xffffffffu, v, 1);
            if (!(lane & 1)) st_pk8(&g_mod[cta * 16 + (lane >> 1)], pack_bf(v, o), tag);
        }
    }
    TS(1);

    if (cta < 128) {
        {
            const int off[4] = {tid, 320 + tid, tid < 64 ? 256 + tid : tid, tid < 64 ? 576 + tid : 320 + tid};
            uint32_t val[4];
            poll8<4>(g_mod, off, val, tag);
#pragma unroll
            for (int rep = 0; rep < 2; rep++) {
                int p = tid + rep * 256;
                if (p < 320) {
                    uint32_t sa = val[2 * rep], ca = val[2 * rep + 1];
                    uint32_t xx = x32[p];
                    float n0 = bfr(bfr(bf_lo(xx) - mean_x) * rden_x), n1 = bfr(bfr(bf_hi(xx) - mean_x) * rden_x);
                    float h0 = bfr(n0 * bfr(1.0f + bf_lo(ca))) + bf_lo(sa);
                    float h1 = bfr(n1 * bfr(1.0f + bf_hi(ca))) + bf_hi(sa);
                    h32[p] = pack_bf(h0, h1);
                }
            }
        }
        bar_cons();
        TS(2);
        float acc[3][4] = {};
        uint32_t a[5][3][4], bb[5][2];
#pragma unroll
        for (int ks = 0; ks < 5; ks++) {
            const int r0 = wid * 80 + ks * 16;
            bb[ks][0] = h32[(r0 >> 1) + j4]; bb[ks][1] = h32[(r0 >> 1) + 4 + j4];
        }
        mbar_wait(BAR(B_WQ + ((wid * 80) >> 7)), 0);
        mbar_wait(BAR(B_WQ + ((wid * 80 + 79) >> 7)), 0);
#pragma unroll
        for (int ks = 0; ks < 5; ks++) {
            const int r = wid * 80 + ks * 16 + l8 + 8 * (mi >> 1);
#pragma unroll
            for (int mt = 0; mt < 3; mt++) ldsm4t(a[ks][mt], sb + SM_WQ + r * 96 + ((2 * mt + (mi & 1)) << 4));
        }
#pragma unroll
        for (int ks = 0; ks < 5; ks++) {
#pragma unroll
            for (int mt = 0; mt < 3; mt++) mma16816(acc[mt], a[ks][mt], bb[ks][0], bb[ks][1]);
        }
        if (j4 == 0) {
#pragma unroll
            for (int mt = 0; mt < 3; mt++) { red[wid * 64 + mt * 16 + g4] = acc[mt][0]; red[wid * 64 + mt * 16 + 8 + g4] = acc[mt][2]; }
        }
        bar_cons();
        if (tid < 64) {
            float v = 0.f;
            if (tid < 48) {
#pragma unroll
                for (int w = 0; w < 8; w++) v += red[w * 64 + tid];
            }
            float o = __shfl_down_sync(0xffffffffu, v, 1);
            if (tid < 48 && !(tid & 1)) st_pk8(&g_q[cta * 24 + (tid >> 1)], pack_bf(v, o), tag);
        }
        TS(3);
    }
    {
        int off[5];
#pragma unroll
        for (int j = 0; j < 5; j++) {
            int p = tid + 256 * j;
            if (p >= NQH * 96) p = tid;
            off[j] = p < GH * 96 ? grp * GH * 96 + p : NG * GH * 96 + (p - GH * 96);
        }
        uint32_t val[5];
        poll8<5>(g_q, off, val, tag);
#pragma unroll
        for (int j = 0; j < 5; j++)
            if (tid + 256 * j < NQH * 96) q32[tid + 256 * j] = val[j];
    }
    bar_cons();
    if (tid == 0) mbar_arrive(BAR(B_PRO));
    TS(4);

    bool live = true;
    if (wid < 4) {
        const int pair = wid >> 1, half = wid & 1;
        const int rowK = half * 16 + l8 + 8 * (mi & 1), hiK = mi >> 1;
        const int rowV = half * 16 + l8 + 8 * (mi >> 1), hiV = mi & 1;
        float acc[12][4];
#pragma unroll
        for (int i = 0; i < 12; i++) { acc[i][0] = acc[i][1] = acc[i][2] = acc[i][3] = 0.f; }
        float m_run = NEG_BIG, l_run = 0.f;
        uint32_t qf[12][2];
#pragma unroll
        for (int i = 0; i < 12; i++) { qf[i][0] = qf[i][1] = 0; }
        int cur = -1, flushed = 0, cnt = 0;
        int s = 2 * pair; uint32_t par = 0;
        float* mb = reinterpret_cast<float*>(smem + SM_MERGE) + wid * 200;
#pragma unroll 1
        while (true) {
            mbar_wait(BAR(B_FULL + s), par);
            const uint32_t mt_ = meta[s];
            const int run = mt_ & 0xff;
            if (run != cur) {
#pragma unroll 1
                while (flushed < run) {
                    if (flushed != cur) {
#pragma unroll
                        for (int i = 0; i < 12; i++) { acc[i][0] = acc[i][1] = acc[i][2] = acc[i][3] = 0.f; }
                        m_run = NEG_BIG; l_run = 0.f; cnt = 0;
                    }
                    float v[24];
#pragma unroll
                    for (int i = 0; i < 12; i++) { v[2 * i] = acc[i][0] + acc[i][1]; v[2 * i + 1] = acc[i][2] + acc[i][3]; }
                    float u[12], w6[6];
                    const bool o1 = j4 & 1, o2 = j4 & 2;
#pragma unroll
                    for (int i = 0; i < 12; i++) {
                        float send = o1 ? v[i] : v[i + 12], keep = o1 ? v[i + 12] : v[i];
                        u[i] = keep + __shfl_xor_sync(0xffffffffu, send, 1);
                    }
#pragma unroll
                    for (int i = 0; i < 6; i++) {
                        float send = o2 ? u[i] : u[i + 6], keep = o2 ? u[i + 6] : u[i];
                        w6[i] = keep + __shfl_xor_sync(0xffffffffu, send, 2);
                    }
                    float l = l_run;
                    l += __shfl_xor_sync(0xffffffffu, l, 4);
                    l += __shfl_xor_sync(0xffffffffu, l, 8);
                    l += __shfl_xor_sync(0xffffffffu, l, 16);
                    mbar_wait(BAR(B_FLE), (flushed & 1) ^ 1);
#pragma unroll
                    for (int i = 0; i < 6; i++) {
                        int idx = (o1 ? 12 : 0) + (o2 ? 6 : 0) + i;
                        mb[4 + 16 * (idx >> 1) + 8 * (idx & 1) + g4] = w6[i];
                    }
                    if (lane == 0) { mb[0] = m_run; mb[1] = l; mb[2] = __int_as_float(cnt); }
                    __syncwarp();
                    if (lane == 0) mbar_arrive(BAR(B_FLF));
                    flushed++;
                    cur = -1;
                }
                if (mt_ & META_END) {
                    mbar_wait(BAR(B_FLE), (flushed & 1) ^ 1);
                    if (lane == 0) mbar_arrive(BAR(B_FLF));
                    break;
                }
                cur = run;
                const int qi = (mt_ >> 8) & 0xff;
#pragma unroll
                for (int i = 0; i < 12; i++) { acc[i][0] = acc[i][1] = acc[i][2] = acc[i][3] = 0.f; }
                m_run = NEG_BIG; l_run = 0.f; cnt = 0;
#pragma unroll
                for (int ks = 0; ks < 12; ks++) {
                    qf[ks][0] = q32[qi * 96 + ks * 8 + j4];
                    qf[ks][1] = q32[qi * 96 + ks * 8 + 4 + j4];
                }
            }
            cnt++;
            const uint32_t kb = sb + SM_RING + s * CHUNK;
            float sc[3][4] = {};
            {
                uint32_t a[12][4];
#pragma unroll
                for (int t = 0; t < 3; t++) {
                    const int ln = rowK * 3 + t;
#pragma unroll
                    for (int kk = 0; kk < 4; kk++) ldsm4(a[t * 4 + kk], kb + ln * 128 + (((2 * kk + hiK) ^ (ln & 7)) << 4));
                }
#pragma unroll
                for (int kk = 0; kk < 4; kk++) {
#pragma unroll
                    for (int t = 0; t < 3; t++) mma16816(sc[t], a[t * 4 + kk], qf[t * 4 + kk][0], qf[t * 4 + kk][1]);
                }
            }
            __syncwarp();
            if (lane == 0) mbar_arrive(BAR(B_EMPTY + s));
            int sv = s + 1; uint32_t parv = par;
            if (sv == NSLOT) { sv = 0; parv ^= 1; }
            const float scale = 0.07216878364870322f;
            float s0 = bfr(bfr(sc[0][0] + sc[1][0] + sc[2][0]) * scale);
            float s1 = bfr(bfr(sc[0][2] + sc[1][2] + sc[2][2]) * scale);
            float tm = fmaxf(s0, s1);
            tm = fmaxf(tm, __shfl_xor_sync(0xffffffffu, tm, 4));
            tm = fmaxf(tm, __shfl_xor_sync(0xffffffffu, tm, 8));
            tm = fmaxf(tm, __shfl_xor_sync(0xffffffffu, tm, 16));
            if (tm > m_run) {
                float alpha = ex2((m_run - tm) * LOG2E);
                l_run *= alpha;
#pragma unroll
                for (int i = 0; i < 12; i++) { acc[i][0] *= alpha; acc[i][1] *= alpha; acc[i][2] *= alpha; acc[i][3] *= alpha; }
                m_run = tm;
            }
            float p0 = ex2((s0 - m_run) * LOG2E);
            float p1 = ex2((s1 - m_run) * LOG2E);
            l_run += p0 + p1;
            uint32_t b0 = 0, b1 = 0;
            if (j4 == (g4 >> 1)) {
                uint32_t e0 = pack_bf(p0, 0.f) & 0xffffu, e1 = pack_bf(p1, 0.f) & 0xffffu;
                b0 = (g4 & 1) ? (e0 << 16) : e0;
                b1 = (g4 & 1) ? (e1 << 16) : e1;
            }
            mbar_wait(BAR(B_FULL + sv), parv);
            const uint32_t vb = sb + SM_RING + sv * CHUNK;
            {
                uint32_t a[12][4];
#pragma unroll
                for (int t = 0; t < 3; t++) {
                    const int ln = rowV * 3 + t;
#pragma unroll
                    for (int kk = 0; kk < 4; kk++) ldsm4t(a[t * 4 + kk], vb + ln * 128 + (((2 * kk + hiV) ^ (ln & 7)) << 4));
                }
#pragma unroll
                for (int i = 0; i < 12; i++) mma16816(acc[i], a[i], b0, b1);
            }
            __syncwarp();
            if (lane == 0) mbar_arrive(BAR(B_EMPTY + sv));
            s += 4;
            if (s >= NSLOT) { s -= NSLOT; par ^= 1; }
        }
        TS(7);
    } else if (wid == 4) {
        const float* mb = reinterpret_cast<const float*>(smem + SM_MERGE);
#pragma unroll 1
        for (int f = 0;; f++) {
            mbar_wait(BAR(B_FLF), f & 1);
            const int head = (int)meta[16 + f];
            if (head == 0xFF) break;
            float m0 = mb[0], m1 = mb[200], m2 = mb[400], m3 = mb[600];
            float M = fmaxf(fmaxf(m0, m1), fmaxf(m2, m3));
            float w0 = ex2((m0 - M) * LOG2E), w1 = ex2((m1 - M) * LOG2E);
            float w2 = ex2((m2 - M) * LOG2E), w3 = ex2((m3 - M) * LOG2E);
            const int idx = head < NG * GH ? rank : cta;
            uint4* dst = &g_dat[head][idx][0];
            float o[6];
#pragma unroll
            for (int i = 0; i < 6; i++) {
                int d = 4 + (i < 3 ? 3 * lane + i : 96 + 3 * lane + (i - 3));
                o[i] = w0 * mb[d] + w1 * mb[200 + d] + w2 * mb[400 + d] + w3 * mb[600 + d];
            }
            float L = w0 * mb[1] + w1 * mb[201] + w2 * mb[401] + w3 * mb[601];
            const uint32_t tiles = __float_as_int(mb[2]) + __float_as_int(mb[402]);
            st_pk16(dst + lane, __float_as_uint(o[0]), __float_as_uint(o[1]), __float_as_uint(o[2]), tag);
            st_pk16(dst + 32 + lane, __float_as_uint(o[3]), __float_as_uint(o[4]), __float_as_uint(o[5]), tag);
            if (lane == 0) st_pk16(&g_hdr[head][idx], __float_as_uint(M), __float_as_uint(L), tiles, tag);
            __syncwarp();
            if (lane == 0) mbar_arrive(BAR(B_FLE));
        }
        TS(8);
    } else if (wid >= 6) {
        if (cta < 128) {
            const int t = tid - 192;
            uint32_t* cb32 = reinterpret_cast<uint32_t*>(smem + SM_CB);
            uint32_t* sb32 = reinterpret_cast<uint32_t*>(smem + SM_SB);
            const int col = cta * 5 + t;
            int off[12];
            uint32_t val[12];
#pragma unroll
            for (int rep = 0; rep < 5; rep++) { off[2 * rep] = 960 + t + 64 * rep; off[2 * rep + 1] = 1280 + t + 64 * rep; }
            off[10] = t < 5 ? (1280 + col) >> 1 : 960;
            off[11] = t < 5 ? (3200 + col) >> 1 : 960;
            poll8<12>(g_mod, off, val, tag);
#pragma unroll
            for (int rep = 0; rep < 5; rep++) {
                sb32[t + 64 * rep] = val[2 * rep];
                cb32[t + 64 * rep] = pack_bf(1.0f + bf_lo(val[2 * rep + 1]), 1.0f + bf_hi(val[2 * rep + 1]));
            }
            if (t < 5) {
                own[t] = (col & 1) ? bf_hi(val[10]) : bf_lo(val[10]);
                own[8 + t] = (col & 1) ? bf_hi(val[11]) : bf_lo(val[11]);
                uint32_t xx = x32[col >> 1];
                own[16 + t] = (col & 1) ? bf_hi(xx) : bf_lo(xx);
            }
        }
        live = false;
    }
    if (cta >= 128) return;

    const uint32_t sb0 = sb;
    const int tid0 = tid;
#pragma unroll 1
    while (true) {
        uint32_t sb = sb0; int tid = tid0;
        asm volatile("" : "+r"(sb), "+r"(tid));
        const int wid = tid >> 5, lane = tid & 31;
        const int g4 = lane >> 2, j4 = lane & 3, mi = lane >> 3, l8 = lane & 7;
        if (live) bar_cons();
        if (live) TS(9);
        uint32_t ob[3][2];
        {
            const int h = cta >> 2, js = cta & 3;
            const int ncand = h >= NG * GH ? G : (G - h / GH + NG - 1) / NG;
            const int k = tid & 15, rr = tid >> 4;
            const uint4* hdr = &g_hdr[h][tid < ncand ? tid : 0];
            const uint4* dat = &g_dat[h][0][16 * js + k];
            float* hm = reinterpret_cast<float*>(smem + SM_X2);
            float* hl = hm + 160;
            int* wc = reinterpret_cast<int*>(hl + 160);
            float* part = reinterpret_cast<float*>(smem + SM_MERGE);
            float L;
            uint32_t it = 0;
#pragma unroll 1
            while (true) {
                uint4 hd = ld_raw16p(hdr, live && tid < ncand);
                uint4 dv[MAXG / 16];
#pragma unroll
                for (int i = 0; i < MAXG / 16; i++) dv[i] = ld_raw16p(dat + (rr + 16 * i) * 64, live && rr + 16 * i < ncand);
                const bool hv = tid < ncand && hd.w == tag;
                int c = __reduce_add_sync(0xffffffffu, hv ? (int)hd.z : 0);
                if (live) {
                    if (tid < 160) { hm[tid] = hv ? __uint_as_float(hd.x) : NEG_BIG; hl[tid] = hv ? __uint_as_float(hd.y) : 0.f; }
                    if (lane == 0) wc[wid] = c;
                    bar_cons();
                }
                float mm[5], M = NEG_BIG;
#pragma unroll
                for (int i = 0; i < 5; i++) { mm[i] = hm[lane + 32 * i]; M = fmaxf(M, mm[i]); }
#pragma unroll
                for (int o = 16; o > 0; o >>= 1) M = fmaxf(M, __shfl_xor_sync(0xffffffffu, M, o));
                float ls = 0.f;
#pragma unroll
                for (int i = 0; i < 5; i++) ls += ex2((mm[i] - M) * LOG2E) * hl[lane + 32 * i];
                L = warp_sum(ls);
                const int total = wc[0] + wc[1] + wc[2] + wc[3] + wc[4];
                bool bad = total != TPH;
                float a0 = 0.f, a1 = 0.f, a2 = 0.f;
#pragma unroll
                for (int i = 0; i < MAXG / 16; i++) {
                    const float m = hm[rr + 16 * i];
                    const bool use = m != NEG_BIG;
                    const float w = use ? ex2((m - M) * LOG2E) : 0.f;
                    bad = bad || (use && dv[i].w != tag);
                    a0 += use ? w * __uint_as_float(dv[i].x) : 0.f;
                    a1 += use ? w * __uint_as_float(dv[i].y) : 0.f;
                    a2 += use ? w * __uint_as_float(dv[i].z) : 0.f;
                }
                a0 += __shfl_xor_sync(0xffffffffu, a0, 16);
                a1 += __shfl_xor_sync(0xffffffffu, a1, 16);
                a2 += __shfl_xor_sync(0xffffffffu, a2, 16);
                if (!live) break;
                if (lane < 16) { part[wid * 48 + 3 * k] = a0; part[wid * 48 + 3 * k + 1] = a1; part[wid * 48 + 3 * k + 2] = a2; }
                if (!bar_cons_or(bad)) break;
                if (++it > SPIN_LIMIT) __trap();
            }
            __nv_bfloat16* osw = reinterpret_cast<__nv_bfloat16*>(smem + SM_SC) + wid * 48;
            const float inv = __fdividef(1.0f, L);
            float o0 = 0.f, o1 = 0.f;
#pragma unroll
            for (int w = 0; w < 8; w++) { o0 += part[w * 48 + lane]; o1 += part[w * 48 + 32 + (lane & 15)]; }
            if (live) { osw[lane] = __float2bfloat16_rn(o0 * inv); if (lane < 16) osw[32 + lane] = __float2bfloat16_rn(o1 * inv); }
            __syncwarp();
            const uint32_t* os32 = reinterpret_cast<const uint32_t*>(osw);
#pragma unroll
            for (int ks = 0; ks < 3; ks++) { ob[ks][0] = os32[ks * 8 + j4]; ob[ks][1] = os32[ks * 8 + 4 + j4]; }
        }
        if (live) TS(10);
        {
            float acc[5][4] = {};
            uint32_t a[5][3][4];
            if (live) { mbar_wait(BAR(B_WO + ((wid * 5) >> 3)), 0); mbar_wait(BAR(B_WO + ((wid * 5 + 4) >> 3)), 0); }
#pragma unroll
            for (int i = 0; i < 5; i++) {
                const int mt = wid * 5 + i;
                const int cc = 2 * (mt & 3) + (mi & 1);
#pragma unroll
                for (int ks = 0; ks < 3; ks++) {
                    const int r = ks * 16 + l8 + 8 * (mi >> 1);
                    ldsm4t(a[i][ks], sb + SM_WO + (mt >> 2) * 6144 + r * 128 + ((cc ^ (r & 7)) << 4));
                }
            }
#pragma unroll
            for (int ks = 0; ks < 3; ks++) {
#pragma unroll
                for (int i = 0; i < 5; i++) mma16816(acc[i], a[i][ks], ob[ks][0], ob[ks][1]);
            }
            if (live && j4 == 0) {
#pragma unroll
                for (int i = 0; i < 5; i++) { stage[(wid * 5 + i) * 16 + g4] = acc[i][0]; stage[(wid * 5 + i) * 16 + 8 + g4] = acc[i][2]; }
            }
            if (live) bar_cons();
            const int o = tid >> 1, k = tid & 1;
            const float* sp = stage + o * 5 + k * 3;
            float v0 = sp[0], v1 = sp[1], v2 = k ? 0.f : sp[2];
            if (live) st_pk16(&g_h1[o][cta][k], __float_as_uint(v0), __float_as_uint(v1), __float_as_uint(v2), tag);
        }
        if (live) TS(11);
        {
            uint4 v = poll16(&g_h1[cta][tid >> 1][tid & 1], tag, live);
            float a0 = __uint_as_float(v.x), a1 = __uint_as_float(v.y), a2 = __uint_as_float(v.z);
#pragma unroll
            for (int o = 2; o <= 16; o <<= 1) {
                a0 += __shfl_xor_sync(0xffffffffu, a0, o);
                a1 += __shfl_xor_sync(0xffffffffu, a1, o);
                a2 += __shfl_xor_sync(0xffffffffu, a2, o);
            }
            if (live && lane < 2) { red[wid * 8 + lane * 3] = a0; red[wid * 8 + lane * 3 + 1] = a1; if (lane == 0) red[wid * 8 + 2] = a2; }
            if (live) bar_cons();
            if (live) TS(12);
            if (wid == 0 || !live) {
                float sum = 0.f;
                const int l5 = lane < 5 ? lane : 0;
#pragma unroll
                for (int w = 0; w < 8; w++) sum += red[w * 8 + l5];
                float x2 = bfr(own[16 + l5] + bfr(own[l5] * bfr(sum)));
                if (live && lane < 5) own[24 + lane] = x2;
                float y1 = __shfl_sync(0xffffffffu, x2, 1), y2 = __shfl_sync(0xffffffffu, x2, 2);
                float y3 = __shfl_sync(0xffffffffu, x2, 3), y4 = __shfl_sync(0xffffffffu, x2, 4);
                if (live && lane == 0) st_pk16(&g_x2[cta][0], pack_bf(x2, y1), pack_bf(y2, y3), pack_bf(y4, 0.f), tag);
            }
        }
        if (live) TS(13);
        if (cta < 96) {
            float* x2s = reinterpret_cast<float*>(smem + SM_X2);
            float* st8 = red + 256;
            if (tid < 128 || !live) {
                if (live) spin(P_DLY);
                uint4 v = poll16(&g_x2[tid & 127][0], tag, live);
                const float e0 = bf_lo(v.x), e1 = bf_hi(v.x), e2 = bf_lo(v.y), e3 = bf_hi(v.y), e4 = bf_lo(v.z);
                float* d = x2s + (tid & 127) * 5;
                if (live) { d[0] = e0; d[1] = e1; d[2] = e2; d[3] = e3; d[4] = e4; }
                float s1 = ((e0 + e1) + (e2 + e3)) + e4;
                s1 = warp_sum(s1);
                if (live && lane == 0) st8[wid] = s1;
            }
            if (live) bar_cons();
            if (live) TS(14);
            const float mean = ((st8[0] + st8[1]) + (st8[2] + st8[3])) * (1.0f / 640.0f);
            float q = 0.f;
#pragma unroll
            for (int i = 0; i < 20; i++) { float d = x2s[lane + 32 * i] - mean; q += d * d; }
            q = warp_sum(q);
            const float mean_b = bfr(mean);
            const float rden = __fdividef(1.0f, bfr(fsqrt(bfr(bfr(q * (1.0f / 640.0f)) + 1e-5f))));
            const uint32_t* cb32 = reinterpret_cast<const uint32_t*>(smem + SM_CB);
            const uint32_t* sb32 = reinterpret_cast<const uint32_t*>(smem + SM_SB);
#pragma unroll
            for (int rep = 0; rep < 2; rep++) {
                const int p = lane + 32 * rep;
                if (p < 40) {
                    int pp = wid * 40 + p;
                    float v0 = x2s[2 * pp], v1 = x2s[2 * pp + 1];
                    uint32_t cv = cb32[pp], sv = sb32[pp];
                    float n0 = bfr(bfr(v0 - mean_b) * rden), n1 = bfr(bfr(v1 - mean_b) * rden);
                    uint32_t hv = pack_bf(bfr(n0 * bf_lo(cv)) + bf_lo(sv), bfr(n1 * bf_hi(cv)) + bf_hi(sv));
                    if (live) h32[pp] = hv;
                }
            }
            float ag[2][4] = {}, au[2][4] = {};
            uint32_t a1[5][4], a3[5][4], bb[5][2];
            if (live) { mbar_wait(BAR(B_W1 + (wid >> 2)), 0); mbar_wait(BAR(B_W3 + (wid >> 2)), 0); }
#pragma unroll
            for (int ks = 0; ks < 5; ks++) {
                const int r = wid * 80 + ks * 16 + l8 + 8 * (mi >> 1);
                const uint32_t off = r * 32 + (((mi & 1) ^ ((r >> 2) & 1)) << 4);
                ldsm4t(a1[ks], sb + SM_W1 + off);
                ldsm4t(a3[ks], sb + SM_W3 + off);
            }
            __syncwarp();
#pragma unroll
            for (int ks = 0; ks < 5; ks++) {
                const int r0 = wid * 80 + ks * 16;
                bb[ks][0] = h32[(r0 >> 1) + j4]; bb[ks][1] = h32[(r0 >> 1) + 4 + j4];
            }
#pragma unroll
            for (int ks = 0; ks < 5; ks++) { mma16816(ag[ks & 1], a1[ks], bb[ks][0], bb[ks][1]); mma16816(au[ks & 1], a3[ks], bb[ks][0], bb[ks][1]); }
            if (live && j4 == 0) {
                red[wid * 64 + g4] = ag[0][0] + ag[1][0]; red[wid * 64 + 8 + g4] = ag[0][2] + ag[1][2];
                red[wid * 64 + 16 + g4] = au[0][0] + au[1][0]; red[wid * 64 + 24 + g4] = au[0][2] + au[1][2];
            }
            uint32_t a2[5][4];
            if (live) { mbar_wait(BAR(B_W2 + ((wid * 5) / 20)), 0); mbar_wait(BAR(B_W2 + ((wid * 5 + 4) / 20)), 0); }
#pragma unroll
            for (int i = 0; i < 5; i++) {
                const int mt = wid * 5 + i;
                const int cc = 2 * (mt & 3) + (mi & 1);
                const int r = l8 + 8 * (mi >> 1);
                ldsm4t(a2[i], sb + SM_W2 + (mt >> 2) * 2048 + r * 128 + ((cc ^ (r & 7)) << 4));
            }
            if (live) bar_cons();
            if (live) TS(15);
            float v = 0.f;
#pragma unroll
            for (int w = 0; w < 8; w++) v += red[w * 64 + lane];
            v = bfr(v);
            float up = __shfl_down_sync(0xffffffffu, v, 16);
            float hact = bfr(bfr(silu(v)) * up);
            float e0 = __shfl_sync(0xffffffffu, hact, 2 * j4), e1 = __shfl_sync(0xffffffffu, hact, 2 * j4 + 1);
            float e2 = __shfl_sync(0xffffffffu, hact, 2 * j4 + 8), e3 = __shfl_sync(0xffffffffu, hact, 2 * j4 + 9);
            const uint32_t b0 = pack_bf(e0, e1), b1 = pack_bf(e2, e3);
            float acc[5][4] = {};
#pragma unroll
            for (int i = 0; i < 5; i++) mma16816(acc[i], a2[i], b0, b1);
            if (live && j4 == 0) {
#pragma unroll
                for (int i = 0; i < 5; i++) { stage[(wid * 5 + i) * 16 + g4] = acc[i][0]; stage[(wid * 5 + i) * 16 + 8 + g4] = acc[i][2]; }
            }
            if (live) bar_cons();
            const int o = tid >> 1, k = tid & 1;
            const float* sp = stage + o * 5 + k * 3;
            float v0 = sp[0], v1 = sp[1], v2 = k ? 0.f : sp[2];
            if (live) st_pk16(&g_h3[o][cta][k], __float_as_uint(v0), __float_as_uint(v1), __float_as_uint(v2), tag);
        }
        if (live) TS(16);
        {
            float a0 = 0.f, a1 = 0.f, a2 = 0.f;
            if (tid < 192 || !live) {
                const int t2 = tid < 192 ? tid : tid - 128;
                if (live && cta < 96) spin(P_DLY);
                uint4 v = poll16(&g_h3[cta][t2 >> 1][t2 & 1], tag, live);
                a0 = __uint_as_float(v.x); a1 = __uint_as_float(v.y); a2 = __uint_as_float(v.z);
            }
#pragma unroll
            for (int o = 2; o <= 16; o <<= 1) {
                a0 += __shfl_xor_sync(0xffffffffu, a0, o);
                a1 += __shfl_xor_sync(0xffffffffu, a1, o);
                a2 += __shfl_xor_sync(0xffffffffu, a2, o);
            }
            float* fin = reinterpret_cast<float*>(smem + SM_FIN);
            if (live && lane < 2) { fin[wid * 8 + lane * 3] = a0; fin[wid * 8 + lane * 3 + 1] = a1; if (lane == 0) fin[wid * 8 + 2] = a2; }
            if (live) bar_cons();
            if (live) TS(17);
            if (wid == 0 || !live) {
                const int l5 = lane < 5 ? lane : 0;
                float sum = 0.f;
#pragma unroll
                for (int w = 0; w < 6; w++) sum += fin[w * 8 + l5];
                float y = own[24 + l5] + bfr(own[8 + l5] * bfr(sum));
                if (live && lane < 5) out[cta * 5 + lane] = __float2bfloat16_rn(y);
            }
            if (live && cta == 0 && tid == 0) g_epoch = tag;
        }
        if (live) { TS(18); break; }
        live = true;
    }
}

typedef CUresult (*EncodeFn)(CUtensorMap*, CUtensorMapDataType, cuuint32_t, void*, const cuuint64_t*, const cuuint64_t*,
                             const cuuint32_t*, const cuuint32_t*, CUtensorMapInterleave, CUtensorMapSwizzle,
                             CUtensorMapL2promotion, CUtensorMapFloatOOBfill);

void make_map(EncodeFn enc, CUtensorMap* tm, const void* ptr, uint64_t cols, uint64_t rows, uint32_t box_c, uint32_t box_r,
              CUtensorMapSwizzle sw, CUtensorMapL2promotion prom) {
    cuuint64_t dims[2] = {cols, rows};
    cuuint64_t strides[1] = {cols * 2};
    cuuint32_t box[2] = {box_c, box_r};
    cuuint32_t es[2] = {1, 1};
    enc(tm, CU_TENSOR_MAP_DATA_TYPE_BFLOAT16, 2, const_cast<void*>(ptr), dims, strides, box, es,
        CU_TENSOR_MAP_INTERLEAVE_NONE, sw, prom, CU_TENSOR_MAP_FLOAT_OOB_FILL_NONE);
}

}

extern "C" void kernel_launch(void* const* d_in, const int* in_sizes, int n_in, void* d_out, int out_size) {
    (void)in_sizes; (void)n_in; (void)out_size;
    static EncodeFn enc = nullptr;
    static int num_sms = 0;
    if (!enc) {
        void* fn = nullptr;
        cudaDriverEntryPointQueryResult qr;
        cudaGetDriverEntryPoint("cuTensorMapEncodeTiled", &fn, cudaEnableDefault, &qr);
        enc = (EncodeFn)fn;
        cudaDeviceGetAttribute(&num_sms, cudaDevAttrMultiProcessorCount, 0);
        cudaFuncSetAttribute(fused_decode_kernel, cudaFuncAttributeMaxDynamicSharedMemorySize, SM_TOTAL);
    }
    CUtensorMap tmK, tmV, tmMod, tmWq, tmWo, tmW1, tmW3, tmW2;
    const uint64_t kv_lines = (uint64_t)NH * SK * 3;
    make_map(enc, &tmK, d_in[1], 64, kv_lines, 64, 96, CU_TENSOR_MAP_SWIZZLE_128B, CU_TENSOR_MAP_L2_PROMOTION_L2_128B);
    make_map(enc, &tmV, d_in[2], 64, kv_lines, 64, 96, CU_TENSOR_MAP_SWIZZLE_128B, CU_TENSOR_MAP_L2_PROMOTION_L2_128B);
    make_map(enc, &tmWq, d_in[3], NH * DH, D, 48, 128, CU_TENSOR_MAP_SWIZZLE_NONE, CU_TENSOR_MAP_L2_PROMOTION_L2_128B);
    make_map(enc, &tmWo, d_in[4], D, NH * DH, 64, 48, CU_TENSOR_MAP_SWIZZLE_128B, CU_TENSOR_MAP_L2_PROMOTION_L2_128B);
    make_map(enc, &tmW1, d_in[6], FF, D, 16, 160, CU_TENSOR_MAP_SWIZZLE_32B, CU_TENSOR_MAP_L2_PROMOTION_L2_128B);
    make_map(enc, &tmW3, d_in[7], FF, D, 16, 160, CU_TENSOR_MAP_SWIZZLE_32B, CU_TENSOR_MAP_L2_PROMOTION_L2_128B);
    make_map(enc, &tmW2, d_in[8], D, FF, 64, 16, CU_TENSOR_MAP_SWIZZLE_128B, CU_TENSOR_MAP_L2_PROMOTION_L2_128B);
    make_map(enc, &tmMod, d_in[10], 6 * D, D, 32, 160, CU_TENSOR_MAP_SWIZZLE_64B, CU_TENSOR_MAP_L2_PROMOTION_L2_128B);
    int grid = num_sms < MAXG ? num_sms : MAXG;
    fused_decode_kernel<<<grid, NTHREADS, SM_TOTAL, cudaStreamPerThread>>>(
        tmK, tmV, tmMod, tmWq, tmWo, tmW1, tmW3, tmW2, (const __nv_bfloat16*)d_in[0], (const __nv_bfloat16*)d_in[9],
        (__nv_bfloat16*)d_out);
}
```

```cpp
#include <cuda_runtime.h>
#include <cuda_bf16.h>
#include <cuda.h>
#include <stdint.h>

namespace {

constexpr int D = 640, NH = 32, SK = 8192, DH = 192, FF = 1536;
constexpr int NG = 4;
constexpr int GH = 7;
constexpr int NGLOB = NH - NG * GH;
constexpr int NQH = GH + NGLOB;
constexpr int TILE = 32;
constexpr int TPH = SK / TILE;
constexpr int GT = GH * TPH;
constexpr int PT = NGLOB * TPH;
constexpr int CHUNK = TILE * DH * 2;
#define P_NSLOT 8
#define P_WIN 3
#define P_DLY 450
constexpr int NSLOT = P_NSLOT;
constexpr int WIN = P_WIN;
constexpr int MAXG = 144;
constexpr int NTHREADS = 288;
constexpr float NEG_BIG = -3.402823466e38f;

constexpr int SM_WMOD = 0;
constexpr int SM_WQ = 40960;
constexpr int SM_WO = 0;
constexpr int SM_W1 = 61440;
constexpr int SM_W3 = 81920;
constexpr int SM_RING = 102400;
constexpr int SM_MISC = SM_RING + NSLOT * CHUNK;
constexpr int SM_BARS = SM_MISC;
constexpr int SM_META = SM_BARS + 512;
constexpr int SM_Q = SM_META + 128;
constexpr int SM_SC = SM_Q + NQH * DH * 2;
constexpr int SM_H = SM_SC + 1280;
constexpr int SM_X = SM_H + 1280;
constexpr int SM_CB = SM_X + 1280;
constexpr int SM_SB = SM_CB + 1280;
constexpr int SM_OWN = SM_SB + 1280;
constexpr int SM_RED = SM_OWN + 128;
constexpr int SM_MERGE = SM_RED + 2048;
constexpr int SM_STAGE = SM_MERGE + 3200;
constexpr int SM_X2 = SM_STAGE + 2560;
constexpr int SM_FIN = SM_X2 + 2560;
constexpr int SM_TOTAL = SM_FIN + 256;
static_assert(SM_TOTAL <= 232448, "shared memory budget");

constexpr int B_FULL = 0;
constexpr int B_EMPTY = 8;
constexpr int B_MOD = 16;
constexpr int B_WQ = 20;
constexpr int B_WO = 25;
constexpr int B_W1 = 30;
constexpr int B_W3 = 32;
constexpr int B_W2 = 34;
constexpr int B_FLF = 36, B_FLE = 37, B_PRO = 38, B_DUMMY = 39;
static_assert(NSLOT <= 8 && NSLOT >= 6 && WIN <= 4 && WIN <= NSLOT - 3, "barrier map / end markers vs window");
constexpr uint32_t META_END = 0x10000u;

__device__ unsigned g_epoch;
__device__ unsigned g_ctr[2][(NG + 1) * 32];
__device__ __align__(128) unsigned long long g_mod[1920];
__device__ __align__(128) unsigned long long g_q[3072];
__device__ __align__(128) uint4 g_hdr[NH][MAXG];
__device__ __align__(128) uint4 g_dat[NH][MAXG][64];
__device__ __align__(128) uint4 g_h1[128][128][2];
__device__ __align__(128) uint4 g_x2[128][2];
__device__ __align__(128) uint4 g_h3[128][96][2];

#define TS(k) do {} while (0)
#define DBG(k) do {} while (0)
#define CLK(k) do {} while (0)

__device__ __forceinline__ uint32_t smem_u32(const void* p) { return (uint32_t)__cvta_generic_to_shared(p); }
__device__ __forceinline__ void mbar_init(uint32_t bar, uint32_t cnt) {
    asm volatile("mbarrier.init.shared::cta.b64 [%0], %1;" ::"r"(bar), "r"(cnt) : "memory");
}
__device__ __forceinline__ void mbar_expect_tx(uint32_t bar, uint32_t bytes) {
    asm volatile("mbarrier.arrive.expect_tx.shared::cta.b64 _, [%0], %1;" ::"r"(bar), "r"(bytes) : "memory");
}
__device__ __forceinline__ void mbar_arrive(uint32_t bar) {
    asm volatile("mbarrier.arrive.shared::cta.b64 _, [%0];" ::"r"(bar) : "memory");
}
constexpr uint32_t SPIN_LIMIT = 1u << 22;
__device__ __forceinline__ void mbar_wait(uint32_t bar, uint32_t parity) {
    asm volatile(
        "{\n.reg .pred p;\n.reg .u32 c;\nmov.u32 c, 0;\n"
        "LW:\nmbarrier.try_wait.parity.shared::cta.b64 p, [%0], %1;\n@p bra LD;\n"
        "add.u32 c, c, 1;\nsetp.lt.u32 p, c, 0x400000;\n@p bra LW;\ntrap;\nLD:\n}" ::"r"(bar), "r"(parity)
        : "memory");
}
__device__ __forceinline__ void mbar_wait3(uint32_t b0, uint32_t b1, uint32_t b2) {
    asm volatile(
        "{\n.reg .pred p, q, r;\n.reg .u32 c;\nmov.u32 c, 0;\n"
        "LW:\nmbarrier.try_wait.parity.shared::cta.b64 p, [%0], 0;\n"
        "mbarrier.try_wait.parity.shared::cta.b64 q, [%1], 0;\n"
        "mbarrier.try_wait.parity.shared::cta.b64 r, [%2], 0;\n"
        "and.pred p, p, q;\nand.pred p, p, r;\n@p bra LD;\n"
        "add.u32 c, c, 1;\nsetp.lt.u32 p, c, 0x400000;\n@p bra LW;\ntrap;\nLD:\n}" ::"r"(b0), "r"(b1), "r"(b2)
        : "memory");
}
__device__ __forceinline__ void tma2d(uint32_t dst, const CUtensorMap* tm, int c0, int c1, uint32_t bar) {
    asm volatile(
        "cp.async.bulk.tensor.2d.shared::cluster.global.mbarrier::complete_tx::bytes [%0], [%1, {%3, %4}], [%2];" ::"r"(dst),
        "l"(tm), "r"(bar), "r"(c0), "r"(c1)
        : "memory");
}
__device__ __forceinline__ void tma2d_hint(uint32_t dst, const CUtensorMap* tm, int c0, int c1, uint32_t bar, uint64_t pol) {
    asm volatile(
        "cp.async.bulk.tensor.2d.shared::cluster.global.mbarrier::complete_tx::bytes.L2::cache_hint [%0], [%1, {%3, %4}], [%2], %5;" ::"r"(dst),
        "l"(tm), "r"(bar), "r"(c0), "r"(c1), "l"(pol)
        : "memory");
}
__device__ __forceinline__ void prefetch_tm(const CUtensorMap* tm) {
    asm volatile("prefetch.tensormap [%0];" ::"l"(tm) : "memory");
}
__device__ __forceinline__ void ldsm4(uint32_t (&r)[4], uint32_t addr) {
    asm volatile("ldmatrix.sync.aligned.m8n8.x4.shared.b16 {%0,%1,%2,%3}, [%4];"
                 : "=r"(r[0]), "=r"(r[1]), "=r"(r[2]), "=r"(r[3])
                 : "r"(addr));
}
__device__ __forceinline__ void ldsm4t(uint32_t (&r)[4], uint32_t addr) {
    asm volatile("ldmatrix.sync.aligned.m8n8.x4.trans.shared.b16 {%0,%1,%2,%3}, [%4];"
                 : "=r"(r[0]), "=r"(r[1]), "=r"(r[2]), "=r"(r[3])
                 : "r"(addr));
}
__device__ __forceinline__ void mma16816(float (&d)[4], const uint32_t (&a)[4], uint32_t b0, uint32_t b1) {
    asm volatile(
        "mma.sync.aligned.m16n8k16.row.col.f32.bf16.bf16.f32 {%0,%1,%2,%3}, {%4,%5,%6,%7}, {%8,%9}, {%0,%1,%2,%3};"
        : "+f"(d[0]), "+f"(d[1]), "+f"(d[2]), "+f"(d[3])
        : "r"(a[0]), "r"(a[1]), "r"(a[2]), "r"(a[3]), "r"(b0), "r"(b1));
}
__device__ __forceinline__ void bar_cons() { asm volatile("bar.sync 1, 256;" ::: "memory"); }
__device__ __forceinline__ bool bar_cons_or(bool p) {
    uint32_t r;
    asm volatile("{\n.reg .pred p, q;\nsetp.ne.u32 p, %1, 0;\nbar.red.or.pred q, 1, 256, p;\nselp.u32 %0, 1, 0, q;\n}"
                 : "=r"(r) : "r"((uint32_t)p) : "memory");
    return r != 0;
}
__device__ __forceinline__ void spin(int cycles) {
    long long t0 = clock64();
    while (clock64() - t0 < cycles) {}
}

__device__ __forceinline__ float bfr(float x) { return __bfloat162float(__float2bfloat16_rn(x)); }
__device__ __forceinline__ uint32_t pack_bf(float lo, float hi) {
    __nv_bfloat162 t = __floats2bfloat162_rn(lo, hi);
    return *reinterpret_cast<uint32_t*>(&t);
}
__device__ __forceinline__ float bf_lo(uint32_t v) { return __uint_as_float(v << 16); }
__device__ __forceinline__ float bf_hi(uint32_t v) { return __uint_as_float(v & 0xffff0000u); }

__device__ __forceinline__ void st_pk8(unsigned long long* p, uint32_t v, uint32_t tag) {
    unsigned long long w = ((unsigned long long)tag << 32) | v;
    asm volatile("st.relaxed.gpu.global.b64 [%0], %1;" ::"l"(p), "l"(w) : "memory");
}
__device__ __forceinline__ unsigned long long ld_raw8(const unsigned long long* p) {
    unsigned long long w;
    asm volatile("ld.relaxed.gpu.global.b64 %0, [%1];" : "=l"(w) : "l"(p) : "memory");
    return w;
}
template <int N>
__device__ __forceinline__ void poll8(const unsigned long long* base, const int (&off)[N], uint32_t (&val)[N], uint32_t tag) {
    uint32_t it = 0;
    while (true) {
        unsigned long long w[N];
#pragma unroll
        for (int i = 0; i < N; i++) w[i] = ld_raw8(base + off[i]);
        bool ok = true;
#pragma unroll
        for (int i = 0; i < N; i++) { ok = ok && ((uint32_t)(w[i] >> 32) == tag); val[i] = (uint32_t)w[i]; }
        if (ok) break;
        if (++it > SPIN_LIMIT) __trap();
    }
}
__device__ __forceinline__ void st_pk16(uint4* p, uint32_t a, uint32_t b, uint32_t c, uint32_t tag) {
    asm volatile(
        "{\n.reg .b128 t;\n.reg .b64 lo, hi;\nmov.b64 lo, {%1, %2};\nmov.b64 hi, {%3, %4};\nmov.b128 t, {lo, hi};\n"
        "st.relaxed.gpu.global.b128 [%0], t;\n}" ::"l"(p), "r"(a), "r"(b), "r"(c), "r"(tag)
        : "memory");
}
template <int OFF = 0>
__device__ __forceinline__ uint4 ld_raw16p(const uint4* p, uint32_t on) {
    uint4 v;
    asm volatile(
        "{\n.reg .b128 t;\n.reg .b64 lo, hi;\n.reg .pred q;\nsetp.ne.u32 q, %5, 0;\n"
        "mov.b64 lo, 0;\nmov.b128 t, {lo, lo};\n"
        "@q ld.relaxed.gpu.global.b128 t, [%4 + %6];\nmov.b128 {lo, hi}, t;\n"
        "mov.b64 {%0, %1}, lo;\nmov.b64 {%2, %3}, hi;\n}"
        : "=r"(v.x), "=r"(v.y), "=r"(v.z), "=r"(v.w)
        : "l"(p), "r"(on), "n"(OFF * 16)
        : "memory");
    return v;
}
template <int N, int STRIDE, int I = 0>
struct LoadN {
    static __device__ __forceinline__ void run(uint4* v, const uint4* p, bool live, int base, int step, int lim) {
        v[I] = ld_raw16p<I * STRIDE>(p, live && base + step * I < lim);
        LoadN<N, STRIDE, I + 1>::run(v, p, live, base, step, lim);
    }
};
template <int N, int STRIDE>
struct LoadN<N, STRIDE, N> {
    static __device__ __forceinline__ void run(uint4*, const uint4*, bool, int, int, int) {}
};
__device__ __forceinline__ uint4 poll16(const uint4* p, uint32_t tag, bool live) {
    uint32_t it = 0;
    uint4 v;
    while (true) {
        v = ld_raw16p(p, live);
        if (!live || v.w == tag) break;
        if (++it > SPIN_LIMIT) __trap();
    }
    return v;
}
__device__ __forceinline__ void st_zero16(void* p) {
    asm volatile("st.relaxed.gpu.global.v4.u32 [%0], {%1, %1, %1, %1};" ::"l"(p), "r"(0u) : "memory");
}
__device__ __forceinline__ float ex2(float x) {
    float y;
    asm("ex2.approx.ftz.f32 %0, %1;" : "=f"(y) : "f"(x));
    return y;
}
__device__ __forceinline__ float fsqrt(float x) {
    float y;
    asm("sqrt.approx.f32 %0, %1;" : "=f"(y) : "f"(x));
    return y;
}
constexpr float LOG2E = 1.4426950408889634f;
__device__ __forceinline__ float silu(float a) { return __fdividef(a, 1.0f + ex2(-a * LOG2E)); }
__device__ __forceinline__ float warp_sum(float v) {
#pragma unroll
    for (int o = 16; o > 0; o >>= 1) v += __shfl_xor_sync(0xffffffffu, v, o);
    return v;
}

__device__ __forceinline__ void ln_stats(const float (&v)[20], float& mean_b, float& den_b) {
    float s = 0.f;
#pragma unroll
    for (int i = 0; i < 20; i++) s += v[i];
    s = warp_sum(s);
    float mean = s * (1.0f / 640.0f);
    float q = 0.f;
#pragma unroll
    for (int i = 0; i < 20; i++) { float d = v[i] - mean; q += d * d; }
    q = warp_sum(q);
    float var_b = bfr(q * (1.0f / 640.0f));
    mean_b = bfr(mean);
    den_b = bfr(fsqrt(bfr(var_b + 1e-5f)));
}

struct Window {
    uint32_t bar[WIN];
    uint32_t par[WIN];
    __device__ __forceinline__ void init(uint32_t dummy) {
#pragma unroll
        for (int i = 0; i < WIN; i++) { bar[i] = dummy; par[i] = 1; }
    }
    __device__ __forceinline__ void push(uint32_t b, uint32_t p) {
        mbar_wait(bar[0], par[0]);
#pragma unroll
        for (int i = 0; i + 1 < WIN; i++) { bar[i] = bar[i + 1]; par[i] = par[i + 1]; }
        bar[WIN - 1] = b; par[WIN - 1] = p;
    }
};

__global__ void __launch_bounds__(NTHREADS, 1)
fused_decode_kernel(const __grid_constant__ CUtensorMap tmK, const __grid_constant__ CUtensorMap tmV,
                    const __grid_constant__ CUtensorMap tmMod, const __grid_constant__ CUtensorMap tmWq,
                    const __grid_constant__ CUtensorMap tmWo, const __grid_constant__ CUtensorMap tmW1,
                    const __grid_constant__ CUtensorMap tmW3, const __grid_constant__ CUtensorMap tmW2,
                    const __nv_bfloat16* __restrict__ x_in, const __nv_bfloat16* __restrict__ c_in,
                    __nv_bfloat16* __restrict__ out) {
    extern __shared__ __align__(1024) uint8_t smem[];
    const uint32_t sb = smem_u32(smem);
    const int tid = threadIdx.x, wid = tid >> 5, lane = tid & 31;
    const int cta = blockIdx.x, G = gridDim.x;
    const int grp = cta % NG, rank = cta / NG;
    const uint32_t bars = sb + SM_BARS;
    auto BAR = [&](int i) { return bars + 8u * i; };
    volatile uint32_t* meta = reinterpret_cast<volatile uint32_t*>(smem + SM_META);

    if (wid >= 8) {
        Window win;
        unsigned epoch = 0;
        if (tid == 256) {
            TS(0);
            if (sb & 1023u) __trap();
            asm volatile("ld.relaxed.gpu.global.u32 %0, [%1];" : "=r"(epoch) : "l"(&g_epoch) : "memory");
            prefetch_tm(&tmMod); prefetch_tm(&tmWq); prefetch_tm(&tmK); prefetch_tm(&tmV);
#pragma unroll
            for (int i = 0; i < 4; i++) mbar_init(BAR(B_MOD + i), 1);
            mbar_init(BAR(B_DUMMY), 1);
            asm volatile("fence.mbarrier_init.release.cluster;" ::: "memory");
            asm volatile("fence.proxy.async.shared::cta;" ::: "memory");
            win.init(BAR(B_DUMMY));
            if (cta < 120) {
#pragma unroll 1
                for (int i = 0; i < WIN; i++) {
                    win.push(BAR(B_MOD + i), 0);
                    mbar_expect_tx(BAR(B_MOD + i), 10240);
                    tma2d(sb + SM_WMOD + i * 10240, &tmMod, cta * 32, i * 160, BAR(B_MOD + i));
                }
            }
#pragma unroll 1
            for (int i = 0; i < B_DUMMY; i++) {
                if (i >= B_MOD && i < B_MOD + 4) continue;
                int cnt = (i >= B_EMPTY && i < B_MOD) ? 2 : (i == B_FLF ? 4 : 1);
                mbar_init(BAR(i), cnt);
            }
            asm volatile("fence.mbarrier_init.release.cluster;" ::: "memory");
            asm volatile("fence.proxy.async.shared::cta;" ::: "memory");
        }
        __syncwarp();
        __syncthreads();
        if (tid == 256) {
            prefetch_tm(&tmWo); prefetch_tm(&tmW1); prefetch_tm(&tmW3); prefetch_tm(&tmW2);
            unsigned* ctr = &g_ctr[epoch & 1][grp * 32];
            unsigned* gctr = &g_ctr[epoch & 1][NG * 32];
            if (cta == 0) {
                for (int g = 0; g <= NG; g++) g_ctr[(epoch + 1) & 1][g * 32] = 0;
            }
            unsigned pend = atomicAdd(ctr, 1);
            if (cta < 120) {
#pragma unroll 1
                for (int i = WIN; i < 4; i++) {
                    win.push(BAR(B_MOD + i), 0);
                    mbar_expect_tx(BAR(B_MOD + i), 10240);
                    tma2d(sb + SM_WMOD + i * 10240, &tmMod, cta * 32, i * 160, BAR(B_MOD + i));
                }
            }
            if (cta < 128) {
#pragma unroll 1
                for (int i = 0; i < 5; i++) {
                    win.push(BAR(B_WQ + i), 0);
                    mbar_expect_tx(BAR(B_WQ + i), 12288);
                    tma2d(sb + SM_WQ + i * 12288, &tmWq, cta * 48, i * 128, BAR(B_WQ + i));
                }
            }
            uint64_t pol;
            asm volatile("createpolicy.fractional.L2::evict_first.b64 %0, 1.0;" : "=l"(pol));
            int s = 0; uint32_t par = 0;
            int ntiles = 0, run = -1, last_head = -1;
            bool glob = false;
#pragma unroll 1
            while (true) {
                unsigned t = pend;
                if (!glob && t >= (unsigned)GT) { glob = true; t = atomicAdd(gctr, 1); }
                if (glob && t >= (unsigned)PT) break;
                pend = atomicAdd(glob ? gctr : ctr, 1);
                ntiles++;
                const int hl = t / TPH, tile = t % TPH;
                const int head = glob ? NG * GH + hl : grp * GH + hl;
                const int qidx = glob ? GH + hl : hl;
                if (head != last_head) { last_head = head; run++; meta[16 + run] = head; }
                const int line0 = (head * SK + tile * TILE) * 3;
#pragma unroll 1
                for (int kv = 0; kv < 2; kv++) {
                    win.push(BAR(B_FULL + s), par);
                    mbar_wait(BAR(B_EMPTY + s), par ^ 1);
                    meta[s] = run | (qidx << 8);
                    mbar_expect_tx(BAR(B_FULL + s), CHUNK);
                    tma2d_hint(sb + SM_RING + s * CHUNK, kv ? &tmV : &tmK, 0, line0, BAR(B_FULL + s), pol);
                    if (++s == NSLOT) { s = 0; par ^= 1; }
                }
            }
            TS(5);
            meta[16 + run + 1] = 0xFFu;
#pragma unroll 1
            for (int e = 0; e < 2; e++) {
                mbar_wait(BAR(B_EMPTY + s), par ^ 1);
                meta[s] = (run + 1) | META_END;
                mbar_arrive(BAR(B_FULL + s));
                if (++s == NSLOT) { s = 0; par ^= 1; }
                if (++s == NSLOT) { s = 0; par ^= 1; }
            }
            if (cta < 128) {
                mbar_wait(BAR(B_PRO), 0);
#pragma unroll 1
                for (int i = 0; i < 5; i++) {
                    win.push(BAR(B_WO + i), 0);
                    mbar_expect_tx(BAR(B_WO + i), 12288);
                    tma2d(sb + SM_WO + (2 * i) * 6144, &tmWo, (2 * i) * 64, cta * 48, BAR(B_WO + i));
                    tma2d(sb + SM_WO + (2 * i + 1) * 6144, &tmWo, (2 * i + 1) * 64, cta * 48, BAR(B_WO + i));
                }
                if (cta < 96) {
#pragma unroll 1
                    for (int i = 0; i < 4; i++) {
                        const int m = i & 1, hf = i >> 1;
                        const uint32_t bar = BAR((m ? B_W3 : B_W1) + hf);
                        const uint32_t dst = sb + (m ? SM_W3 : SM_W1) + hf * 10240;
                        const CUtensorMap* tm = m ? &tmW3 : &tmW1;
                        win.push(bar, 0);
                        mbar_expect_tx(bar, 10240);
                        tma2d(dst, tm, cta * 16, hf * 320, bar);
                        tma2d(dst + 5120, tm, cta * 16, hf * 320 + 160, bar);
                    }
#pragma unroll 1
                    for (int i = 0; i < 2; i++) {
                        win.push(BAR(B_W2 + i), 0);
                        mbar_wait(BAR(B_EMPTY + s), par ^ 1);
                        meta[10 + i] = s;
                        mbar_expect_tx(BAR(B_W2 + i), 10240);
#pragma unroll 1
                        for (int b = 0; b < 5; b++)
                            tma2d(sb + SM_RING + s * CHUNK + b * 2048, &tmW2, (5 * i + b) * 64, cta * 16, BAR(B_W2 + i));
                        if (++s == NSLOT) { s = 0; par ^= 1; }
                    }
                }
            }
            TS(6);
        }
    } else {
    const int g4 = lane >> 2, j4 = lane & 3, mi = lane >> 3, l8 = lane & 7;
    uint32_t* sc32 = reinterpret_cast<uint32_t*>(smem + SM_SC);
    uint32_t* h32 = reinterpret_cast<uint32_t*>(smem + SM_H);
    uint32_t* x32 = reinterpret_cast<uint32_t*>(smem + SM_X);
    uint32_t* q32 = reinterpret_cast<uint32_t*>(smem + SM_Q);
    float* red = reinterpret_cast<float*>(smem + SM_RED);
    float* stage = reinterpret_cast<float*>(smem + SM_STAGE);
    float* own = reinterpret_cast<float*>(smem + SM_OWN);

    {
        const uint32_t* cg = reinterpret_cast<const uint32_t*>(c_in);
        const uint32_t* xg = reinterpret_cast<const uint32_t*>(x_in);
        uint32_t c0 = cg[tid], x0 = xg[tid], c1 = 0, x1 = 0;
        if (tid < 64) { c1 = cg[256 + tid]; x1 = xg[256 + tid]; }
        unsigned epoch = 0;
        if (tid == 0) asm volatile("ld.relaxed.gpu.global.u32 %0, [%1];" : "=r"(epoch) : "l"(&g_epoch) : "memory");
        if (cta < 120 && tid < 8) st_zero16(reinterpret_cast<uint4*>(&g_mod[cta * 16]) + tid);
        if (cta < 128 && tid >= 32 && tid < 44) st_zero16(reinterpret_cast<uint4*>(&g_q[cta * 24]) + (tid - 32));
        if (cta < 128) {
            if (tid >= 64 && tid < 66) st_zero16(&g_x2[cta][tid - 64]);
            st_zero16(&g_h1[tid >> 1][cta][tid & 1]);
            if (cta < 96) st_zero16(&g_h3[tid >> 1][cta][tid & 1]);
        }
#pragma unroll 1
        for (int f = tid >> 6; f < NQH; f += 4) {
            const int head = f < GH ? grp * GH + f : NG * GH + (f - GH);
            const int idx = f < GH ? rank : cta;
            st_zero16(&g_dat[head][idx][tid & 63]);
            if ((tid & 63) == 0) st_zero16(&g_hdr[head][idx]);
        }
        sc32[tid] = pack_bf(silu(bf_lo(c0)), silu(bf_hi(c0))); x32[tid] = x0;
        if (tid < 64) { sc32[256 + tid] = pack_bf(silu(bf_lo(c1)), silu(bf_hi(c1))); x32[256 + tid] = x1; }
        if (tid == 0) meta[8] = epoch + 1;
    }
    __syncthreads();
    const uint32_t tag = meta[8];

    float mean_x = 0.f, rden_x = 1.f;
    if (cta < 128) {
        float xv[20];
#pragma unroll
        for (int i = 0; i < 10; i++) { uint32_t v = x32[lane + 32 * i]; xv[2 * i] = bf_lo(v); xv[2 * i + 1] = bf_hi(v); }
        float den;
        ln_stats(xv, mean_x, den);
        rden_x = __fdividef(1.0f, den);
    }

    if (cta < 120) {
        float acc[2][4] = {};
        uint32_t a[5][2][4], bb[5][2];
        const uint32_t base = sb + SM_WMOD + (wid >> 1) * 10240;
#pragma unroll
        for (int ks = 0; ks < 5; ks++) {
            const int r0 = wid * 80 + ks * 16;
            bb[ks][0] = sc32[(r0 >> 1) + j4]; bb[ks][1] = sc32[(r0 >> 1) + 4 + j4];
        }
        mbar_wait(BAR(B_MOD + (wid >> 1)), 0);
#pragma unroll
        for (int ks = 0; ks < 5; ks++) {
            const int r = (wid & 1) * 80 + ks * 16 + l8 + 8 * (mi >> 1);
#pragma unroll
            for (int mt = 0; mt < 2; mt++) ldsm4t(a[ks][mt], base + r * 64 + (((2 * mt + (mi & 1)) ^ ((r >> 1) & 3)) << 4));
        }
#pragma unroll
        for (int ks = 0; ks < 5; ks++) { mma16816(acc[0], a[ks][0], bb[ks][0], bb[ks][1]); mma16816(acc[1], a[ks][1], bb[ks][0], bb[ks][1]); }
        if (j4 == 0) {
#pragma unroll
            for (int mt = 0; mt < 2; mt++) { red[wid * 64 + mt * 16 + g4] = acc[mt][0]; red[wid * 64 + mt * 16 + 8 + g4] = acc[mt][2]; }
        }
        bar_cons();
        if (wid == 0) {
            float v = 0.f;
#pragma unroll
            for (int w = 0; w < 8; w++) v += red[w * 64 + lane];
            float o = __shfl_down_sync(0xffffffffu, v, 1);
            if (!(lane & 1)) st_pk8(&g_mod[cta * 16 + (lane >> 1)], pack_bf(v, o), tag);
        }
    }
    TS(1);

    if (cta < 128) {
        {
            const int off[4] = {tid, 320 + tid, tid < 64 ? 256 + tid : tid, tid < 64 ? 576 + tid : 320 + tid};
            uint32_t val[4];
            poll8<4>(g_mod, off, val, tag);
#pragma unroll
            for (int rep = 0; rep < 2; rep++) {
                int p = tid + rep * 256;
                if (p < 320) {
                    uint32_t sa = val[2 * rep], ca = val[2 * rep + 1];
                    uint32_t xx = x32[p];
                    float n0 = bfr(bfr(bf_lo(xx) - mean_x) * rden_x), n1 = bfr(bfr(bf_hi(xx) - mean_x) * rden_x);
                    float h0 = bfr(n0 * bfr(1.0f + bf_lo(ca))) + bf_lo(sa);
                    float h1 = bfr(n1 * bfr(1.0f + bf_hi(ca))) + bf_hi(sa);
                    h32[p] = pack_bf(h0, h1);
                }
            }
        }
        bar_cons();
        TS(2);
        float acc[3][4] = {};
        uint32_t a[5][3][4], bb[5][2];
#pragma unroll
        for (int ks = 0; ks < 5; ks++) {
            const int r0 = wid * 80 + ks * 16;
            bb[ks][0] = h32[(r0 >> 1) + j4]; bb[ks][1] = h32[(r0 >> 1) + 4 + j4];
        }
        mbar_wait(BAR(B_WQ + ((wid * 80) >> 7)), 0);
        mbar_wait(BAR(B_WQ + ((wid * 80 + 79) >> 7)), 0);
#pragma unroll
        for (int ks = 0; ks < 5; ks++) {
            const int r = wid * 80 + ks * 16 + l8 + 8 * (mi >> 1);
#pragma unroll
            for (int mt = 0; mt < 3; mt++) ldsm4t(a[ks][mt], sb + SM_WQ + r * 96 + ((2 * mt + (mi & 1)) << 4));
        }
#pragma unroll
        for (int ks = 0; ks < 5; ks++) {
#pragma unroll
            for (int mt = 0; mt < 3; mt++) mma16816(acc[mt], a[ks][mt], bb[ks][0], bb[ks][1]);
        }
        if (j4 == 0) {
#pragma unroll
            for (int mt = 0; mt < 3; mt++) { red[wid * 64 + mt * 16 + g4] = acc[mt][0]; red[wid * 64 + mt * 16 + 8 + g4] = acc[mt][2]; }
        }
        bar_cons();
        if (tid < 64) {
            float v = 0.f;
            if (tid < 48) {
#pragma unroll
                for (int w = 0; w < 8; w++) v += red[w * 64 + tid];
            }
            float o = __shfl_down_sync(0xffffffffu, v, 1);
            if (tid < 48 && !(tid & 1)) st_pk8(&g_q[cta * 24 + (tid >> 1)], pack_bf(v, o), tag);
        }
        TS(3);
    }
    {
        int off[5];
#pragma unroll
        for (int j = 0; j < 5; j++) {
            int p = tid + 256 * j;
            if (p >= NQH * 96) p = tid;
            off[j] = p < GH * 96 ? grp * GH * 96 + p : NG * GH * 96 + (p - GH * 96);
        }
        uint32_t val[5];
        poll8<5>(g_q, off, val, tag);
#pragma unroll
        for (int j = 0; j < 5; j++)
            if (tid + 256 * j < NQH * 96) q32[tid + 256 * j] = val[j];
    }
    bar_cons();
    if (tid == 0) mbar_arrive(BAR(B_PRO));
    TS(4);

    bool live = true;
    if (wid < 4) {
        const int pair = wid >> 1, half = wid & 1;
        const int rowK = half * 16 + l8 + 8 * (mi & 1), hiK = mi >> 1;
        const int rowV = half * 16 + l8 + 8 * (mi >> 1), hiV = mi & 1;
        float acc[12][4];
#pragma unroll
        for (int i = 0; i < 12; i++) { acc[i][0] = acc[i][1] = acc[i][2] = acc[i][3] = 0.f; }
        float m_run = NEG_BIG, l_run = 0.f;
        uint32_t qf[12][2];
#pragma unroll
        for (int i = 0; i < 12; i++) { qf[i][0] = qf[i][1] = 0; }
        int cur = -1, flushed = 0, cnt = 0;
        int s = 2 * pair; uint32_t par = 0;
        float* mb = reinterpret_cast<float*>(smem + SM_MERGE) + wid * 200;
#pragma unroll 1
        while (true) {
            mbar_wait(BAR(B_FULL + s), par);
            const uint32_t mt_ = meta[s];
            const int run = mt_ & 0xff;
            if (run != cur) {
#pragma unroll 1
                while (flushed < run) {
                    if (flushed != cur) {
#pragma unroll
                        for (int i = 0; i < 12; i++) { acc[i][0] = acc[i][1] = acc[i][2] = acc[i][3] = 0.f; }
                        m_run = NEG_BIG; l_run = 0.f; cnt = 0;
                    }
                    float v[24];
#pragma unroll
                    for (int i = 0; i < 12; i++) { v[2 * i] = acc[i][0] + acc[i][1]; v[2 * i + 1] = acc[i][2] + acc[i][3]; }
                    float u[12], w6[6];
                    const bool o1 = j4 & 1, o2 = j4 & 2;
#pragma unroll
                    for (int i = 0; i < 12; i++) {
                        float send = o1 ? v[i] : v[i + 12], keep = o1 ? v[i + 12] : v[i];
                        u[i] = keep + __shfl_xor_sync(0xffffffffu, send, 1);
                    }
#pragma unroll
                    for (int i = 0; i < 6; i++) {
                        float send = o2 ? u[i] : u[i + 6], keep = o2 ? u[i + 6] : u[i];
                        w6[i] = keep + __shfl_xor_sync(0xffffffffu, send, 2);
                    }
                    float l = l_run;
                    l += __shfl_xor_sync(0xffffffffu, l, 4);
                    l += __shfl_xor_sync(0xffffffffu, l, 8);
                    l += __shfl_xor_sync(0xffffffffu, l, 16);
                    mbar_wait(BAR(B_FLE), (flushed & 1) ^ 1);
#pragma unroll
                    for (int i = 0; i < 6; i++) {
                        int idx = (o1 ? 12 : 0) + (o2 ? 6 : 0) + i;
                        mb[4 + 16 * (idx >> 1) + 8 * (idx & 1) + g4] = w6[i];
                    }
                    if (lane == 0) { mb[0] = m_run; mb[1] = l; mb[2] = __int_as_float(cnt); }
                    __syncwarp();
                    if (lane == 0) mbar_arrive(BAR(B_FLF));
                    flushed++;
                    cur = -1;
                }
                if (mt_ & META_END) {
                    mbar_wait(BAR(B_FLE), (flushed & 1) ^ 1);
                    if (lane == 0) mbar_arrive(BAR(B_FLF));
                    break;
                }
                cur = run;
                const int qi = (mt_ >> 8) & 0xff;
#pragma unroll
                for (int i = 0; i < 12; i++) { acc[i][0] = acc[i][1] = acc[i][2] = acc[i][3] = 0.f; }
                m_run = NEG_BIG; l_run = 0.f; cnt = 0;
#pragma unroll
                for (int ks = 0; ks < 12; ks++) {
                    qf[ks][0] = q32[qi * 96 + ks * 8 + j4];
                    qf[ks][1] = q32[qi * 96 + ks * 8 + 4 + j4];
                }
            }
            cnt++;
            const uint32_t kb = sb + SM_RING + s * CHUNK;
            float sc[3][4] = {};
            {
                uint32_t a[12][4];
#pragma unroll
                for (int t = 0; t < 3; t++) {
                    const int ln = rowK * 3 + t;
#pragma unroll
                    for (int kk = 0; kk < 4; kk++) ldsm4(a[t * 4 + kk], kb + ln * 128 + (((2 * kk + hiK) ^ (ln & 7)) << 4));
                }
#pragma unroll
                for (int kk = 0; kk < 4; kk++) {
#pragma unroll
                    for (int t = 0; t < 3; t++) mma16816(sc[t], a[t * 4 + kk], qf[t * 4 + kk][0], qf[t * 4 + kk][1]);
                }
            }
            __syncwarp();
            if (lane == 0) mbar_arrive(BAR(B_EMPTY + s));
            int sv = s + 1; uint32_t parv = par;
            if (sv == NSLOT) { sv = 0; parv ^= 1; }
            const float scale = 0.07216878364870322f;
            float s0 = bfr(bfr(sc[0][0] + sc[1][0] + sc[2][0]) * scale);
            float s1 = bfr(bfr(sc[0][2] + sc[1][2] + sc[2][2]) * scale);
            float tm = fmaxf(s0, s1);
            tm = fmaxf(tm, __shfl_xor_sync(0xffffffffu, tm, 4));
            tm = fmaxf(tm, __shfl_xor_sync(0xffffffffu, tm, 8));
            tm = fmaxf(tm, __shfl_xor_sync(0xffffffffu, tm, 16));
            if (tm > m_run) {
                float alpha = ex2((m_run - tm) * LOG2E);
                l_run *= alpha;
#pragma unroll
                for (int i = 0; i < 12; i++) { acc[i][0] *= alpha; acc[i][1] *= alpha; acc[i][2] *= alpha; acc[i][3] *= alpha; }
                m_run = tm;
            }
            float p0 = ex2((s0 - m_run) * LOG2E);
            float p1 = ex2((s1 - m_run) * LOG2E);
            l_run += p0 + p1;
            uint32_t b0 = 0, b1 = 0;
            if (j4 == (g4 >> 1)) {
                uint32_t e0 = pack_bf(p0, 0.f) & 0xffffu, e1 = pack_bf(p1, 0.f) & 0xffffu;
                b0 = (g4 & 1) ? (e0 << 16) : e0;
                b1 = (g4 & 1) ? (e1 << 16) : e1;
            }
            mbar_wait(BAR(B_FULL + sv), parv);
            const uint32_t vb = sb + SM_RING + sv * CHUNK;
            {
                uint32_t a[12][4];
#pragma unroll
                for (int t = 0; t < 3; t++) {
                    const int ln = rowV * 3 + t;
#pragma unroll
                    for (int kk = 0; kk < 4; kk++) ldsm4t(a[t * 4 + kk], vb + ln * 128 + (((2 * kk + hiV) ^ (ln & 7)) << 4));
                }
#pragma unroll
                for (int i = 0; i < 12; i++) mma16816(acc[i], a[i], b0, b1);
            }
            __syncwarp();
            if (lane == 0) mbar_arrive(BAR(B_EMPTY + sv));
            s += 4;
            if (s >= NSLOT) { s -= NSLOT; par ^= 1; }
        }
        TS(7);
    } else if (wid == 4) {
        const float* mb = reinterpret_cast<const float*>(smem + SM_MERGE);
#pragma unroll 1
        for (int f = 0;; f++) {
            mbar_wait(BAR(B_FLF), f & 1);
            const int head = (int)meta[16 + f];
            if (head == 0xFF) break;
            float m0 = mb[0], m1 = mb[200], m2 = mb[400], m3 = mb[600];
            float M = fmaxf(fmaxf(m0, m1), fmaxf(m2, m3));
            float w0 = ex2((m0 - M) * LOG2E), w1 = ex2((m1 - M) * LOG2E);
            float w2 = ex2((m2 - M) * LOG2E), w3 = ex2((m3 - M) * LOG2E);
            const int idx = head < NG * GH ? rank : cta;
            uint4* dst = &g_dat[head][idx][0];
            float o[6];
#pragma unroll
            for (int i = 0; i < 6; i++) {
                int d = 4 + (i < 3 ? 3 * lane + i : 96 + 3 * lane + (i - 3));
                o[i] = w0 * mb[d] + w1 * mb[200 + d] + w2 * mb[400 + d] + w3 * mb[600 + d];
            }
            float L = w0 * mb[1] + w1 * mb[201] + w2 * mb[401] + w3 * mb[601];
            const uint32_t tiles = __float_as_int(mb[2]) + __float_as_int(mb[402]);
            st_pk16(dst + lane, __float_as_uint(o[0]), __float_as_uint(o[1]), __float_as_uint(o[2]), tag);
            st_pk16(dst + 32 + lane, __float_as_uint(o[3]), __float_as_uint(o[4]), __float_as_uint(o[5]), tag);
            if (lane == 0) st_pk16(&g_hdr[head][idx], __float_as_uint(M), __float_as_uint(L), tiles, tag);
            __syncwarp();
            if (lane == 0) mbar_arrive(BAR(B_FLE));
        }
        TS(8);
    } else if (wid >= 6) {
        if (cta < 128) {
            const int t = tid - 192;
            uint32_t* cb32 = reinterpret_cast<uint32_t*>(smem + SM_CB);
            uint32_t* sb32 = reinterpret_cast<uint32_t*>(smem + SM_SB);
            const int col = cta * 5 + t;
            int off[12];
            uint32_t val[12];
#pragma unroll
            for (int rep = 0; rep < 5; rep++) { off[2 * rep] = 960 + t + 64 * rep; off[2 * rep + 1] = 1280 + t + 64 * rep; }
            off[10] = t < 5 ? (1280 + col) >> 1 : 960;
            off[11] = t < 5 ? (3200 + col) >> 1 : 960;
            poll8<12>(g_mod, off, val, tag);
#pragma unroll
            for (int rep = 0; rep < 5; rep++) {
                sb32[t + 64 * rep] = val[2 * rep];
                cb32[t + 64 * rep] = pack_bf(1.0f + bf_lo(val[2 * rep + 1]), 1.0f + bf_hi(val[2 * rep + 1]));
            }
            if (t < 5) {
                own[t] = (col & 1) ? bf_hi(val[10]) : bf_lo(val[10]);
                own[8 + t] = (col & 1) ? bf_hi(val[11]) : bf_lo(val[11]);
                uint32_t xx = x32[col >> 1];
                own[16 + t] = (col & 1) ? bf_hi(xx) : bf_lo(xx);
            }
        }
        live = false;
    }
    const uint32_t sb0 = sb;
    const int tid0 = tid;
#pragma unroll 1
    while (cta < 128) {
        uint32_t sb = sb0; int tid = tid0;
        asm volatile("" : "+r"(sb), "+r"(tid));
        const int wid = tid >> 5, lane = tid & 31;
        const int g4 = lane >> 2, j4 = lane & 3, mi = lane >> 3, l8 = lane & 7;
        if (live) bar_cons();
        if (live) TS(9);
        CLK(0);
        {
            const int h = cta >> 2, js = cta & 3;
            const int ncand = h >= NG * GH ? G : (G - h / GH + NG - 1) / NG;
            const int k = lane & 15, rr = tid >> 4;
            const uint4* hdr = &g_hdr[h][lane];
            const uint4* dat = &g_dat[h][rr][16 * js + k];
            float* part = reinterpret_cast<float*>(smem + SM_MERGE);
            uint32_t wa[5][3][4];
            float L;
            uint32_t it = 0;
#pragma unroll 1
            while (true) {
                uint4 hd[5], dv[MAXG / 16];
                LoadN<5, 32>::run(hd, hdr, live, lane, 32, ncand);
                LoadN<MAXG / 16, 1024>::run(dv, dat, live, rr, 16, ncand);
                if (it == 0) {
                    if (live) mbar_wait3(BAR(B_WO + ((wid * 5) >> 3)), BAR(B_WO + ((wid * 5 + 4) >> 3)), BAR(B_WO + ((wid * 5) >> 3)));
#pragma unroll
                    for (int i = 0; i < 5; i++) {
                        const int mt = wid * 5 + i;
                        const int cc = 2 * (mt & 3) + (mi & 1);
#pragma unroll
                        for (int ks = 0; ks < 3; ks++) {
                            const int r = ks * 16 + l8 + 8 * (mi >> 1);
                            ldsm4t(wa[i][ks], sb + SM_WO + (mt >> 2) * 6144 + r * 128 + ((cc ^ (r & 7)) << 4));
                        }
                    }
                }
                CLK(1);
                float w[5], M = NEG_BIG;
                int c = 0;
#pragma unroll
                for (int i = 0; i < 5; i++) {
                    const bool v = lane + 32 * i < ncand && hd[i].w == tag;
                    w[i] = v ? __uint_as_float(hd[i].x) : NEG_BIG;
                    M = fmaxf(M, w[i]);
                    c += v ? (int)hd[i].z : 0;
                }
#pragma unroll
                for (int o = 16; o > 0; o >>= 1) M = fmaxf(M, __shfl_xor_sync(0xffffffffu, M, o));
                c = __reduce_add_sync(0xffffffffu, c);
                float ls = 0.f;
#pragma unroll
                for (int i = 0; i < 5; i++) {
                    const bool v = w[i] != NEG_BIG;
                    const float e = ex2((w[i] - M) * LOG2E);
                    w[i] = v ? e : -1.0f;
                    if (v) ls = fmaf(e, __uint_as_float(hd[i].y), ls);
                }
                L = warp_sum(ls);
                bool bad = c != TPH;
                float a0 = 0.f, a1 = 0.f, a2 = 0.f;
#pragma unroll
                for (int i = 0; i < MAXG / 16; i++) {
                    const float wi = __shfl_sync(0xffffffffu, w[i >> 1], rr + 16 * (i & 1));
                    if (wi >= 0.f) {
                        bad = bad || dv[i].w != tag;
                        a0 = fmaf(wi, __uint_as_float(dv[i].x), a0);
                        a1 = fmaf(wi, __uint_as_float(dv[i].y), a1);
                        a2 = fmaf(wi, __uint_as_float(dv[i].z), a2);
                    }
                }
                a0 += __shfl_xor_sync(0xffffffffu, a0, 16);
                a1 += __shfl_xor_sync(0xffffffffu, a1, 16);
                a2 += __shfl_xor_sync(0xffffffffu, a2, 16);
                CLK(2);
                if (!live) break;
                if (lane < 16) { part[wid * 48 + 3 * k] = a0; part[wid * 48 + 3 * k + 1] = a1; part[wid * 48 + 3 * k + 2] = a2; }
                it++;
                if (!bar_cons_or(bad)) break;
                if (it > SPIN_LIMIT) __trap();
            }
            __nv_bfloat16* osw = reinterpret_cast<__nv_bfloat16*>(smem + SM_SC) + wid * 48;
            const float inv = __fdividef(1.0f, L);
            float o0 = 0.f, o1 = 0.f;
#pragma unroll
            for (int w = 0; w < 8; w++) { o0 += part[w * 48 + lane]; o1 += part[w * 48 + 32 + (lane & 15)]; }
            if (live) { osw[lane] = __float2bfloat16_rn(o0 * inv); if (lane < 16) osw[32 + lane] = __float2bfloat16_rn(o1 * inv); }
            __syncwarp();
            const uint32_t* os32 = reinterpret_cast<const uint32_t*>(osw);
            float acc[5][4] = {};
            if (live) TS(10);
            CLK(3);
#pragma unroll
            for (int ks = 0; ks < 3; ks++) {
                const uint32_t b0 = os32[ks * 8 + j4], b1 = os32[ks * 8 + 4 + j4];
#pragma unroll
                for (int i = 0; i < 5; i++) mma16816(acc[i], wa[i][ks], b0, b1);
            }
            if (live && j4 == 0) {
#pragma unroll
                for (int i = 0; i < 5; i++) { stage[(wid * 5 + i) * 16 + g4] = acc[i][0]; stage[(wid * 5 + i) * 16 + 8 + g4] = acc[i][2]; }
            }
            CLK(4);
            if (live) bar_cons();
            const int o = tid >> 1, kk = tid & 1;
            const float* sp = stage + o * 5 + kk * 3;
            float v0 = sp[0], v1 = sp[1], v2 = kk ? 0.f : sp[2];
            if (live) st_pk16(&g_h1[o][cta][kk], __float_as_uint(v0), __float_as_uint(v1), __float_as_uint(v2), tag);
        }
        if (live) TS(11);
        CLK(5);
        if (wid == 0 || !live) {
            const uint4* p = &g_h1[cta][0][0] + lane;
            uint4 v[8];
            uint32_t it = 0;
            while (true) {
                bool ok = true;
                LoadN<8, 32>::run(v, p, live, 0, 0, 1);
#pragma unroll
                for (int j = 0; j < 8; j++) ok = ok && v[j].w == tag;
                if (ok || !live) break;
                if (++it > SPIN_LIMIT) __trap();
            }
            CLK(6);
            float a0 = 0.f, a1 = 0.f, a2 = 0.f;
#pragma unroll
            for (int j = 0; j < 8; j++) { a0 += __uint_as_float(v[j].x); a1 += __uint_as_float(v[j].y); a2 += __uint_as_float(v[j].z); }
#pragma unroll
            for (int o = 2; o <= 16; o <<= 1) {
                a0 += __shfl_xor_sync(0xffffffffu, a0, o);
                a1 += __shfl_xor_sync(0xffffffffu, a1, o);
                a2 += __shfl_xor_sync(0xffffffffu, a2, o);
            }
            const float gx = own[lane & 7], xx = own[16 + (lane & 7)];
            const float t0 = __shfl_sync(0xffffffffu, a0, lane >= 3), t1 = __shfl_sync(0xffffffffu, a1, lane >= 3);
            const float sum = (lane == 0 || lane == 3) ? t0 : (lane == 2 ? a2 : t1);
            const float x2 = bfr(xx + bfr(gx * bfr(sum)));
            if (live && lane < 5) own[24 + lane] = x2;
            const float y1 = __shfl_sync(0xffffffffu, x2, 1), y2 = __shfl_sync(0xffffffffu, x2, 2);
            const float y3 = __shfl_sync(0xffffffffu, x2, 3), y4 = __shfl_sync(0xffffffffu, x2, 4);
            if (live && lane == 0) st_pk16(&g_x2[cta][0], pack_bf(x2, y1), pack_bf(y2, y3), pack_bf(y4, 0.f), tag);
            if (live) TS(13);
        }
        CLK(8);
        if (cta < 96) {
            uint32_t a1[5][4], a3[5][4], a2[5][4];
            if (live) mbar_wait3(BAR(B_W1 + (wid >> 2)), BAR(B_W3 + (wid >> 2)), BAR(B_W2 + (wid >> 2)));
            const uint32_t w2b = sb + SM_RING + meta[10 + (wid >> 2)] % NSLOT * CHUNK;
#pragma unroll
            for (int ks = 0; ks < 5; ks++) {
                const int r = wid * 80 + ks * 16 + l8 + 8 * (mi >> 1);
                const uint32_t off = r * 32 + (((mi & 1) ^ ((r >> 2) & 1)) << 4);
                ldsm4t(a1[ks], sb + SM_W1 + off);
                ldsm4t(a3[ks], sb + SM_W3 + off);
            }
#pragma unroll
            for (int i = 0; i < 5; i++) {
                const int mt = (wid & 3) * 5 + i;
                const int cc = 2 * (mt & 3) + (mi & 1);
                const int r = l8 + 8 * (mi >> 1);
                ldsm4t(a2[i], w2b + (mt >> 2) * 2048 + r * 128 + ((cc ^ (r & 7)) << 4));
            }
            CLK(9);
            float* x2s = reinterpret_cast<float*>(smem + SM_X2);
            float* st8 = red + 256;
            if (wid >= 4) {
                uint4 v = poll16(&g_x2[tid - 128][0], tag, live);
                const float e0 = bf_lo(v.x), e1 = bf_hi(v.x), e2 = bf_lo(v.y), e3 = bf_hi(v.y), e4 = bf_lo(v.z);
                float* d = x2s + (tid - 128) * 5;
                if (live) { d[0] = e0; d[1] = e1; d[2] = e2; d[3] = e3; d[4] = e4; }
                const float pv = __shfl_sync(0xffffffffu, e0, 0);
                const float d0 = e0 - pv, d1 = e1 - pv, d2 = e2 - pv, d3 = e3 - pv, d4 = e4 - pv;
                float s1 = ((d0 + d1) + (d2 + d3)) + d4;
                float s2 = fmaf(d0, d0, fmaf(d1, d1, fmaf(d2, d2, fmaf(d3, d3, d4 * d4))));
#pragma unroll
                for (int o = 16; o > 0; o >>= 1) { s1 += __shfl_xor_sync(0xffffffffu, s1, o); s2 += __shfl_xor_sync(0xffffffffu, s2, o); }
                if (live && lane == 0) { st8[2 * (wid - 4)] = pv + s1 * (1.0f / 160.0f); st8[2 * (wid - 4) + 1] = s2 - s1 * s1 * (1.0f / 160.0f); }
            }
            if (live) bar_cons();
            if (live) TS(14);
            CLK(10);
            const float4 sA = *reinterpret_cast<const float4*>(st8), sB = *reinterpret_cast<const float4*>(st8 + 4);
            const float mean = ((sA.x + sA.z) + (sB.x + sB.z)) * 0.25f;
            const float u0 = sA.x - mean, u1 = sA.z - mean, u2 = sB.x - mean, u3 = sB.z - mean;
            const float m2 = ((sA.y + sA.w) + (sB.y + sB.w)) + 160.0f * ((u0 * u0 + u1 * u1) + (u2 * u2 + u3 * u3));
            const float mean_b = bfr(mean);
            const float rden = __fdividef(1.0f, bfr(fsqrt(bfr(bfr(m2 * (1.0f / 640.0f)) + 1e-5f))));
            const uint32_t* cb32 = reinterpret_cast<const uint32_t*>(smem + SM_CB);
            const uint32_t* sb32 = reinterpret_cast<const uint32_t*>(smem + SM_SB);
#pragma unroll
            for (int rep = 0; rep < 2; rep++) {
                const int p = lane + 32 * rep;
                if (p < 40) {
                    int pp = wid * 40 + p;
                    const float2 xv = *reinterpret_cast<const float2*>(x2s + 2 * pp);
                    uint32_t cv = cb32[pp], sv = sb32[pp];
                    float n0 = bfr(bfr(xv.x - mean_b) * rden), n1 = bfr(bfr(xv.y - mean_b) * rden);
                    uint32_t hv = pack_bf(bfr(n0 * bf_lo(cv)) + bf_lo(sv), bfr(n1 * bf_hi(cv)) + bf_hi(sv));
                    if (live) h32[pp] = hv;
                }
            }
            __syncwarp();
            CLK(11);
            float ag[2][4] = {}, au[2][4] = {};
#pragma unroll
            for (int ks = 0; ks < 5; ks++) {
                const int r0 = wid * 80 + ks * 16;
                const uint32_t b0 = h32[(r0 >> 1) + j4], b1 = h32[(r0 >> 1) + 4 + j4];
                mma16816(ag[ks & 1], a1[ks], b0, b1);
                mma16816(au[ks & 1], a3[ks], b0, b1);
            }
            if (live && j4 == 0) {
                red[wid * 32 + g4] = ag[0][0] + ag[1][0]; red[wid * 32 + 8 + g4] = ag[0][2] + ag[1][2];
                red[wid * 32 + 16 + g4] = au[0][0] + au[1][0]; red[wid * 32 + 24 + g4] = au[0][2] + au[1][2];
            }
            CLK(12);
            if (live) bar_cons();
            if (live) TS(15);
            CLK(13);
            float v = 0.f;
#pragma unroll
            for (int w = 0; w < 8; w++) v += red[w * 32 + lane];
            v = bfr(v);
            float up = __shfl_down_sync(0xffffffffu, v, 16);
            float hact = bfr(bfr(silu(v)) * up);
            float e0 = __shfl_sync(0xffffffffu, hact, 2 * j4), e1 = __shfl_sync(0xffffffffu, hact, 2 * j4 + 1);
            float e2 = __shfl_sync(0xffffffffu, hact, 2 * j4 + 8), e3 = __shfl_sync(0xffffffffu, hact, 2 * j4 + 9);
            const uint32_t b0 = pack_bf(e0, e1), b1 = pack_bf(e2, e3);
            float acc[5][4] = {};
#pragma unroll
            for (int i = 0; i < 5; i++) mma16816(acc[i], a2[i], b0, b1);
            if (live && j4 == 0) {
#pragma unroll
                for (int i = 0; i < 5; i++) { stage[(wid * 5 + i) * 16 + g4] = acc[i][0]; stage[(wid * 5 + i) * 16 + 8 + g4] = acc[i][2]; }
            }
            CLK(14);
            if (live) bar_cons();
            const int o = tid >> 1, k = tid & 1;
            const float* sp = stage + o * 5 + k * 3;
            float v0 = sp[0], v1 = sp[1], v2 = k ? 0.f : sp[2];
            if (live) st_pk16(&g_h3[o][cta][k], __float_as_uint(v0), __float_as_uint(v1), __float_as_uint(v2), tag);
        }
        if (live) TS(16);
        CLK(15);
        if (wid == 0 || !live) {
            const uint4* p = &g_h3[cta][0][0] + lane;
            uint4 v[6];
            uint32_t it = 0;
            if (live && cta < 96) spin(P_DLY);
            while (true) {
                bool ok = true;
                LoadN<6, 32>::run(v, p, live, 0, 0, 1);
#pragma unroll
                for (int j = 0; j < 6; j++) ok = ok && v[j].w == tag;
                if (ok || !live) break;
                if (++it > SPIN_LIMIT) __trap();
            }
            CLK(16);
            float a0 = 0.f, a1 = 0.f, a2 = 0.f;
#pragma unroll
            for (int j = 0; j < 6; j++) { a0 += __uint_as_float(v[j].x); a1 += __uint_as_float(v[j].y); a2 += __uint_as_float(v[j].z); }
#pragma unroll
            for (int o = 2; o <= 16; o <<= 1) {
                a0 += __shfl_xor_sync(0xffffffffu, a0, o);
                a1 += __shfl_xor_sync(0xffffffffu, a1, o);
                a2 += __shfl_xor_sync(0xffffffffu, a2, o);
            }
            const float gx = own[8 + (lane & 7)], xx = own[24 + (lane & 7)];
            const float t0 = __shfl_sync(0xffffffffu, a0, lane >= 3), t1 = __shfl_sync(0xffffffffu, a1, lane >= 3);
            const float sum = (lane == 0 || lane == 3) ? t0 : (lane == 2 ? a2 : t1);
            const float y = xx + bfr(gx * bfr(sum));
            if (live && lane < 5) out[cta * 5 + lane] = __float2bfloat16_rn(y);
            if (live && cta == 0 && lane == 0) g_epoch = tag;
        }
        CLK(17);
        if (live) { TS(18); break; }
        live = true;
    }
    }
}

typedef CUresult (*EncodeFn)(CUtensorMap*, CUtensorMapDataType, cuuint32_t, void*, const cuuint64_t*, const cuuint64_t*,
                             const cuuint32_t*, const cuuint32_t*, CUtensorMapInterleave, CUtensorMapSwizzle,
                             CUtensorMapL2promotion, CUtensorMapFloatOOBfill);

void make_map(EncodeFn enc, CUtensorMap* tm, const void* ptr, uint64_t cols, uint64_t rows, uint32_t box_c, uint32_t box_r,
              CUtensorMapSwizzle sw, CUtensorMapL2promotion prom) {
    cuuint64_t dims[2] = {cols, rows};
    cuuint64_t strides[1] = {cols * 2};
    cuuint32_t box[2] = {box_c, box_r};
    cuuint32_t es[2] = {1, 1};
    enc(tm, CU_TENSOR_MAP_DATA_TYPE_BFLOAT16, 2, const_cast<void*>(ptr), dims, strides, box, es,
        CU_TENSOR_MAP_INTERLEAVE_NONE, sw, prom, CU_TENSOR_MAP_FLOAT_OOB_FILL_NONE);
}

}

extern "C" void kernel_launch(void* const* d_in, const int* in_sizes, int n_in, void* d_out, int out_size) {
    (void)in_sizes; (void)n_in; (void)out_size;
    static EncodeFn enc = nullptr;
    static int num_sms = 0;
    if (!enc) {
        void* fn = nullptr;
        cudaDriverEntryPointQueryResult qr;
        cudaGetDriverEntryPoint("cuTensorMapEncodeTiled", &fn, cudaEnableDefault, &qr);
        enc = (EncodeFn)fn;
        cudaDeviceGetAttribute(&num_sms, cudaDevAttrMultiProcessorCount, 0);
        cudaFuncSetAttribute(fused_decode_kernel, cudaFuncAttributeMaxDynamicSharedMemorySize, SM_TOTAL);
    }
    CUtensorMap tmK, tmV, tmMod, tmWq, tmWo, tmW1, tmW3, tmW2;
    const uint64_t kv_lines = (uint64_t)NH * SK * 3;
    make_map(enc, &tmK, d_in[1], 64, kv_lines, 64, 96, CU_TENSOR_MAP_SWIZZLE_128B, CU_TENSOR_MAP_L2_PROMOTION_L2_128B);
    make_map(enc, &tmV, d_in[2], 64, kv_lines, 64, 96, CU_TENSOR_MAP_SWIZZLE_128B, CU_TENSOR_MAP_L2_PROMOTION_L2_128B);
    make_map(enc, &tmWq, d_in[3], NH * DH, D, 48, 128, CU_TENSOR_MAP_SWIZZLE_NONE, CU_TENSOR_MAP_L2_PROMOTION_L2_128B);
    make_map(enc, &tmWo, d_in[4], D, NH * DH, 64, 48, CU_TENSOR_MAP_SWIZZLE_128B, CU_TENSOR_MAP_L2_PROMOTION_L2_128B);
    make_map(enc, &tmW1, d_in[6], FF, D, 16, 160, CU_TENSOR_MAP_SWIZZLE_32B, CU_TENSOR_MAP_L2_PROMOTION_L2_128B);
    make_map(enc, &tmW3, d_in[7], FF, D, 16, 160, CU_TENSOR_MAP_SWIZZLE_32B, CU_TENSOR_MAP_L2_PROMOTION_L2_128B);
    make_map(enc, &tmW2, d_in[8], D, FF, 64, 16, CU_TENSOR_MAP_SWIZZLE_128B, CU_TENSOR_MAP_L2_PROMOTION_L2_128B);
    make_map(enc, &tmMod, d_in[10], 6 * D, D, 32, 160, CU_TENSOR_MAP_SWIZZLE_64B, CU_TENSOR_MAP_L2_PROMOTION_L2_128B);
    int grid = num_sms < MAXG ? num_sms : MAXG;
    fused_decode_kernel<<<grid, NTHREADS, SM_TOTAL, cudaStreamPerThread>>>(
        tmK, tmV, tmMod, tmWq, tmWo, tmW1, tmW3, tmW2, (const __nv_bfloat16*)d_in[0], (const __nv_bfloat16*)d_in[9],
        (__nv_bfloat16*)d_out);
}
```

```cpp
#include <cuda_runtime.h>
#include <cuda_bf16.h>
#include <cuda.h>
#include <stdint.h>

namespace {

constexpr int D = 640, NH = 32, SK = 8192, DH = 192, FF = 1536;
constexpr int NG = 4;
constexpr int GH = 7;
constexpr int NGLOB = NH - NG * GH;
constexpr int NQH = GH + NGLOB;
constexpr int TILE = 32;
constexpr int TPH = SK / TILE;
constexpr int GT = GH * TPH;
constexpr int PT = NGLOB * TPH;
constexpr int CHUNK = TILE * DH * 2;
#define P_NSLOT 8
#define P_WIN 3
#define P_DLY 450
constexpr int NSLOT = P_NSLOT;
constexpr int WIN = P_WIN;
constexpr int MAXG = 144;
constexpr int NTHREADS = 288;
constexpr float NEG_BIG = -3.402823466e38f;

constexpr int SM_WMOD = 0;
constexpr int SM_WQ = 40960;
constexpr int SM_WO = 0;
constexpr int SM_W1 = 61440;
constexpr int SM_W3 = 81920;
constexpr int SM_RING = 102400;
constexpr int SM_MISC = SM_RING + NSLOT * CHUNK;
constexpr int SM_BARS = SM_MISC;
constexpr int SM_META = SM_BARS + 512;
constexpr int SM_Q = SM_META + 128;
constexpr int SM_SC = SM_Q + NQH * DH * 2;
constexpr int SM_H = SM_SC + 1280;
constexpr int SM_X = SM_H + 1280;
constexpr int SM_CB = SM_X + 1280;
constexpr int SM_SB = SM_CB + 1280;
constexpr int SM_OWN = SM_SB + 1280;
constexpr int SM_RED = SM_OWN + 128;
constexpr int SM_MERGE = SM_RED + 2048;
constexpr int SM_STAGE = SM_MERGE + 3200;
constexpr int SM_X2 = SM_STAGE + 2560;
constexpr int SM_FIN = SM_X2 + 2560;
constexpr int SM_TOTAL = SM_FIN + 256;
static_assert(SM_TOTAL <= 232448, "shared memory budget");

constexpr int B_FULL = 0;
constexpr int B_EMPTY = 8;
constexpr int B_MOD = 16;
constexpr int B_WQ = 20;
constexpr int B_WO = 25;
constexpr int B_W1 = 30;
constexpr int B_W3 = 32;
constexpr int B_W2 = 34;
constexpr int B_FLF = 36, B_FLE = 37, B_PRO = 38, B_DUMMY = 39;
static_assert(NSLOT <= 8 && NSLOT >= 6 && WIN <= 4 && WIN <= NSLOT - 3, "barrier map / end markers vs window");
constexpr uint32_t META_END = 0x10000u;

__device__ unsigned g_epoch;
__device__ unsigned g_ctr[2][(NG + 1) * 32];
__device__ __align__(128) unsigned long long g_mod[1920];
__device__ __align__(128) unsigned long long g_q[3072];
__device__ __align__(128) uint4 g_hdr[NH][MAXG];
__device__ __align__(128) uint4 g_dat[NH][MAXG][64];
__device__ __align__(128) uint4 g_h1[128][128][2];
__device__ __align__(128) uint4 g_x2[128][2];
__device__ __align__(128) uint4 g_h3[128][96][2];

#define TS(k) do {} while (0)
#define DBG(k) do {} while (0)
#define CLK(k) do {} while (0)

__device__ __forceinline__ uint32_t smem_u32(const void* p) { return (uint32_t)__cvta_generic_to_shared(p); }
__device__ __forceinline__ void mbar_init(uint32_t bar, uint32_t cnt) {
    asm volatile("mbarrier.init.shared::cta.b64 [%0], %1;" ::"r"(bar), "r"(cnt) : "memory");
}
__device__ __forceinline__ void mbar_expect_tx(uint32_t bar, uint32_t bytes) {
    asm volatile("mbarrier.arrive.expect_tx.shared::cta.b64 _, [%0], %1;" ::"r"(bar), "r"(bytes) : "memory");
}
__device__ __forceinline__ void mbar_arrive(uint32_t bar) {
    asm volatile("mbarrier.arrive.shared::cta.b64 _, [%0];" ::"r"(bar) : "memory");
}
constexpr uint32_t SPIN_LIMIT = 1u << 22;
__device__ __forceinline__ void mbar_wait(uint32_t bar, uint32_t parity) {
    asm volatile(
        "{\n.reg .pred p;\n.reg .u32 c;\nmov.u32 c, 0;\n"
        "LW:\nmbarrier.try_wait.parity.shared::cta.b64 p, [%0], %1;\n@p bra LD;\n"
        "add.u32 c, c, 1;\nsetp.lt.u32 p, c, 0x400000;\n@p bra LW;\ntrap;\nLD:\n}" ::"r"(bar), "r"(parity)
        : "memory");
}
__device__ __forceinline__ uint32_t mbar_try(uint32_t bar, uint32_t parity) {
    uint32_t ok;
    asm volatile("{\n.reg .pred p;\nmbarrier.try_wait.parity.shared::cta.b64 p, [%1], %2;\nselp.u32 %0, 1, 0, p;\n}"
                 : "=r"(ok) : "r"(bar), "r"(parity) : "memory");
    return ok;
}
__device__ __forceinline__ void mbar_wait3(uint32_t b0, uint32_t b1, uint32_t b2) {
    asm volatile(
        "{\n.reg .pred p, q, r;\n.reg .u32 c;\nmov.u32 c, 0;\n"
        "LW:\nmbarrier.try_wait.parity.shared::cta.b64 p, [%0], 0;\n"
        "mbarrier.try_wait.parity.shared::cta.b64 q, [%1], 0;\n"
        "mbarrier.try_wait.parity.shared::cta.b64 r, [%2], 0;\n"
        "and.pred p, p, q;\nand.pred p, p, r;\n@p bra LD;\n"
        "add.u32 c, c, 1;\nsetp.lt.u32 p, c, 0x400000;\n@p bra LW;\ntrap;\nLD:\n}" ::"r"(b0), "r"(b1), "r"(b2)
        : "memory");
}
__device__ __forceinline__ void tma2d(uint32_t dst, const CUtensorMap* tm, int c0, int c1, uint32_t bar) {
    asm volatile(
        "cp.async.bulk.tensor.2d.shared::cluster.global.mbarrier::complete_tx::bytes [%0], [%1, {%3, %4}], [%2];" ::"r"(dst),
        "l"(tm), "r"(bar), "r"(c0), "r"(c1)
        : "memory");
}
__device__ __forceinline__ void tma2d_hint(uint32_t dst, const CUtensorMap* tm, int c0, int c1, uint32_t bar, uint64_t pol) {
    asm volatile(
        "cp.async.bulk.tensor.2d.shared::cluster.global.mbarrier::complete_tx::bytes.L2::cache_hint [%0], [%1, {%3, %4}], [%2], %5;" ::"r"(dst),
        "l"(tm), "r"(bar), "r"(c0), "r"(c1), "l"(pol)
        : "memory");
}
__device__ __forceinline__ void prefetch_tm(const CUtensorMap* tm) {
    asm volatile("prefetch.tensormap [%0];" ::"l"(tm) : "memory");
}
__device__ __forceinline__ void ldsm4(uint32_t (&r)[4], uint32_t addr) {
    asm volatile("ldmatrix.sync.aligned.m8n8.x4.shared.b16 {%0,%1,%2,%3}, [%4];"
                 : "=r"(r[0]), "=r"(r[1]), "=r"(r[2]), "=r"(r[3])
                 : "r"(addr));
}
__device__ __forceinline__ void ldsm4t(uint32_t (&r)[4], uint32_t addr) {
    asm volatile("ldmatrix.sync.aligned.m8n8.x4.trans.shared.b16 {%0,%1,%2,%3}, [%4];"
                 : "=r"(r[0]), "=r"(r[1]), "=r"(r[2]), "=r"(r[3])
                 : "r"(addr));
}
__device__ __forceinline__ void mma16816(float (&d)[4], const uint32_t (&a)[4], uint32_t b0, uint32_t b1) {
    asm volatile(
        "mma.sync.aligned.m16n8k16.row.col.f32.bf16.bf16.f32 {%0,%1,%2,%3}, {%4,%5,%6,%7}, {%8,%9}, {%0,%1,%2,%3};"
        : "+f"(d[0]), "+f"(d[1]), "+f"(d[2]), "+f"(d[3])
        : "r"(a[0]), "r"(a[1]), "r"(a[2]), "r"(a[3]), "r"(b0), "r"(b1));
}
__device__ __forceinline__ void bar_cons() { asm volatile("bar.sync 1, 256;" ::: "memory"); }
__device__ __forceinline__ void spin(int cycles) {
    long long t0 = clock64();
    while (clock64() - t0 < cycles) {}
}

__device__ __forceinline__ float bfr(float x) {
    uint32_t r;
    asm("cvt.rn.bf16x2.f32 %0, %1, %2;" : "=r"(r) : "f"(x), "f"(0.0f));
    return __uint_as_float(r);
}
__device__ __forceinline__ uint32_t pack_bf(float lo, float hi) {
    __nv_bfloat162 t = __floats2bfloat162_rn(lo, hi);
    return *reinterpret_cast<uint32_t*>(&t);
}
__device__ __forceinline__ float bf_lo(uint32_t v) { return __uint_as_float(v << 16); }
__device__ __forceinline__ float bf_hi(uint32_t v) { return __uint_as_float(v & 0xffff0000u); }

__device__ __forceinline__ void st_pk8(unsigned long long* p, uint32_t v, uint32_t tag) {
    unsigned long long w = ((unsigned long long)tag << 32) | v;
    asm volatile("st.relaxed.gpu.global.b64 [%0], %1;" ::"l"(p), "l"(w) : "memory");
}
__device__ __forceinline__ unsigned long long ld_raw8(const unsigned long long* p) {
    unsigned long long w;
    asm volatile("ld.relaxed.gpu.global.b64 %0, [%1];" : "=l"(w) : "l"(p) : "memory");
    return w;
}
template <int N>
__device__ __forceinline__ void poll8(const unsigned long long* base, const int (&off)[N], uint32_t (&val)[N], uint32_t tag) {
    uint32_t it = 0;
    while (true) {
        unsigned long long w[N];
#pragma unroll
        for (int i = 0; i < N; i++) w[i] = ld_raw8(base + off[i]);
        bool ok = true;
#pragma unroll
        for (int i = 0; i < N; i++) { ok = ok && ((uint32_t)(w[i] >> 32) == tag); val[i] = (uint32_t)w[i]; }
        if (__all_sync(0xffffffffu, ok)) break;
        if (++it > SPIN_LIMIT) __trap();
    }
}
__device__ __forceinline__ void st_pk16(uint4* p, uint32_t a, uint32_t b, uint32_t c, uint32_t tag) {
    asm volatile(
        "{\n.reg .b128 t;\n.reg .b64 lo, hi;\nmov.b64 lo, {%1, %2};\nmov.b64 hi, {%3, %4};\nmov.b128 t, {lo, hi};\n"
        "st.relaxed.gpu.global.b128 [%0], t;\n}" ::"l"(p), "r"(a), "r"(b), "r"(c), "r"(tag)
        : "memory");
}
template <int OFF = 0>
__device__ __forceinline__ uint4 ld_raw16p(const uint4* p, uint32_t on) {
    uint4 v;
    asm volatile(
        "{\n.reg .b128 t;\n.reg .b64 lo, hi;\n.reg .pred q;\nsetp.ne.u32 q, %5, 0;\n"
        "mov.b64 lo, 0;\nmov.b128 t, {lo, lo};\n"
        "@q ld.relaxed.gpu.global.b128 t, [%4 + %6];\nmov.b128 {lo, hi}, t;\n"
        "mov.b64 {%0, %1}, lo;\nmov.b64 {%2, %3}, hi;\n}"
        : "=r"(v.x), "=r"(v.y), "=r"(v.z), "=r"(v.w)
        : "l"(p), "r"(on), "n"(OFF * 16)
        : "memory");
    return v;
}
template <int N, int STRIDE, int I = 0>
struct LoadN {
    static __device__ __forceinline__ void run(uint4* v, const uint4* p, bool live, int base, int step, int lim) {
        v[I] = ld_raw16p<I * STRIDE>(p, live && base + step * I < lim);
        LoadN<N, STRIDE, I + 1>::run(v, p, live, base, step, lim);
    }
};
template <int N, int STRIDE>
struct LoadN<N, STRIDE, N> {
    static __device__ __forceinline__ void run(uint4*, const uint4*, bool, int, int, int) {}
};
__device__ __forceinline__ uint4 poll16(const uint4* p, uint32_t tag, bool live) {
    uint32_t it = 0;
    uint4 v;
    while (true) {
        v = ld_raw16p(p, live);
        if (__all_sync(0xffffffffu, v.w == tag) || !live) break;
        if (++it > SPIN_LIMIT) __trap();
    }
    return v;
}
__device__ __forceinline__ void st_zero16(void* p) {
    asm volatile("st.relaxed.gpu.global.v4.u32 [%0], {%1, %1, %1, %1};" ::"l"(p), "r"(0u) : "memory");
}
__device__ __forceinline__ float ex2(float x) {
    float y;
    asm("ex2.approx.ftz.f32 %0, %1;" : "=f"(y) : "f"(x));
    return y;
}
__device__ __forceinline__ float fsqrt(float x) {
    float y;
    asm("sqrt.approx.f32 %0, %1;" : "=f"(y) : "f"(x));
    return y;
}
constexpr float LOG2E = 1.4426950408889634f;
__device__ __forceinline__ float silu(float a) { return __fdividef(a, 1.0f + ex2(-a * LOG2E)); }
__device__ __forceinline__ float warp_sum(float v) {
#pragma unroll
    for (int o = 16; o > 0; o >>= 1) v += __shfl_xor_sync(0xffffffffu, v, o);
    return v;
}

__device__ __forceinline__ void ln_stats(const float (&v)[20], float& mean_b, float& den_b) {
    float s = 0.f;
#pragma unroll
    for (int i = 0; i < 20; i++) s += v[i];
    s = warp_sum(s);
    float mean = s * (1.0f / 640.0f);
    float q = 0.f;
#pragma unroll
    for (int i = 0; i < 20; i++) { float d = v[i] - mean; q += d * d; }
    q = warp_sum(q);
    float var_b = bfr(q * (1.0f / 640.0f));
    mean_b = bfr(mean);
    den_b = bfr(fsqrt(bfr(var_b + 1e-5f)));
}

struct Window {
    uint32_t bar[WIN];
    uint32_t par[WIN];
    __device__ __forceinline__ void init(uint32_t dummy) {
#pragma unroll
        for (int i = 0; i < WIN; i++) { bar[i] = dummy; par[i] = 1; }
    }
    __device__ __forceinline__ void push(uint32_t b, uint32_t p) {
        mbar_wait(bar[0], par[0]);
#pragma unroll
        for (int i = 0; i + 1 < WIN; i++) { bar[i] = bar[i + 1]; par[i] = par[i + 1]; }
        bar[WIN - 1] = b; par[WIN - 1] = p;
    }
};

__global__ void __launch_bounds__(NTHREADS, 1)
fused_decode_kernel(const __grid_constant__ CUtensorMap tmK, const __grid_constant__ CUtensorMap tmV,
                    const __grid_constant__ CUtensorMap tmMod, const __grid_constant__ CUtensorMap tmWq,
                    const __grid_constant__ CUtensorMap tmWo, const __grid_constant__ CUtensorMap tmW1,
                    const __grid_constant__ CUtensorMap tmW3, const __grid_constant__ CUtensorMap tmW2,
                    const __nv_bfloat16* __restrict__ x_in, const __nv_bfloat16* __restrict__ c_in,
                    __nv_bfloat16* __restrict__ out) {
    extern __shared__ __align__(1024) uint8_t smem[];
    const uint32_t sb = smem_u32(smem);
    const int tid = threadIdx.x, wid = tid >> 5, lane = tid & 31;
    const int cta = blockIdx.x, G = gridDim.x;
    const int grp = cta % NG, rank = cta / NG;
    const uint32_t bars = sb + SM_BARS;
    auto BAR = [&](int i) { return bars + 8u * i; };
    volatile uint32_t* meta = reinterpret_cast<volatile uint32_t*>(smem + SM_META);

    if (wid >= 8) {
        Window win;
        unsigned epoch = 0;
        if (tid == 256) {
            TS(0);
            if (sb & 1023u) __trap();
            asm volatile("ld.relaxed.gpu.global.u32 %0, [%1];" : "=r"(epoch) : "l"(&g_epoch) : "memory");
            prefetch_tm(&tmMod); prefetch_tm(&tmWq); prefetch_tm(&tmK); prefetch_tm(&tmV);
#pragma unroll
            for (int i = 0; i < 4; i++) mbar_init(BAR(B_MOD + i), 1);
            mbar_init(BAR(B_DUMMY), 1);
            asm volatile("fence.mbarrier_init.release.cluster;" ::: "memory");
            asm volatile("fence.proxy.async.shared::cta;" ::: "memory");
            win.init(BAR(B_DUMMY));
            if (cta < 120) {
#pragma unroll 1
                for (int i = 0; i < WIN; i++) {
                    win.push(BAR(B_MOD + i), 0);
                    mbar_expect_tx(BAR(B_MOD + i), 10240);
                    tma2d(sb + SM_WMOD + i * 10240, &tmMod, cta * 32, i * 160, BAR(B_MOD + i));
                }
            }
#pragma unroll 1
            for (int i = 0; i < B_DUMMY; i++) {
                if (i >= B_MOD && i < B_MOD + 4) continue;
                int cnt = (i >= B_EMPTY && i < B_MOD) ? 2 : (i == B_FLF ? 4 : 1);
                mbar_init(BAR(i), cnt);
            }
            asm volatile("fence.mbarrier_init.release.cluster;" ::: "memory");
            asm volatile("fence.proxy.async.shared::cta;" ::: "memory");
        }
        __syncwarp();
        __syncthreads();
        if (tid == 256) {
            prefetch_tm(&tmWo); prefetch_tm(&tmW1); prefetch_tm(&tmW3); prefetch_tm(&tmW2);
            unsigned* ctr = &g_ctr[epoch & 1][grp * 32];
            unsigned* gctr = &g_ctr[epoch & 1][NG * 32];
            if (cta == 0) {
                for (int g = 0; g <= NG; g++) g_ctr[(epoch + 1) & 1][g * 32] = 0;
            }
            unsigned pend = atomicAdd(ctr, 1);
            if (cta < 120) {
#pragma unroll 1
                for (int i = WIN; i < 4; i++) {
                    win.push(BAR(B_MOD + i), 0);
                    mbar_expect_tx(BAR(B_MOD + i), 10240);
                    tma2d(sb + SM_WMOD + i * 10240, &tmMod, cta * 32, i * 160, BAR(B_MOD + i));
                }
            }
            if (cta < 128) {
#pragma unroll 1
                for (int i = 0; i < 5; i++) {
                    win.push(BAR(B_WQ + i), 0);
                    mbar_expect_tx(BAR(B_WQ + i), 12288);
                    tma2d(sb + SM_WQ + i * 12288, &tmWq, cta * 48, i * 128, BAR(B_WQ + i));
                }
            }
            uint64_t pol;
            asm volatile("createpolicy.fractional.L2::evict_first.b64 %0, 1.0;" : "=l"(pol));
            int s = 0; uint32_t par = 0;
            int ntiles = 0, run = -1, last_head = -1;
            bool glob = false;
#pragma unroll 1
            while (true) {
                unsigned t = pend;
                if (!glob && t >= (unsigned)GT) { glob = true; t = atomicAdd(gctr, 1); }
                if (glob && t >= (unsigned)PT) break;
                pend = atomicAdd(glob ? gctr : ctr, 1);
                ntiles++;
                const int hl = t / TPH, tile = t % TPH;
                const int head = glob ? NG * GH + hl : grp * GH + hl;
                const int qidx = glob ? GH + hl : hl;
                if (head != last_head) { last_head = head; run++; meta[16 + run] = head; }
                const int line0 = (head * SK + tile * TILE) * 3;
#pragma unroll 1
                for (int kv = 0; kv < 2; kv++) {
                    win.push(BAR(B_FULL + s), par);
                    mbar_wait(BAR(B_EMPTY + s), par ^ 1);
                    meta[s] = run | (qidx << 8);
                    mbar_expect_tx(BAR(B_FULL + s), CHUNK);
                    tma2d_hint(sb + SM_RING + s * CHUNK, kv ? &tmV : &tmK, 0, line0, BAR(B_FULL + s), pol);
                    if (++s == NSLOT) { s = 0; par ^= 1; }
                }
            }
            TS(5);
            meta[16 + run + 1] = 0xFFu;
#pragma unroll 1
            for (int e = 0; e < 2; e++) {
                mbar_wait(BAR(B_EMPTY + s), par ^ 1);
                meta[s] = (run + 1) | META_END;
                mbar_arrive(BAR(B_FULL + s));
                if (++s == NSLOT) { s = 0; par ^= 1; }
                if (++s == NSLOT) { s = 0; par ^= 1; }
            }
            if (cta < 128) {
                mbar_wait(BAR(B_PRO), 0);
#pragma unroll 1
                for (int i = 0; i < 5; i++) {
                    win.push(BAR(B_WO + i), 0);
                    mbar_expect_tx(BAR(B_WO + i), 12288);
                    tma2d(sb + SM_WO + (2 * i) * 6144, &tmWo, (2 * i) * 64, cta * 48, BAR(B_WO + i));
                    tma2d(sb + SM_WO + (2 * i + 1) * 6144, &tmWo, (2 * i + 1) * 64, cta * 48, BAR(B_WO + i));
                }
                if (cta < 96) {
#pragma unroll 1
                    for (int i = 0; i < 4; i++) {
                        const int m = i & 1, hf = i >> 1;
                        const uint32_t bar = BAR((m ? B_W3 : B_W1) + hf);
                        const uint32_t dst = sb + (m ? SM_W3 : SM_W1) + hf * 10240;
                        const CUtensorMap* tm = m ? &tmW3 : &tmW1;
                        win.push(bar, 0);
                        mbar_expect_tx(bar, 10240);
                        tma2d(dst, tm, cta * 16, hf * 320, bar);
                        tma2d(dst + 5120, tm, cta * 16, hf * 320 + 160, bar);
                    }
#pragma unroll 1
                    for (int i = 0; i < 2; i++) {
                        win.push(BAR(B_W2 + i), 0);
                        mbar_wait(BAR(B_EMPTY + s), par ^ 1);
                        meta[10 + i] = s;
                        mbar_expect_tx(BAR(B_W2 + i), 10240);
#pragma unroll 1
                        for (int b = 0; b < 5; b++)
                            tma2d(sb + SM_RING + s * CHUNK + b * 2048, &tmW2, (5 * i + b) * 64, cta * 16, BAR(B_W2 + i));
                        if (++s == NSLOT) { s = 0; par ^= 1; }
                    }
                }
            }
            TS(6);
        }
    } else {
    const int g4 = lane >> 2, j4 = lane & 3, mi = lane >> 3, l8 = lane & 7;
    uint32_t* sc32 = reinterpret_cast<uint32_t*>(smem + SM_SC);
    uint32_t* h32 = reinterpret_cast<uint32_t*>(smem + SM_H);
    uint32_t* x32 = reinterpret_cast<uint32_t*>(smem + SM_X);
    uint32_t* q32 = reinterpret_cast<uint32_t*>(smem + SM_Q);
    float* red = reinterpret_cast<float*>(smem + SM_RED);
    float* stage = reinterpret_cast<float*>(smem + SM_STAGE);
    float* own = reinterpret_cast<float*>(smem + SM_OWN);

    {
        const uint32_t* cg = reinterpret_cast<const uint32_t*>(c_in);
        const uint32_t* xg = reinterpret_cast<const uint32_t*>(x_in);
        uint32_t c0 = cg[tid], x0 = xg[tid], c1 = 0, x1 = 0;
        if (tid < 64) { c1 = cg[256 + tid]; x1 = xg[256 + tid]; }
        unsigned epoch = 0;
        if (tid == 0) asm volatile("ld.relaxed.gpu.global.u32 %0, [%1];" : "=r"(epoch) : "l"(&g_epoch) : "memory");
        if (cta < 120 && tid < 8) st_zero16(reinterpret_cast<uint4*>(&g_mod[cta * 16]) + tid);
        if (cta < 128 && tid >= 32 && tid < 44) st_zero16(reinterpret_cast<uint4*>(&g_q[cta * 24]) + (tid - 32));
        if (cta < 128) {
            if (tid >= 64 && tid < 66) st_zero16(&g_x2[cta][tid - 64]);
            st_zero16(&g_h1[tid >> 1][cta][tid & 1]);
            if (cta < 96) st_zero16(&g_h3[tid >> 1][cta][tid & 1]);
        }
#pragma unroll 1
        for (int f = tid >> 6; f < NQH; f += 4) {
            const int head = f < GH ? grp * GH + f : NG * GH + (f - GH);
            const int idx = f < GH ? rank : cta;
            st_zero16(&g_dat[head][idx][tid & 63]);
            if ((tid & 63) == 0) st_zero16(&g_hdr[head][idx]);
        }
        sc32[tid] = pack_bf(silu(bf_lo(c0)), silu(bf_hi(c0))); x32[tid] = x0;
        if (tid < 64) { sc32[256 + tid] = pack_bf(silu(bf_lo(c1)), silu(bf_hi(c1))); x32[256 + tid] = x1; }
        if (tid == 0) meta[8] = epoch + 1;
    }
    __syncthreads();
    const uint32_t tag = meta[8];

    float mean_x = 0.f, rden_x = 1.f;
    if (cta < 128) {
        float xv[20];
#pragma unroll
        for (int i = 0; i < 10; i++) { uint32_t v = x32[lane + 32 * i]; xv[2 * i] = bf_lo(v); xv[2 * i + 1] = bf_hi(v); }
        float den;
        ln_stats(xv, mean_x, den);
        rden_x = __fdividef(1.0f, den);
    }

    if (cta < 120) {
        float acc[2][4] = {};
        uint32_t a[5][2][4], bb[5][2];
        const uint32_t base = sb + SM_WMOD + (wid >> 1) * 10240;
#pragma unroll
        for (int ks = 0; ks < 5; ks++) {
            const int r0 = wid * 80 + ks * 16;
            bb[ks][0] = sc32[(r0 >> 1) + j4]; bb[ks][1] = sc32[(r0 >> 1) + 4 + j4];
        }
        mbar_wait(BAR(B_MOD + (wid >> 1)), 0);
#pragma unroll
        for (int ks = 0; ks < 5; ks++) {
            const int r = (wid & 1) * 80 + ks * 16 + l8 + 8 * (mi >> 1);
#pragma unroll
            for (int mt = 0; mt < 2; mt++) ldsm4t(a[ks][mt], base + r * 64 + (((2 * mt + (mi & 1)) ^ ((r >> 1) & 3)) << 4));
        }
#pragma unroll
        for (int ks = 0; ks < 5; ks++) { mma16816(acc[0], a[ks][0], bb[ks][0], bb[ks][1]); mma16816(acc[1], a[ks][1], bb[ks][0], bb[ks][1]); }
        if (j4 == 0) {
#pragma unroll
            for (int mt = 0; mt < 2; mt++) { red[wid * 64 + mt * 16 + g4] = acc[mt][0]; red[wid * 64 + mt * 16 + 8 + g4] = acc[mt][2]; }
        }
        bar_cons();
        if (wid == 0) {
            float v = 0.f;
#pragma unroll
            for (int w = 0; w < 8; w++) v += red[w * 64 + lane];
            float o = __shfl_down_sync(0xffffffffu, v, 1);
            if (!(lane & 1)) st_pk8(&g_mod[cta * 16 + (lane >> 1)], pack_bf(v, o), tag);
        }
    }
    TS(1);

    if (cta < 128) {
        {
            const int off[4] = {tid, 320 + tid, tid < 64 ? 256 + tid : tid, tid < 64 ? 576 + tid : 320 + tid};
            uint32_t val[4];
            poll8<4>(g_mod, off, val, tag);
#pragma unroll
            for (int rep = 0; rep < 2; rep++) {
                int p = tid + rep * 256;
                if (p < 320) {
                    uint32_t sa = val[2 * rep], ca = val[2 * rep + 1];
                    uint32_t xx = x32[p];
                    float n0 = bfr(bfr(bf_lo(xx) - mean_x) * rden_x), n1 = bfr(bfr(bf_hi(xx) - mean_x) * rden_x);
                    float h0 = bfr(n0 * bfr(1.0f + bf_lo(ca))) + bf_lo(sa);
                    float h1 = bfr(n1 * bfr(1.0f + bf_hi(ca))) + bf_hi(sa);
                    h32[p] = pack_bf(h0, h1);
                }
            }
        }
        bar_cons();
        TS(2);
        float acc[3][4] = {};
        uint32_t a[5][3][4], bb[5][2];
#pragma unroll
        for (int ks = 0; ks < 5; ks++) {
            const int r0 = wid * 80 + ks * 16;
            bb[ks][0] = h32[(r0 >> 1) + j4]; bb[ks][1] = h32[(r0 >> 1) + 4 + j4];
        }
        mbar_wait(BAR(B_WQ + ((wid * 80) >> 7)), 0);
        mbar_wait(BAR(B_WQ + ((wid * 80 + 79) >> 7)), 0);
#pragma unroll
        for (int ks = 0; ks < 5; ks++) {
            const int r = wid * 80 + ks * 16 + l8 + 8 * (mi >> 1);
#pragma unroll
            for (int mt = 0; mt < 3; mt++) ldsm4t(a[ks][mt], sb + SM_WQ + r * 96 + ((2 * mt + (mi & 1)) << 4));
        }
#pragma unroll
        for (int ks = 0; ks < 5; ks++) {
#pragma unroll
            for (int mt = 0; mt < 3; mt++) mma16816(acc[mt], a[ks][mt], bb[ks][0], bb[ks][1]);
        }
        if (j4 == 0) {
#pragma unroll
            for (int mt = 0; mt < 3; mt++) { red[wid * 64 + mt * 16 + g4] = acc[mt][0]; red[wid * 64 + mt * 16 + 8 + g4] = acc[mt][2]; }
        }
        bar_cons();
        if (tid < 64) {
            float v = 0.f;
            if (tid < 48) {
#pragma unroll
                for (int w = 0; w < 8; w++) v += red[w * 64 + tid];
            }
            float o = __shfl_down_sync(0xffffffffu, v, 1);
            if (tid < 48 && !(tid & 1)) st_pk8(&g_q[cta * 24 + (tid >> 1)], pack_bf(v, o), tag);
        }
        TS(3);
    }
    {
        int off[5];
#pragma unroll
        for (int j = 0; j < 5; j++) {
            int p = tid + 256 * j;
            if (p >= NQH * 96) p = tid;
            off[j] = p < GH * 96 ? grp * GH * 96 + p : NG * GH * 96 + (p - GH * 96);
        }
        uint32_t val[5];
        poll8<5>(g_q, off, val, tag);
#pragma unroll
        for (int j = 0; j < 5; j++)
            if (tid + 256 * j < NQH * 96) q32[tid + 256 * j] = val[j];
    }
    bar_cons();
    if (tid == 0) mbar_arrive(BAR(B_PRO));
    TS(4);

    bool live = true;
    if (wid < 4) {
        const int pair = wid >> 1, half = wid & 1;
        const int rowK = half * 16 + l8 + 8 * (mi & 1), hiK = mi >> 1;
        const int rowV = half * 16 + l8 + 8 * (mi >> 1), hiV = mi & 1;
        float acc[12][4];
#pragma unroll
        for (int i = 0; i < 12; i++) { acc[i][0] = acc[i][1] = acc[i][2] = acc[i][3] = 0.f; }
        float m_run = NEG_BIG, l_run = 0.f;
        uint32_t qf[12][2];
#pragma unroll
        for (int i = 0; i < 12; i++) { qf[i][0] = qf[i][1] = 0; }
        int cur = -1, flushed = 0, cnt = 0;
        int s = 2 * pair; uint32_t par = 0;
        float* mb = reinterpret_cast<float*>(smem + SM_MERGE) + wid * 200;
        uint32_t ready = 0;
#pragma unroll 1
        while (true) {
            if (!ready) mbar_wait(BAR(B_FULL + s), par);
            const uint32_t mt_ = meta[s];
            const int run = mt_ & 0xff;
            if (run != cur) {
#pragma unroll 1
                while (flushed < run) {
                    if (flushed != cur) {
#pragma unroll
                        for (int i = 0; i < 12; i++) { acc[i][0] = acc[i][1] = acc[i][2] = acc[i][3] = 0.f; }
                        m_run = NEG_BIG; l_run = 0.f; cnt = 0;
                    }
                    const uint32_t fle = mbar_try(BAR(B_FLE), (flushed & 1) ^ 1);
                    float v[24];
#pragma unroll
                    for (int i = 0; i < 12; i++) { v[2 * i] = acc[i][0] + acc[i][1]; v[2 * i + 1] = acc[i][2] + acc[i][3]; }
                    float u[12], w6[6];
                    const bool o1 = j4 & 1, o2 = j4 & 2;
#pragma unroll
                    for (int i = 0; i < 12; i++) {
                        float send = o1 ? v[i] : v[i + 12], keep = o1 ? v[i + 12] : v[i];
                        u[i] = keep + __shfl_xor_sync(0xffffffffu, send, 1);
                    }
#pragma unroll
                    for (int i = 0; i < 6; i++) {
                        float send = o2 ? u[i] : u[i + 6], keep = o2 ? u[i + 6] : u[i];
                        w6[i] = keep + __shfl_xor_sync(0xffffffffu, send, 2);
                    }
                    float l = l_run;
                    l += __shfl_xor_sync(0xffffffffu, l, 4);
                    l += __shfl_xor_sync(0xffffffffu, l, 8);
                    l += __shfl_xor_sync(0xffffffffu, l, 16);
                    if (!fle) mbar_wait(BAR(B_FLE), (flushed & 1) ^ 1);
#pragma unroll
                    for (int i = 0; i < 6; i++) {
                        int idx = (o1 ? 12 : 0) + (o2 ? 6 : 0) + i;
                        mb[4 + 16 * (idx >> 1) + 8 * (idx & 1) + g4] = w6[i];
                    }
                    if (lane == 0) { mb[0] = m_run; mb[1] = l; mb[2] = __int_as_float(cnt); }
                    __syncwarp();
                    if (lane == 0) mbar_arrive(BAR(B_FLF));
                    flushed++;
                    cur = -1;
                }
                if (mt_ & META_END) {
                    mbar_wait(BAR(B_FLE), (flushed & 1) ^ 1);
                    if (lane == 0) mbar_arrive(BAR(B_FLF));
                    break;
                }
                cur = run;
                const int qi = (mt_ >> 8) & 0xff;
#pragma unroll
                for (int i = 0; i < 12; i++) { acc[i][0] = acc[i][1] = acc[i][2] = acc[i][3] = 0.f; }
                m_run = NEG_BIG; l_run = 0.f; cnt = 0;
#pragma unroll
                for (int ks = 0; ks < 12; ks++) {
                    qf[ks][0] = q32[qi * 96 + ks * 8 + j4];
                    qf[ks][1] = q32[qi * 96 + ks * 8 + 4 + j4];
                }
            }
            cnt++;
            const uint32_t kb = sb + SM_RING + s * CHUNK;
            float sc[3][4] = {};
            {
                uint32_t a[12][4];
#pragma unroll
                for (int t = 0; t < 3; t++) {
                    const int ln = rowK * 3 + t;
#pragma unroll
                    for (int kk = 0; kk < 4; kk++) ldsm4(a[t * 4 + kk], kb + ln * 128 + (((2 * kk + hiK) ^ (ln & 7)) << 4));
                }
#pragma unroll
                for (int kk = 0; kk < 4; kk++) {
#pragma unroll
                    for (int t = 0; t < 3; t++) mma16816(sc[t], a[t * 4 + kk], qf[t * 4 + kk][0], qf[t * 4 + kk][1]);
                }
            }
            __syncwarp();
            if (lane == 0) mbar_arrive(BAR(B_EMPTY + s));
            int sv = s + 1; uint32_t parv = par;
            if (sv == NSLOT) { sv = 0; parv ^= 1; }
            const float scale = 0.07216878364870322f;
            float s0 = bfr(bfr(sc[0][0] + sc[1][0] + sc[2][0]) * scale);
            float s1 = bfr(bfr(sc[0][2] + sc[1][2] + sc[2][2]) * scale);
            float tm = fmaxf(s0, s1);
            tm = fmaxf(tm, __shfl_xor_sync(0xffffffffu, tm, 4));
            tm = fmaxf(tm, __shfl_xor_sync(0xffffffffu, tm, 8));
            tm = fmaxf(tm, __shfl_xor_sync(0xffffffffu, tm, 16));
            if (tm > m_run) {
                float alpha = ex2((m_run - tm) * LOG2E);
                l_run *= alpha;
#pragma unroll
                for (int i = 0; i < 12; i++) { acc[i][0] *= alpha; acc[i][1] *= alpha; acc[i][2] *= alpha; acc[i][3] *= alpha; }
                m_run = tm;
            }
            float p0 = ex2((s0 - m_run) * LOG2E);
            float p1 = ex2((s1 - m_run) * LOG2E);
            l_run += p0 + p1;
            uint32_t b0 = 0, b1 = 0;
            if (j4 == (g4 >> 1)) {
                uint32_t e0 = pack_bf(p0, 0.f) & 0xffffu, e1 = pack_bf(p1, 0.f) & 0xffffu;
                b0 = (g4 & 1) ? (e0 << 16) : e0;
                b1 = (g4 & 1) ? (e1 << 16) : e1;
            }
            mbar_wait(BAR(B_FULL + sv), parv);
            s += 4;
            if (s >= NSLOT) { s -= NSLOT; par ^= 1; }
            ready = mbar_try(BAR(B_FULL + s), par);
            const uint32_t vb = sb + SM_RING + sv * CHUNK;
            {
                uint32_t a[12][4];
#pragma unroll
                for (int t = 0; t < 3; t++) {
                    const int ln = rowV * 3 + t;
#pragma unroll
                    for (int kk = 0; kk < 4; kk++) ldsm4t(a[t * 4 + kk], vb + ln * 128 + (((2 * kk + hiV) ^ (ln & 7)) << 4));
                }
#pragma unroll
                for (int i = 0; i < 12; i++) mma16816(acc[i], a[i], b0, b1);
            }
            __syncwarp();
            if (lane == 0) mbar_arrive(BAR(B_EMPTY + sv));
        }
        TS(7);
    } else if (wid == 4) {
        const float* mb = reinterpret_cast<const float*>(smem + SM_MERGE);
#pragma unroll 1
        for (int f = 0;; f++) {
            mbar_wait(BAR(B_FLF), f & 1);
            const int head = (int)meta[16 + f];
            if (head == 0xFF) break;
            float m0 = mb[0], m1 = mb[200], m2 = mb[400], m3 = mb[600];
            float M = fmaxf(fmaxf(m0, m1), fmaxf(m2, m3));
            float w0 = ex2((m0 - M) * LOG2E), w1 = ex2((m1 - M) * LOG2E);
            float w2 = ex2((m2 - M) * LOG2E), w3 = ex2((m3 - M) * LOG2E);
            const int idx = head < NG * GH ? rank : cta;
            uint4* dst = &g_dat[head][idx][0];
            float o[6];
#pragma unroll
            for (int i = 0; i < 6; i++) {
                int d = 4 + (i < 3 ? 3 * lane + i : 96 + 3 * lane + (i - 3));
                o[i] = w0 * mb[d] + w1 * mb[200 + d] + w2 * mb[400 + d] + w3 * mb[600 + d];
            }
            float L = w0 * mb[1] + w1 * mb[201] + w2 * mb[401] + w3 * mb[601];
            const uint32_t tiles = __float_as_int(mb[2]) + __float_as_int(mb[402]);
            st_pk16(dst + lane, __float_as_uint(o[0]), __float_as_uint(o[1]), __float_as_uint(o[2]), tag);
            st_pk16(dst + 32 + lane, __float_as_uint(o[3]), __float_as_uint(o[4]), __float_as_uint(o[5]), tag);
            if (lane == 0) st_pk16(&g_hdr[head][idx], __float_as_uint(M), __float_as_uint(L), tiles, tag);
            __syncwarp();
            if (lane == 0) mbar_arrive(BAR(B_FLE));
        }
        TS(8);
    } else if (wid >= 6) {
        if (cta < 128) {
            const int t = tid - 192;
            uint32_t* cb32 = reinterpret_cast<uint32_t*>(smem + SM_CB);
            uint32_t* sb32 = reinterpret_cast<uint32_t*>(smem + SM_SB);
            const int col = cta * 5 + t;
            int off[12];
            uint32_t val[12];
#pragma unroll
            for (int rep = 0; rep < 5; rep++) { off[2 * rep] = 960 + t + 64 * rep; off[2 * rep + 1] = 1280 + t + 64 * rep; }
            off[10] = t < 5 ? (1280 + col) >> 1 : 960;
            off[11] = t < 5 ? (3200 + col) >> 1 : 960;
            poll8<12>(g_mod, off, val, tag);
#pragma unroll
            for (int rep = 0; rep < 5; rep++) {
                sb32[t + 64 * rep] = val[2 * rep];
                cb32[t + 64 * rep] = pack_bf(1.0f + bf_lo(val[2 * rep + 1]), 1.0f + bf_hi(val[2 * rep + 1]));
            }
            if (t < 5) {
                own[t] = (col & 1) ? bf_hi(val[10]) : bf_lo(val[10]);
                own[8 + t] = (col & 1) ? bf_hi(val[11]) : bf_lo(val[11]);
                uint32_t xx = x32[col >> 1];
                own[16 + t] = (col & 1) ? bf_hi(xx) : bf_lo(xx);
            }
        }
        live = false;
    }
    const uint32_t sb0 = sb;
    const int tid0 = tid;
#pragma unroll 1
    while (cta < 128) {
        uint32_t sb = sb0; int tid = tid0;
        asm volatile("" : "+r"(sb), "+r"(tid));
        const int wid = tid >> 5, lane = tid & 31;
        const int g4 = lane >> 2, j4 = lane & 3, mi = lane >> 3, l8 = lane & 7;
        if (live) bar_cons();
        if (live) TS(9);
        CLK(0);
        {
            const int h = cta >> 2, js = cta & 3;
            const int ncand = h >= NG * GH ? G : (G - h / GH + NG - 1) / NG;
            const int k = lane & 15, rr = tid >> 4;
            const uint4* hdr = &g_hdr[h][lane];
            const uint4* dat = &g_dat[h][rr][16 * js + k];
            float* part = reinterpret_cast<float*>(smem + SM_MERGE);
            uint32_t wa[5][3][4];
            float L, a0, a1, a2;
            uint32_t it = 0;
#pragma unroll 1
            while (true) {
                uint4 hd[5], dv[MAXG / 16];
                LoadN<5, 32>::run(hd, hdr, live, lane, 32, ncand);
                LoadN<MAXG / 16, 1024>::run(dv, dat, live, rr, 16, ncand);
                if (it == 0) {
                    if (live) mbar_wait3(BAR(B_WO + ((wid * 5) >> 3)), BAR(B_WO + ((wid * 5 + 4) >> 3)), BAR(B_WO + ((wid * 5) >> 3)));
#pragma unroll
                    for (int i = 0; i < 5; i++) {
                        const int mt = wid * 5 + i;
                        const int cc = 2 * (mt & 3) + (mi & 1);
#pragma unroll
                        for (int ks = 0; ks < 3; ks++) {
                            const int r = ks * 16 + l8 + 8 * (mi >> 1);
                            ldsm4t(wa[i][ks], sb + SM_WO + (mt >> 2) * 6144 + r * 128 + ((cc ^ (r & 7)) << 4));
                        }
                    }
                }
                CLK(1);
                it++;
                float w[5], M = NEG_BIG;
                int c = 0;
#pragma unroll
                for (int i = 0; i < 5; i++) {
                    const bool v = hd[i].w == tag;
                    w[i] = v ? __uint_as_float(hd[i].x) : NEG_BIG;
                    M = fmaxf(M, w[i]);
                    c += v ? (int)hd[i].z : 0;
                }
                c = __reduce_add_sync(0xffffffffu, c);
                if (live && c != TPH) { if (it > SPIN_LIMIT) __trap(); continue; }
#pragma unroll
                for (int o = 16; o > 0; o >>= 1) M = fmaxf(M, __shfl_xor_sync(0xffffffffu, M, o));
                float ls = 0.f;
#pragma unroll
                for (int i = 0; i < 5; i++) {
                    const bool v = w[i] != NEG_BIG;
                    const float e = ex2((w[i] - M) * LOG2E);
                    w[i] = v ? e : -1.0f;
                    if (v) ls = fmaf(e, __uint_as_float(hd[i].y), ls);
                }
                bool bad = false;
                a0 = a1 = a2 = 0.f;
#pragma unroll
                for (int i = 0; i < MAXG / 16; i++) {
                    const float wi = __shfl_sync(0xffffffffu, w[i >> 1], rr + 16 * (i & 1));
                    if (wi >= 0.f) {
                        bad = bad || dv[i].w != tag;
                        a0 = fmaf(wi, __uint_as_float(dv[i].x), a0);
                        a1 = fmaf(wi, __uint_as_float(dv[i].y), a1);
                        a2 = fmaf(wi, __uint_as_float(dv[i].z), a2);
                    }
                }
                L = warp_sum(ls);
                if (!__any_sync(0xffffffffu, bad) || !live) break;
            }
            a0 += __shfl_xor_sync(0xffffffffu, a0, 16);
            a1 += __shfl_xor_sync(0xffffffffu, a1, 16);
            a2 += __shfl_xor_sync(0xffffffffu, a2, 16);
            CLK(2);
            if (live && lane < 16) { part[wid * 48 + 3 * k] = a0; part[wid * 48 + 3 * k + 1] = a1; part[wid * 48 + 3 * k + 2] = a2; }
            if (live) bar_cons();
            uint16_t* osw = reinterpret_cast<uint16_t*>(smem + SM_SC) + wid * 48;
            const float inv = __fdividef(1.0f, L);
            float o0 = 0.f, o1 = 0.f;
#pragma unroll
            for (int w = 0; w < 8; w++) { o0 += part[w * 48 + lane]; o1 += part[w * 48 + 32 + (lane & 15)]; }
            if (live) { osw[lane] = (uint16_t)(__float_as_uint(bfr(o0 * inv)) >> 16); if (lane < 16) osw[32 + lane] = (uint16_t)(__float_as_uint(bfr(o1 * inv)) >> 16); }
            __syncwarp();
            const uint32_t* os32 = reinterpret_cast<const uint32_t*>(osw);
            float acc[5][4] = {};
            if (live) TS(10);
            CLK(3);
#pragma unroll
            for (int ks = 0; ks < 3; ks++) {
                const uint32_t b0 = os32[ks * 8 + j4], b1 = os32[ks * 8 + 4 + j4];
#pragma unroll
                for (int i = 0; i < 5; i++) mma16816(acc[i], wa[i][ks], b0, b1);
            }
            if (live && j4 == 0) {
#pragma unroll
                for (int i = 0; i < 5; i++) { stage[(wid * 5 + i) * 16 + g4] = acc[i][0]; stage[(wid * 5 + i) * 16 + 8 + g4] = acc[i][2]; }
            }
            CLK(4);
            if (live) bar_cons();
            const int o = tid >> 1, kk = tid & 1;
            const float* sp = stage + o * 5 + kk * 3;
            float v0 = sp[0], v1 = sp[1], v2 = kk ? 0.f : sp[2];
            if (live) st_pk16(&g_h1[o][cta][kk], __float_as_uint(v0), __float_as_uint(v1), __float_as_uint(v2), tag);
        }
        if (live) TS(11);
        CLK(5);
        if (wid == 0 || !live) {
            const uint4* p = &g_h1[cta][0][0] + lane;
            uint4 v[8];
            uint32_t it = 0;
            while (true) {
                bool ok = true;
                LoadN<8, 32>::run(v, p, live, 0, 0, 1);
#pragma unroll
                for (int j = 0; j < 8; j++) ok = ok && v[j].w == tag;
                if (__all_sync(0xffffffffu, ok) || !live) break;
                if (++it > SPIN_LIMIT) __trap();
            }
            CLK(6);
            float a0 = 0.f, a1 = 0.f, a2 = 0.f;
#pragma unroll
            for (int j = 0; j < 8; j++) { a0 += __uint_as_float(v[j].x); a1 += __uint_as_float(v[j].y); a2 += __uint_as_float(v[j].z); }
#pragma unroll
            for (int o = 2; o <= 16; o <<= 1) {
                a0 += __shfl_xor_sync(0xffffffffu, a0, o);
                a1 += __shfl_xor_sync(0xffffffffu, a1, o);
                a2 += __shfl_xor_sync(0xffffffffu, a2, o);
            }
            const float gx = own[lane & 7], xx = own[16 + (lane & 7)];
            const float t0 = __shfl_sync(0xffffffffu, a0, lane >= 3), t1 = __shfl_sync(0xffffffffu, a1, lane >= 3);
            const float sum = (lane == 0 || lane == 3) ? t0 : (lane == 2 ? a2 : t1);
            const float x2 = bfr(xx + bfr(gx * bfr(sum)));
            if (live && lane < 5) own[24 + lane] = x2;
            const float y1 = __shfl_sync(0xffffffffu, x2, 1), y2 = __shfl_sync(0xffffffffu, x2, 2);
            const float y3 = __shfl_sync(0xffffffffu, x2, 3), y4 = __shfl_sync(0xffffffffu, x2, 4);
            if (live && lane == 0) st_pk16(&g_x2[cta][0], pack_bf(x2, y1), pack_bf(y2, y3), pack_bf(y4, 0.f), tag);
            if (live) TS(13);
        }
        CLK(8);
        if (cta < 96) {
            uint32_t a1[5][4], a3[5][4], a2[5][4];
            if (live) mbar_wait3(BAR(B_W1 + (wid >> 2)), BAR(B_W3 + (wid >> 2)), BAR(B_W2 + (wid >> 2)));
            const uint32_t w2b = sb + SM_RING + meta[10 + (wid >> 2)] % NSLOT * CHUNK;
#pragma unroll
            for (int ks = 0; ks < 5; ks++) {
                const int r = wid * 80 + ks * 16 + l8 + 8 * (mi >> 1);
                const uint32_t off = r * 32 + (((mi & 1) ^ ((r >> 2) & 1)) << 4);
                ldsm4t(a1[ks], sb + SM_W1 + off);
                ldsm4t(a3[ks], sb + SM_W3 + off);
            }
#pragma unroll
            for (int i = 0; i < 5; i++) {
                const int mt = (wid & 3) * 5 + i;
                const int cc = 2 * (mt & 3) + (mi & 1);
                const int r = l8 + 8 * (mi >> 1);
                ldsm4t(a2[i], w2b + (mt >> 2) * 2048 + r * 128 + ((cc ^ (r & 7)) << 4));
            }
            CLK(9);
            float* x2s = reinterpret_cast<float*>(smem + SM_X2);
            float* st8 = red + 256;
            if (wid >= 4) {
                uint4 v = poll16(&g_x2[tid - 128][0], tag, live);
                const float e0 = bf_lo(v.x), e1 = bf_hi(v.x), e2 = bf_lo(v.y), e3 = bf_hi(v.y), e4 = bf_lo(v.z);
                float* d = x2s + (tid - 128) * 5;
                if (live) { d[0] = e0; d[1] = e1; d[2] = e2; d[3] = e3; d[4] = e4; }
                const float pv = __shfl_sync(0xffffffffu, e0, 0);
                const float d0 = e0 - pv, d1 = e1 - pv, d2 = e2 - pv, d3 = e3 - pv, d4 = e4 - pv;
                float s1 = ((d0 + d1) + (d2 + d3)) + d4;
                float s2 = fmaf(d0, d0, fmaf(d1, d1, fmaf(d2, d2, fmaf(d3, d3, d4 * d4))));
#pragma unroll
                for (int o = 16; o > 0; o >>= 1) { s1 += __shfl_xor_sync(0xffffffffu, s1, o); s2 += __shfl_xor_sync(0xffffffffu, s2, o); }
                if (live && lane == 0) { st8[2 * (wid - 4)] = pv + s1 * (1.0f / 160.0f); st8[2 * (wid - 4) + 1] = s2 - s1 * s1 * (1.0f / 160.0f); }
            }
            if (live) bar_cons();
            if (live) TS(14);
            CLK(10);
            const float4 sA = *reinterpret_cast<const float4*>(st8), sB = *reinterpret_cast<const float4*>(st8 + 4);
            const float mean = ((sA.x + sA.z) + (sB.x + sB.z)) * 0.25f;
            const float u0 = sA.x - mean, u1 = sA.z - mean, u2 = sB.x - mean, u3 = sB.z - mean;
            const float m2 = ((sA.y + sA.w) + (sB.y + sB.w)) + 160.0f * ((u0 * u0 + u1 * u1) + (u2 * u2 + u3 * u3));
            const float mean_b = bfr(mean);
            const float rden = __fdividef(1.0f, bfr(fsqrt(bfr(bfr(m2 * (1.0f / 640.0f)) + 1e-5f))));
            const uint32_t* cb32 = reinterpret_cast<const uint32_t*>(smem + SM_CB);
            const uint32_t* sb32 = reinterpret_cast<const uint32_t*>(smem + SM_SB);
#pragma unroll
            for (int rep = 0; rep < 2; rep++) {
                const int p = lane + 32 * rep;
                if (p < 40) {
                    int pp = wid * 40 + p;
                    const float2 xv = *reinterpret_cast<const float2*>(x2s + 2 * pp);
                    uint32_t cv = cb32[pp], sv = sb32[pp];
                    float n0 = bfr(bfr(xv.x - mean_b) * rden), n1 = bfr(bfr(xv.y - mean_b) * rden);
                    uint32_t hv = pack_bf(bfr(n0 * bf_lo(cv)) + bf_lo(sv), bfr(n1 * bf_hi(cv)) + bf_hi(sv));
                    if (live) h32[pp] = hv;
                }
            }
            __syncwarp();
            CLK(11);
            float ag[2][4] = {}, au[2][4] = {};
#pragma unroll
            for (int ks = 0; ks < 5; ks++) {
                const int r0 = wid * 80 + ks * 16;
                const uint32_t b0 = h32[(r0 >> 1) + j4], b1 = h32[(r0 >> 1) + 4 + j4];
                mma16816(ag[ks & 1], a1[ks], b0, b1);
                mma16816(au[ks & 1], a3[ks], b0, b1);
            }
            if (live && j4 == 0) {
                red[wid * 32 + g4] = ag[0][0] + ag[1][0]; red[wid * 32 + 8 + g4] = ag[0][2] + ag[1][2];
                red[wid * 32 + 16 + g4] = au[0][0] + au[1][0]; red[wid * 32 + 24 + g4] = au[0][2] + au[1][2];
            }
            CLK(12);
            if (live) bar_cons();
            if (live) TS(15);
            CLK(13);
            float v = 0.f;
#pragma unroll
            for (int w = 0; w < 8; w++) v += red[w * 32 + lane];
            v = bfr(v);
            float up = __shfl_down_sync(0xffffffffu, v, 16);
            float hact = bfr(bfr(silu(v)) * up);
            float e0 = __shfl_sync(0xffffffffu, hact, 2 * j4), e1 = __shfl_sync(0xffffffffu, hact, 2 * j4 + 1);
            float e2 = __shfl_sync(0xffffffffu, hact, 2 * j4 + 8), e3 = __shfl_sync(0xffffffffu, hact, 2 * j4 + 9);
            const uint32_t b0 = pack_bf(e0, e1), b1 = pack_bf(e2, e3);
            float acc[5][4] = {};
#pragma unroll
            for (int i = 0; i < 5; i++) mma16816(acc[i], a2[i], b0, b1);
            if (live && j4 == 0) {
#pragma unroll
                for (int i = 0; i < 5; i++) { stage[(wid * 5 + i) * 16 + g4] = acc[i][0]; stage[(wid * 5 + i) * 16 + 8 + g4] = acc[i][2]; }
            }
            CLK(14);
            if (live) bar_cons();
            const int o = tid >> 1, k = tid & 1;
            const float* sp = stage + o * 5 + k * 3;
            float v0 = sp[0], v1 = sp[1], v2 = k ? 0.f : sp[2];
            if (live) st_pk16(&g_h3[o][cta][k], __float_as_uint(v0), __float_as_uint(v1), __float_as_uint(v2), tag);
        }
        if (live) TS(16);
        CLK(15);
        if (wid == 0 || !live) {
            const uint4* p = &g_h3[cta][0][0] + lane;
            uint4 v[6];
            uint32_t it = 0;
            if (live && cta < 96) spin(P_DLY);
            while (true) {
                bool ok = true;
                LoadN<6, 32>::run(v, p, live, 0, 0, 1);
#pragma unroll
                for (int j = 0; j < 6; j++) ok = ok && v[j].w == tag;
                if (__all_sync(0xffffffffu, ok) || !live) break;
                if (++it > SPIN_LIMIT) __trap();
            }
            CLK(16);
            float a0 = 0.f, a1 = 0.f, a2 = 0.f;
#pragma unroll
            for (int j = 0; j < 6; j++) { a0 += __uint_as_float(v[j].x); a1 += __uint_as_float(v[j].y); a2 += __uint_as_float(v[j].z); }
#pragma unroll
            for (int o = 2; o <= 16; o <<= 1) {
                a0 += __shfl_xor_sync(0xffffffffu, a0, o);
                a1 += __shfl_xor_sync(0xffffffffu, a1, o);
                a2 += __shfl_xor_sync(0xffffffffu, a2, o);
            }
            const float gx = own[8 + (lane & 7)], xx = own[24 + (lane & 7)];
            const float t0 = __shfl_sync(0xffffffffu, a0, lane >= 3), t1 = __shfl_sync(0xffffffffu, a1, lane >= 3);
            const float sum = (lane == 0 || lane == 3) ? t0 : (lane == 2 ? a2 : t1);
            const float y = xx + bfr(gx * bfr(sum));
            if (live && lane < 5) reinterpret_cast<uint16_t*>(out)[cta * 5 + lane] = (uint16_t)(__float_as_uint(bfr(y)) >> 16);
            if (live && cta == 0 && lane == 0) g_epoch = tag;
        }
        CLK(17);
        if (live) { TS(18); break; }
        live = true;
    }
    }
}

typedef CUresult (*EncodeFn)(CUtensorMap*, CUtensorMapDataType, cuuint32_t, void*, const cuuint64_t*, const cuuint64_t*,
                             const cuuint32_t*, const cuuint32_t*, CUtensorMapInterleave, CUtensorMapSwizzle,
                             CUtensorMapL2promotion, CUtensorMapFloatOOBfill);

void make_map(EncodeFn enc, CUtensorMap* tm, const void* ptr, uint64_t cols, uint64_t rows, uint32_t box_c, uint32_t box_r,
              CUtensorMapSwizzle sw, CUtensorMapL2promotion prom) {
    cuuint64_t dims[2] = {cols, rows};
    cuuint64_t strides[1] = {cols * 2};
    cuuint32_t box[2] = {box_c, box_r};
    cuuint32_t es[2] = {1, 1};
    enc(tm, CU_TENSOR_MAP_DATA_TYPE_BFLOAT16, 2, const_cast<void*>(ptr), dims, strides, box, es,
        CU_TENSOR_MAP_INTERLEAVE_NONE, sw, prom, CU_TENSOR_MAP_FLOAT_OOB_FILL_NONE);
}

}

extern "C" void kernel_launch(void* const* d_in, const int* in_sizes, int n_in, void* d_out, int out_size) {
    (void)in_sizes; (void)n_in; (void)out_size;
    static EncodeFn enc = nullptr;
    static int num_sms = 0;
    if (!enc) {
        void* fn = nullptr;
        cudaDriverEntryPointQueryResult qr;
        cudaGetDriverEntryPoint("cuTensorMapEncodeTiled", &fn, cudaEnableDefault, &qr);
        enc = (EncodeFn)fn;
        cudaDeviceGetAttribute(&num_sms, cudaDevAttrMultiProcessorCount, 0);
        cudaFuncSetAttribute(fused_decode_kernel, cudaFuncAttributeMaxDynamicSharedMemorySize, SM_TOTAL);
    }
    CUtensorMap tmK, tmV, tmMod, tmWq, tmWo, tmW1, tmW3, tmW2;
    const uint64_t kv_lines = (uint64_t)NH * SK * 3;
    make_map(enc, &tmK, d_in[1], 64, kv_lines, 64, 96, CU_TENSOR_MAP_SWIZZLE_128B, CU_TENSOR_MAP_L2_PROMOTION_L2_128B);
    make_map(enc, &tmV, d_in[2], 64, kv_lines, 64, 96, CU_TENSOR_MAP_SWIZZLE_128B, CU_TENSOR_MAP_L2_PROMOTION_L2_128B);
    make_map(enc, &tmWq, d_in[3], NH * DH, D, 48, 128, CU_TENSOR_MAP_SWIZZLE_NONE, CU_TENSOR_MAP_L2_PROMOTION_L2_128B);
    make_map(enc, &tmWo, d_in[4], D, NH * DH, 64, 48, CU_TENSOR_MAP_SWIZZLE_128B, CU_TENSOR_MAP_L2_PROMOTION_L2_128B);
    make_map(enc, &tmW1, d_in[6], FF, D, 16, 160, CU_TENSOR_MAP_SWIZZLE_32B, CU_TENSOR_MAP_L2_PROMOTION_L2_128B);
    make_map(enc, &tmW3, d_in[7], FF, D, 16, 160, CU_TENSOR_MAP_SWIZZLE_32B, CU_TENSOR_MAP_L2_PROMOTION_L2_128B);
    make_map(enc, &tmW2, d_in[8], D, FF, 64, 16, CU_TENSOR_MAP_SWIZZLE_128B, CU_TENSOR_MAP_L2_PROMOTION_L2_128B);
    make_map(enc, &tmMod, d_in[10], 6 * D, D, 32, 160, CU_TENSOR_MAP_SWIZZLE_64B, CU_TENSOR_MAP_L2_PROMOTION_L2_128B);
    int grid = num_sms < MAXG ? num_sms : MAXG;
    fused_decode_kernel<<<grid, NTHREADS, SM_TOTAL, cudaStreamPerThread>>>(
        tmK, tmV, tmMod, tmWq, tmWo, tmW1, tmW3, tmW2, (const __nv_bfloat16*)d_in[0], (const __nv_bfloat16*)d_in[9],
        (__nv_bfloat16*)d_out);
}
```

```cpp
#include <cuda_runtime.h>
#include <cuda_bf16.h>
#include <cuda.h>
#include <stdint.h>

namespace {

constexpr int D = 640, NH = 32, SK = 8192, DH = 192, FF = 1536;
constexpr int NG = 4;
constexpr int GH = 7;
constexpr int NGLOB = NH - NG * GH;
constexpr int NQH = GH + NGLOB;
constexpr int TILE = 32;
constexpr int TPH = SK / TILE;
constexpr int GT = GH * TPH;
constexpr int PT = NGLOB * TPH;
constexpr int CHUNK = TILE * DH * 2;
#define P_NSLOT 8
#define P_WIN 3
#define P_URG 132
#define P_DLY 450
constexpr int NSLOT = P_NSLOT;
constexpr int WIN = P_WIN;
constexpr int MAXG = 132;
constexpr int NTHREADS = 288;
constexpr float NEG_BIG = -3.402823466e38f;

constexpr int SM_WMOD = 0;
constexpr int SM_WQ = 40960;
constexpr int SM_WO = 0;
constexpr int SM_W1 = 61440;
constexpr int SM_W3 = 81920;
constexpr int SM_RING = 102400;
constexpr int SM_MISC = SM_RING + NSLOT * CHUNK;
constexpr int SM_BARS = SM_MISC;
constexpr int SM_META = SM_BARS + 512;
constexpr int SM_Q = SM_META + 128;
constexpr int SM_SC = SM_Q + NQH * DH * 2;
constexpr int SM_H = SM_SC + 1280;
constexpr int SM_X = SM_H + 1280;
constexpr int SM_CB = SM_X + 1280;
constexpr int SM_SB = SM_CB + 1280;
constexpr int SM_OWN = SM_SB + 1280;
constexpr int SM_RED = SM_OWN + 128;
constexpr int SM_MERGE = SM_RED + 2048;
constexpr int SM_STAGE = SM_MERGE + 3200;
constexpr int SM_X2 = SM_STAGE + 2560;
constexpr int SM_FIN = SM_X2 + 2560;
constexpr int SM_TOTAL = SM_FIN + 256;
static_assert(SM_TOTAL <= 232448, "shared memory budget");

constexpr int B_FULL = 0;
constexpr int B_EMPTY = 8;
constexpr int B_MOD = 16;
constexpr int B_WQ = 20;
constexpr int B_WO = 25;
constexpr int B_W1 = 30;
constexpr int B_W3 = 32;
constexpr int B_W2 = 34;
constexpr int B_FLF = 36, B_FLE = 37, B_PRO = 38, B_DUMMY = 39;
static_assert(NSLOT <= 8 && NSLOT >= 6 && WIN <= 4 && WIN <= NSLOT - 3, "barrier map / end markers vs window");
constexpr uint32_t META_END = 0x10000u;

__device__ unsigned g_epoch;
__device__ unsigned g_ctr[2][(NG + 1) * 32];
__device__ __align__(128) unsigned long long g_mod[1920];
__device__ __align__(128) unsigned long long g_q[3072];
__device__ __align__(128) uint4 g_hdr[NH][MAXG];
__device__ __align__(128) uint4 g_dat[NH][MAXG][64];
__device__ __align__(128) uint4 g_h1[128][128][2];
__device__ __align__(128) uint4 g_x2[128][2];
__device__ __align__(128) uint4 g_h3[128][96][2];

#define TS(k) do {} while (0)
#define DBG(k) do {} while (0)
#define CLK(k) do {} while (0)

__device__ __forceinline__ uint32_t smem_u32(const void* p) { return (uint32_t)__cvta_generic_to_shared(p); }
__device__ __forceinline__ void mbar_init(uint32_t bar, uint32_t cnt) {
    asm volatile("mbarrier.init.shared::cta.b64 [%0], %1;" ::"r"(bar), "r"(cnt) : "memory");
}
__device__ __forceinline__ void mbar_expect_tx(uint32_t bar, uint32_t bytes) {
    asm volatile("mbarrier.arrive.expect_tx.shared::cta.b64 _, [%0], %1;" ::"r"(bar), "r"(bytes) : "memory");
}
__device__ __forceinline__ void mbar_arrive(uint32_t bar) {
    asm volatile("mbarrier.arrive.shared::cta.b64 _, [%0];" ::"r"(bar) : "memory");
}
constexpr uint32_t SPIN_LIMIT = 1u << 22;
__device__ __forceinline__ void mbar_wait(uint32_t bar, uint32_t parity) {
    asm volatile(
        "{\n.reg .pred p;\n.reg .u32 c;\nmov.u32 c, 0;\n"
        "LW:\nmbarrier.try_wait.parity.shared::cta.b64 p, [%0], %1;\n@p bra LD;\n"
        "add.u32 c, c, 1;\nsetp.lt.u32 p, c, 0x400000;\n@p bra LW;\ntrap;\nLD:\n}" ::"r"(bar), "r"(parity)
        : "memory");
}
__device__ __forceinline__ uint32_t mbar_try(uint32_t bar, uint32_t parity) {
    uint32_t ok;
    asm volatile("{\n.reg .pred p;\nmbarrier.try_wait.parity.shared::cta.b64 p, [%1], %2;\nselp.u32 %0, 1, 0, p;\n}"
                 : "=r"(ok) : "r"(bar), "r"(parity) : "memory");
    return ok;
}
__device__ __forceinline__ void mbar_wait3(uint32_t b0, uint32_t b1, uint32_t b2) {
    asm volatile(
        "{\n.reg .pred p, q, r;\n.reg .u32 c;\nmov.u32 c, 0;\n"
        "LW:\nmbarrier.try_wait.parity.shared::cta.b64 p, [%0], 0;\n"
        "mbarrier.try_wait.parity.shared::cta.b64 q, [%1], 0;\n"
        "mbarrier.try_wait.parity.shared::cta.b64 r, [%2], 0;\n"
        "and.pred p, p, q;\nand.pred p, p, r;\n@p bra LD;\n"
        "add.u32 c, c, 1;\nsetp.lt.u32 p, c, 0x400000;\n@p bra LW;\ntrap;\nLD:\n}" ::"r"(b0), "r"(b1), "r"(b2)
        : "memory");
}
__device__ __forceinline__ void tma2d(uint32_t dst, const CUtensorMap* tm, int c0, int c1, uint32_t bar) {
    asm volatile(
        "cp.async.bulk.tensor.2d.shared::cluster.global.mbarrier::complete_tx::bytes [%0], [%1, {%3, %4}], [%2];" ::"r"(dst),
        "l"(tm), "r"(bar), "r"(c0), "r"(c1)
        : "memory");
}
__device__ __forceinline__ void tma2d_hint(uint32_t dst, const CUtensorMap* tm, int c0, int c1, uint32_t bar, uint64_t pol) {
    asm volatile(
        "cp.async.bulk.tensor.2d.shared::cluster.global.mbarrier::complete_tx::bytes.L2::cache_hint [%0], [%1, {%3, %4}], [%2], %5;" ::"r"(dst),
        "l"(tm), "r"(bar), "r"(c0), "r"(c1), "l"(pol)
        : "memory");
}
__device__ __forceinline__ void prefetch_tm(const CUtensorMap* tm) {
    asm volatile("prefetch.tensormap [%0];" ::"l"(tm) : "memory");
}
__device__ __forceinline__ void ldsm4(uint32_t (&r)[4], uint32_t addr) {
    asm volatile("ldmatrix.sync.aligned.m8n8.x4.shared.b16 {%0,%1,%2,%3}, [%4];"
                 : "=r"(r[0]), "=r"(r[1]), "=r"(r[2]), "=r"(r[3])
                 : "r"(addr));
}
__device__ __forceinline__ void ldsm4t(uint32_t (&r)[4], uint32_t addr) {
    asm volatile("ldmatrix.sync.aligned.m8n8.x4.trans.shared.b16 {%0,%1,%2,%3}, [%4];"
                 : "=r"(r[0]), "=r"(r[1]), "=r"(r[2]), "=r"(r[3])
                 : "r"(addr));
}
__device__ __forceinline__ void mma16816(float (&d)[4], const uint32_t (&a)[4], uint32_t b0, uint32_t b1) {
    asm volatile(
        "mma.sync.aligned.m16n8k16.row.col.f32.bf16.bf16.f32 {%0,%1,%2,%3}, {%4,%5,%6,%7}, {%8,%9}, {%0,%1,%2,%3};"
        : "+f"(d[0]), "+f"(d[1]), "+f"(d[2]), "+f"(d[3])
        : "r"(a[0]), "r"(a[1]), "r"(a[2]), "r"(a[3]), "r"(b0), "r"(b1));
}
__device__ __forceinline__ void bar_cons() { asm volatile("bar.sync 1, 256;" ::: "memory"); }
__device__ __forceinline__ void spin(int cycles) {
    long long t0 = clock64();
    while (clock64() - t0 < cycles) {}
}

__device__ __forceinline__ float bfr(float x) {
    uint32_t r;
    asm("cvt.rn.bf16x2.f32 %0, %1, %2;" : "=r"(r) : "f"(x), "f"(0.0f));
    return __uint_as_float(r);
}
__device__ __forceinline__ uint32_t pack_bf(float lo, float hi) {
    __nv_bfloat162 t = __floats2bfloat162_rn(lo, hi);
    return *reinterpret_cast<uint32_t*>(&t);
}
__device__ __forceinline__ float bf_lo(uint32_t v) { return __uint_as_float(v << 16); }
__device__ __forceinline__ float bf_hi(uint32_t v) { return __uint_as_float(v & 0xffff0000u); }

__device__ __forceinline__ void st_pk8(unsigned long long* p, uint32_t v, uint32_t tag) {
    unsigned long long w = ((unsigned long long)tag << 32) | v;
    asm volatile("st.relaxed.gpu.global.b64 [%0], %1;" ::"l"(p), "l"(w) : "memory");
}
__device__ __forceinline__ unsigned long long ld_raw8(const unsigned long long* p) {
    unsigned long long w;
    asm volatile("ld.relaxed.gpu.global.b64 %0, [%1];" : "=l"(w) : "l"(p) : "memory");
    return w;
}
template <int N>
__device__ __forceinline__ void poll8(const unsigned long long* base, const int (&off)[N], uint32_t (&val)[N], uint32_t tag) {
    uint32_t it = 0;
    while (true) {
        unsigned long long w[N];
#pragma unroll
        for (int i = 0; i < N; i++) w[i] = ld_raw8(base + off[i]);
        bool ok = true;
#pragma unroll
        for (int i = 0; i < N; i++) { ok = ok && ((uint32_t)(w[i] >> 32) == tag); val[i] = (uint32_t)w[i]; }
        if (__all_sync(0xffffffffu, ok)) break;
        if (++it > SPIN_LIMIT) __trap();
    }
}
__device__ __forceinline__ void st_pk16(uint4* p, uint32_t a, uint32_t b, uint32_t c, uint32_t tag) {
    asm volatile(
        "{\n.reg .b128 t;\n.reg .b64 lo, hi;\nmov.b64 lo, {%1, %2};\nmov.b64 hi, {%3, %4};\nmov.b128 t, {lo, hi};\n"
        "st.relaxed.gpu.global.b128 [%0], t;\n}" ::"l"(p), "r"(a), "r"(b), "r"(c), "r"(tag)
        : "memory");
}
template <int OFF = 0>
__device__ __forceinline__ uint4 ld_raw16p(const uint4* p, uint32_t on) {
    uint4 v;
    asm volatile(
        "{\n.reg .b128 t;\n.reg .b64 lo, hi;\n.reg .pred q;\nsetp.ne.u32 q, %5, 0;\n"
        "mov.b64 lo, 0;\nmov.b128 t, {lo, lo};\n"
        "@q ld.relaxed.gpu.global.b128 t, [%4 + %6];\nmov.b128 {lo, hi}, t;\n"
        "mov.b64 {%0, %1}, lo;\nmov.b64 {%2, %3}, hi;\n}"
        : "=r"(v.x), "=r"(v.y), "=r"(v.z), "=r"(v.w)
        : "l"(p), "r"(on), "n"(OFF * 16)
        : "memory");
    return v;
}
template <int OFF>
__device__ __forceinline__ void ld_fresh16(uint4& v, const uint4* p, uint32_t tag, uint32_t on) {
    asm volatile(
        "{\n.reg .b128 t;\n.reg .b64 lo, hi;\n.reg .pred q;\nsetp.ne.u32 q, %3, %5;\nsetp.ne.and.u32 q, %6, 0, q;\n"
        "mov.b64 lo, {%0, %1};\nmov.b64 hi, {%2, %3};\nmov.b128 t, {lo, hi};\n"
        "@q ld.relaxed.gpu.global.b128 t, [%4 + %7];\nmov.b128 {lo, hi}, t;\n"
        "mov.b64 {%0, %1}, lo;\nmov.b64 {%2, %3}, hi;\n}"
        : "+r"(v.x), "+r"(v.y), "+r"(v.z), "+r"(v.w)
        : "l"(p), "r"(tag), "r"(on), "n"(OFF * 16)
        : "memory");
}
template <int N, int STRIDE, int I = 0>
struct FreshN {
    static __device__ __forceinline__ void run(uint4* v, const uint4* p, uint32_t tag, bool live, int base, int step, int lim) {
        ld_fresh16<I * STRIDE>(v[I], p, tag, live && base + step * I < lim);
        FreshN<N, STRIDE, I + 1>::run(v, p, tag, live, base, step, lim);
    }
};
template <int N, int STRIDE>
struct FreshN<N, STRIDE, N> {
    static __device__ __forceinline__ void run(uint4*, const uint4*, uint32_t, bool, int, int, int) {}
};
template <int N, int STRIDE, int I = 0>
struct LoadN {
    static __device__ __forceinline__ void run(uint4* v, const uint4* p, bool live, int base, int step, int lim) {
        v[I] = ld_raw16p<I * STRIDE>(p, live && base + step * I < lim);
        LoadN<N, STRIDE, I + 1>::run(v, p, live, base, step, lim);
    }
};
template <int N, int STRIDE>
struct LoadN<N, STRIDE, N> {
    static __device__ __forceinline__ void run(uint4*, const uint4*, bool, int, int, int) {}
};
__device__ __forceinline__ uint4 poll16(const uint4* p, uint32_t tag, bool live) {
    uint32_t it = 0;
    uint4 v;
    while (true) {
        v = ld_raw16p(p, live);
        if (__all_sync(0xffffffffu, v.w == tag) || !live) break;
        if (++it > SPIN_LIMIT) __trap();
    }
    return v;
}
__device__ __forceinline__ void st_zero16(void* p) {
    asm volatile("st.relaxed.gpu.global.v4.u32 [%0], {%1, %1, %1, %1};" ::"l"(p), "r"(0u) : "memory");
}
__device__ __forceinline__ float ex2(float x) {
    float y;
    asm("ex2.approx.ftz.f32 %0, %1;" : "=f"(y) : "f"(x));
    return y;
}
__device__ __forceinline__ float fsqrt(float x) {
    float y;
    asm("sqrt.approx.f32 %0, %1;" : "=f"(y) : "f"(x));
    return y;
}
constexpr float LOG2E = 1.4426950408889634f;
__device__ __forceinline__ float silu(float a) { return __fdividef(a, 1.0f + ex2(-a * LOG2E)); }
__device__ __forceinline__ float warp_sum(float v) {
#pragma unroll
    for (int o = 16; o > 0; o >>= 1) v += __shfl_xor_sync(0xffffffffu, v, o);
    return v;
}

__device__ __forceinline__ void ln_stats(const float (&v)[20], float& mean_b, float& den_b) {
    float s = 0.f;
#pragma unroll
    for (int i = 0; i < 20; i++) s += v[i];
    s = warp_sum(s);
    float mean = s * (1.0f / 640.0f);
    float q = 0.f;
#pragma unroll
    for (int i = 0; i < 20; i++) { float d = v[i] - mean; q += d * d; }
    q = warp_sum(q);
    float var_b = bfr(q * (1.0f / 640.0f));
    mean_b = bfr(mean);
    den_b = bfr(fsqrt(bfr(var_b + 1e-5f)));
}

struct Window {
    uint32_t bar[WIN];
    uint32_t par[WIN];
    __device__ __forceinline__ void init(uint32_t dummy) {
#pragma unroll
        for (int i = 0; i < WIN; i++) { bar[i] = dummy; par[i] = 1; }
    }
    __device__ __forceinline__ void push(uint32_t b, uint32_t p, bool wait = true) {
        if (wait) mbar_wait(bar[0], par[0]);
#pragma unroll
        for (int i = 0; i + 1 < WIN; i++) { bar[i] = bar[i + 1]; par[i] = par[i + 1]; }
        bar[WIN - 1] = b; par[WIN - 1] = p;
    }
};

__global__ void __launch_bounds__(NTHREADS, 1)
fused_decode_kernel(const __grid_constant__ CUtensorMap tmK, const __grid_constant__ CUtensorMap tmV,
                    const __grid_constant__ CUtensorMap tmMod, const __grid_constant__ CUtensorMap tmWq,
                    const __grid_constant__ CUtensorMap tmWo, const __grid_constant__ CUtensorMap tmW1,
                    const __grid_constant__ CUtensorMap tmW3, const __grid_constant__ CUtensorMap tmW2,
                    const __nv_bfloat16* __restrict__ x_in, const __nv_bfloat16* __restrict__ c_in,
                    __nv_bfloat16* __restrict__ out) {
    extern __shared__ __align__(1024) uint8_t smem[];
    const uint32_t sb = smem_u32(smem);
    const int tid = threadIdx.x, wid = tid >> 5, lane = tid & 31;
    const int cta = blockIdx.x, G = gridDim.x;
    const int grp = cta % NG, rank = cta / NG;
    const uint32_t bars = sb + SM_BARS;
    auto BAR = [&](int i) { return bars + 8u * i; };
    volatile uint32_t* meta = reinterpret_cast<volatile uint32_t*>(smem + SM_META);

    if (wid >= 8) {
        Window win;
        unsigned epoch = 0;
        if (tid == 256) {
            TS(0);
            if (sb & 1023u) __trap();
            asm volatile("ld.relaxed.gpu.global.u32 %0, [%1];" : "=r"(epoch) : "l"(&g_epoch) : "memory");
            prefetch_tm(&tmMod); prefetch_tm(&tmWq); prefetch_tm(&tmK); prefetch_tm(&tmV);
#pragma unroll
            for (int i = 0; i < 4; i++) mbar_init(BAR(B_MOD + i), 1);
            mbar_init(BAR(B_DUMMY), 1);
            asm volatile("fence.mbarrier_init.release.cluster;" ::: "memory");
            asm volatile("fence.proxy.async.shared::cta;" ::: "memory");
            win.init(BAR(B_DUMMY));
            if (cta < 120) {
#pragma unroll 1
                for (int i = 0; i < WIN; i++) {
                    win.push(BAR(B_MOD + i), 0);
                    mbar_expect_tx(BAR(B_MOD + i), 10240);
                    tma2d(sb + SM_WMOD + i * 10240, &tmMod, cta * 32, i * 160, BAR(B_MOD + i));
                }
            }
#pragma unroll 1
            for (int i = 0; i < B_DUMMY; i++) {
                if (i >= B_MOD && i < B_MOD + 4) continue;
                int cnt = (i >= B_EMPTY && i < B_MOD) ? 2 : (i == B_FLF ? 4 : 1);
                mbar_init(BAR(i), cnt);
            }
            asm volatile("fence.mbarrier_init.release.cluster;" ::: "memory");
            asm volatile("fence.proxy.async.shared::cta;" ::: "memory");
        }
        __syncwarp();
        __syncthreads();
        if (tid == 256) {
            prefetch_tm(&tmWo); prefetch_tm(&tmW1); prefetch_tm(&tmW3); prefetch_tm(&tmW2);
            unsigned* ctr = &g_ctr[epoch & 1][grp * 32];
            unsigned* gctr = &g_ctr[epoch & 1][NG * 32];
            if (cta == 0) {
                for (int g = 0; g <= NG; g++) g_ctr[(epoch + 1) & 1][g * 32] = 0;
            }
            unsigned pend = atomicAdd(ctr, 1);
            if (cta < 120) {
#pragma unroll 1
                for (int i = WIN; i < 4; i++) {
                    win.push(BAR(B_MOD + i), 0);
                    mbar_expect_tx(BAR(B_MOD + i), 10240);
                    tma2d(sb + SM_WMOD + i * 10240, &tmMod, cta * 32, i * 160, BAR(B_MOD + i));
                }
            }
            if (cta < 128) {
#pragma unroll 1
                for (int i = 0; i < 5; i++) {
                    win.push(BAR(B_WQ + i), 0);
                    mbar_expect_tx(BAR(B_WQ + i), 12288);
                    tma2d(sb + SM_WQ + i * 12288, &tmWq, cta * 48, i * 128, BAR(B_WQ + i));
                }
            }
            uint64_t pol;
            asm volatile("createpolicy.fractional.L2::evict_first.b64 %0, 1.0;" : "=l"(pol));
            int s = 0; uint32_t par = 0;
            int ntiles = 0, run = -1, last_head = -1;
            bool glob = false;
#pragma unroll 1
            while (true) {
                unsigned t = pend;
                if (!glob && t >= (unsigned)GT) { glob = true; t = atomicAdd(gctr, 1); }
                if (glob && t >= (unsigned)PT) break;
                pend = atomicAdd(glob ? gctr : ctr, 1);
                ntiles++;
                const int hl = t / TPH, tile = t % TPH;
                const int head = glob ? NG * GH + hl : grp * GH + hl;
                const int qidx = glob ? GH + hl : hl;
                if (head != last_head) { last_head = head; run++; meta[16 + run] = head; }
                const int line0 = (head * SK + tile * TILE) * 3;
                const bool urgent = glob && t >= (unsigned)(PT - P_URG);
#pragma unroll 1
                for (int kv = 0; kv < 2; kv++) {
                    win.push(BAR(B_FULL + s), par, !urgent);
                    mbar_wait(BAR(B_EMPTY + s), par ^ 1);
                    meta[s] = run | (qidx << 8);
                    mbar_expect_tx(BAR(B_FULL + s), CHUNK);
                    tma2d_hint(sb + SM_RING + s * CHUNK, kv ? &tmV : &tmK, 0, line0, BAR(B_FULL + s), pol);
                    if (++s == NSLOT) { s = 0; par ^= 1; }
                }
            }
            TS(5);
            meta[16 + run + 1] = 0xFFu;
#pragma unroll 1
            for (int e = 0; e < 2; e++) {
                mbar_wait(BAR(B_EMPTY + s), par ^ 1);
                meta[s] = (run + 1) | META_END;
                mbar_arrive(BAR(B_FULL + s));
                if (++s == NSLOT) { s = 0; par ^= 1; }
                if (++s == NSLOT) { s = 0; par ^= 1; }
            }
            if (cta < 128) {
                mbar_wait(BAR(B_PRO), 0);
#pragma unroll 1
                for (int i = 0; i < 5; i++) {
                    win.push(BAR(B_WO + i), 0);
                    mbar_expect_tx(BAR(B_WO + i), 12288);
                    tma2d(sb + SM_WO + (2 * i) * 6144, &tmWo, (2 * i) * 64, cta * 48, BAR(B_WO + i));
                    tma2d(sb + SM_WO + (2 * i + 1) * 6144, &tmWo, (2 * i + 1) * 64, cta * 48, BAR(B_WO + i));
                }
                if (cta < 96) {
#pragma unroll 1
                    for (int i = 0; i < 4; i++) {
                        const int m = i & 1, hf = i >> 1;
                        const uint32_t bar = BAR((m ? B_W3 : B_W1) + hf);
                        const uint32_t dst = sb + (m ? SM_W3 : SM_W1) + hf * 10240;
                        const CUtensorMap* tm = m ? &tmW3 : &tmW1;
                        win.push(bar, 0);
                        mbar_expect_tx(bar, 10240);
                        tma2d(dst, tm, cta * 16, hf * 320, bar);
                        tma2d(dst + 5120, tm, cta * 16, hf * 320 + 160, bar);
                    }
#pragma unroll 1
                    for (int i = 0; i < 2; i++) {
                        win.push(BAR(B_W2 + i), 0);
                        mbar_wait(BAR(B_EMPTY + s), par ^ 1);
                        meta[10 + i] = s;
                        mbar_expect_tx(BAR(B_W2 + i), 10240);
#pragma unroll 1
                        for (int b = 0; b < 5; b++)
                            tma2d(sb + SM_RING + s * CHUNK + b * 2048, &tmW2, (5 * i + b) * 64, cta * 16, BAR(B_W2 + i));
                        if (++s == NSLOT) { s = 0; par ^= 1; }
                    }
                }
            }
            TS(6);
        }
    } else {
    const int g4 = lane >> 2, j4 = lane & 3, mi = lane >> 3, l8 = lane & 7;
    uint32_t* sc32 = reinterpret_cast<uint32_t*>(smem + SM_SC);
    uint32_t* h32 = reinterpret_cast<uint32_t*>(smem + SM_H);
    uint32_t* x32 = reinterpret_cast<uint32_t*>(smem + SM_X);
    uint32_t* q32 = reinterpret_cast<uint32_t*>(smem + SM_Q);
    float* red = reinterpret_cast<float*>(smem + SM_RED);
    float* stage = reinterpret_cast<float*>(smem + SM_STAGE);
    float* own = reinterpret_cast<float*>(smem + SM_OWN);

    {
        const uint32_t* cg = reinterpret_cast<const uint32_t*>(c_in);
        const uint32_t* xg = reinterpret_cast<const uint32_t*>(x_in);
        uint32_t c0 = cg[tid], x0 = xg[tid], c1 = 0, x1 = 0;
        if (tid < 64) { c1 = cg[256 + tid]; x1 = xg[256 + tid]; }
        unsigned epoch = 0;
        if (tid == 0) asm volatile("ld.relaxed.gpu.global.u32 %0, [%1];" : "=r"(epoch) : "l"(&g_epoch) : "memory");
        if (cta < 120 && tid < 8) st_zero16(reinterpret_cast<uint4*>(&g_mod[cta * 16]) + tid);
        if (cta < 128 && tid >= 32 && tid < 44) st_zero16(reinterpret_cast<uint4*>(&g_q[cta * 24]) + (tid - 32));
        if (cta < 128) {
            if (tid >= 64 && tid < 66) st_zero16(&g_x2[cta][tid - 64]);
            st_zero16(&g_h1[tid >> 1][cta][tid & 1]);
            if (cta < 96) st_zero16(&g_h3[tid >> 1][cta][tid & 1]);
        }
#pragma unroll 1
        for (int f = tid >> 6; f < NQH; f += 4) {
            const int head = f < GH ? grp * GH + f : NG * GH + (f - GH);
            const int idx = f < GH ? rank : cta;
            st_zero16(&g_dat[head][idx][tid & 63]);
            if ((tid & 63) == 0) st_zero16(&g_hdr[head][idx]);
        }
        sc32[tid] = pack_bf(silu(bf_lo(c0)), silu(bf_hi(c0))); x32[tid] = x0;
        if (tid < 64) { sc32[256 + tid] = pack_bf(silu(bf_lo(c1)), silu(bf_hi(c1))); x32[256 + tid] = x1; }
        if (tid == 0) meta[8] = epoch + 1;
    }
    __syncthreads();
    const uint32_t tag = meta[8];

    float mean_x = 0.f, rden_x = 1.f;
    if (cta < 128) {
        float xv[20];
#pragma unroll
        for (int i = 0; i < 10; i++) { uint32_t v = x32[lane + 32 * i]; xv[2 * i] = bf_lo(v); xv[2 * i + 1] = bf_hi(v); }
        float den;
        ln_stats(xv, mean_x, den);
        rden_x = __fdividef(1.0f, den);
    }

    if (cta < 120) {
        float acc[2][4] = {};
        uint32_t a[5][2][4], bb[5][2];
        const uint32_t base = sb + SM_WMOD + (wid >> 1) * 10240;
#pragma unroll
        for (int ks = 0; ks < 5; ks++) {
            const int r0 = wid * 80 + ks * 16;
            bb[ks][0] = sc32[(r0 >> 1) + j4]; bb[ks][1] = sc32[(r0 >> 1) + 4 + j4];
        }
        mbar_wait(BAR(B_MOD + (wid >> 1)), 0);
#pragma unroll
        for (int ks = 0; ks < 5; ks++) {
            const int r = (wid & 1) * 80 + ks * 16 + l8 + 8 * (mi >> 1);
#pragma unroll
            for (int mt = 0; mt < 2; mt++) ldsm4t(a[ks][mt], base + r * 64 + (((2 * mt + (mi & 1)) ^ ((r >> 1) & 3)) << 4));
        }
#pragma unroll
        for (int ks = 0; ks < 5; ks++) { mma16816(acc[0], a[ks][0], bb[ks][0], bb[ks][1]); mma16816(acc[1], a[ks][1], bb[ks][0], bb[ks][1]); }
        if (j4 == 0) {
#pragma unroll
            for (int mt = 0; mt < 2; mt++) { red[wid * 64 + mt * 16 + g4] = acc[mt][0]; red[wid * 64 + mt * 16 + 8 + g4] = acc[mt][2]; }
        }
        bar_cons();
        if (wid == 0) {
            float v = 0.f;
#pragma unroll
            for (int w = 0; w < 8; w++) v += red[w * 64 + lane];
            float o = __shfl_down_sync(0xffffffffu, v, 1);
            if (!(lane & 1)) st_pk8(&g_mod[cta * 16 + (lane >> 1)], pack_bf(v, o), tag);
        }
    }
    TS(1);

    if (cta < 128) {
        {
            const int off[4] = {tid, 320 + tid, tid < 64 ? 256 + tid : tid, tid < 64 ? 576 + tid : 320 + tid};
            uint32_t val[4];
            poll8<4>(g_mod, off, val, tag);
#pragma unroll
            for (int rep = 0; rep < 2; rep++) {
                int p = tid + rep * 256;
                if (p < 320) {
                    uint32_t sa = val[2 * rep], ca = val[2 * rep + 1];
                    uint32_t xx = x32[p];
                    float n0 = bfr(bfr(bf_lo(xx) - mean_x) * rden_x), n1 = bfr(bfr(bf_hi(xx) - mean_x) * rden_x);
                    float h0 = bfr(n0 * bfr(1.0f + bf_lo(ca))) + bf_lo(sa);
                    float h1 = bfr(n1 * bfr(1.0f + bf_hi(ca))) + bf_hi(sa);
                    h32[p] = pack_bf(h0, h1);
                }
            }
        }
        bar_cons();
        TS(2);
        float acc[3][4] = {};
        uint32_t a[5][3][4], bb[5][2];
#pragma unroll
        for (int ks = 0; ks < 5; ks++) {
            const int r0 = wid * 80 + ks * 16;
            bb[ks][0] = h32[(r0 >> 1) + j4]; bb[ks][1] = h32[(r0 >> 1) + 4 + j4];
        }
        mbar_wait(BAR(B_WQ + ((wid * 80) >> 7)), 0);
        mbar_wait(BAR(B_WQ + ((wid * 80 + 79) >> 7)), 0);
#pragma unroll
        for (int ks = 0; ks < 5; ks++) {
            const int r = wid * 80 + ks * 16 + l8 + 8 * (mi >> 1);
#pragma unroll
            for (int mt = 0; mt < 3; mt++) ldsm4t(a[ks][mt], sb + SM_WQ + r * 96 + ((2 * mt + (mi & 1)) << 4));
        }
#pragma unroll
        for (int ks = 0; ks < 5; ks++) {
#pragma unroll
            for (int mt = 0; mt < 3; mt++) mma16816(acc[mt], a[ks][mt], bb[ks][0], bb[ks][1]);
        }
        if (j4 == 0) {
#pragma unroll
            for (int mt = 0; mt < 3; mt++) { red[wid * 64 + mt * 16 + g4] = acc[mt][0]; red[wid * 64 + mt * 16 + 8 + g4] = acc[mt][2]; }
        }
        bar_cons();
        if (tid < 64) {
            float v = 0.f;
            if (tid < 48) {
#pragma unroll
                for (int w = 0; w < 8; w++) v += red[w * 64 + tid];
            }
            float o = __shfl_down_sync(0xffffffffu, v, 1);
            if (tid < 48 && !(tid & 1)) st_pk8(&g_q[cta * 24 + (tid >> 1)], pack_bf(v, o), tag);
        }
        TS(3);
    }
    {
        int off[5];
#pragma unroll
        for (int j = 0; j < 5; j++) {
            int p = tid + 256 * j;
            if (p >= NQH * 96) p = tid;
            off[j] = p < GH * 96 ? grp * GH * 96 + p : NG * GH * 96 + (p - GH * 96);
        }
        uint32_t val[5];
        poll8<5>(g_q, off, val, tag);
#pragma unroll
        for (int j = 0; j < 5; j++)
            if (tid + 256 * j < NQH * 96) q32[tid + 256 * j] = val[j];
    }
    bar_cons();
    if (tid == 0) mbar_arrive(BAR(B_PRO));
    TS(4);

    bool live = true;
    if (wid < 4) {
        const int pair = wid >> 1, half = wid & 1;
        const int rowK = half * 16 + l8 + 8 * (mi & 1), hiK = mi >> 1;
        const int rowV = half * 16 + l8 + 8 * (mi >> 1), hiV = mi & 1;
        float acc[12][4];
#pragma unroll
        for (int i = 0; i < 12; i++) { acc[i][0] = acc[i][1] = acc[i][2] = acc[i][3] = 0.f; }
        float m_run = NEG_BIG, l_run = 0.f;
        uint32_t qf[12][2];
#pragma unroll
        for (int i = 0; i < 12; i++) { qf[i][0] = qf[i][1] = 0; }
        int cur = -1, flushed = 0, cnt = 0;
        int s = 2 * pair; uint32_t par = 0;
        float* mb = reinterpret_cast<float*>(smem + SM_MERGE) + wid * 200;
        uint32_t ready = 0;
#pragma unroll 1
        while (true) {
            if (!ready) mbar_wait(BAR(B_FULL + s), par);
            const uint32_t mt_ = meta[s];
            const int run = mt_ & 0xff;
            if (mt_ & META_END) CLK(20);
            if (run != cur) {
#pragma unroll 1
                while (flushed < run) {
                    if (flushed != cur) {
#pragma unroll
                        for (int i = 0; i < 12; i++) { acc[i][0] = acc[i][1] = acc[i][2] = acc[i][3] = 0.f; }
                        m_run = NEG_BIG; l_run = 0.f; cnt = 0;
                    }
                    const uint32_t fle = mbar_try(BAR(B_FLE), (flushed & 1) ^ 1);
                    float v[24];
#pragma unroll
                    for (int i = 0; i < 12; i++) { v[2 * i] = acc[i][0] + acc[i][1]; v[2 * i + 1] = acc[i][2] + acc[i][3]; }
                    float u[12], w6[6];
                    const bool o1 = j4 & 1, o2 = j4 & 2;
#pragma unroll
                    for (int i = 0; i < 12; i++) {
                        float send = o1 ? v[i] : v[i + 12], keep = o1 ? v[i + 12] : v[i];
                        u[i] = keep + __shfl_xor_sync(0xffffffffu, send, 1);
                    }
#pragma unroll
                    for (int i = 0; i < 6; i++) {
                        float send = o2 ? u[i] : u[i + 6], keep = o2 ? u[i + 6] : u[i];
                        w6[i] = keep + __shfl_xor_sync(0xffffffffu, send, 2);
                    }
                    float l = l_run;
                    l += __shfl_xor_sync(0xffffffffu, l, 4);
                    l += __shfl_xor_sync(0xffffffffu, l, 8);
                    l += __shfl_xor_sync(0xffffffffu, l, 16);
                    if (!fle) mbar_wait(BAR(B_FLE), (flushed & 1) ^ 1);
#pragma unroll
                    for (int i = 0; i < 6; i++) {
                        int idx = (o1 ? 12 : 0) + (o2 ? 6 : 0) + i;
                        mb[4 + 16 * (idx >> 1) + 8 * (idx & 1) + g4] = w6[i];
                    }
                    if (lane == 0) { mb[0] = m_run; mb[1] = l; mb[2] = __int_as_float(cnt); }
                    __syncwarp();
                    if (lane == 0) mbar_arrive(BAR(B_FLF));
                    flushed++;
                    cur = -1;
                }
                if (mt_ & META_END) {
                    CLK(21);
                    if (flushed == 0 && lane == 0) mbar_arrive(BAR(B_FLF));
                    break;
                }
                cur = run;
                const int qi = (mt_ >> 8) & 0xff;
#pragma unroll
                for (int i = 0; i < 12; i++) { acc[i][0] = acc[i][1] = acc[i][2] = acc[i][3] = 0.f; }
                m_run = NEG_BIG; l_run = 0.f; cnt = 0;
#pragma unroll
                for (int ks = 0; ks < 12; ks++) {
                    qf[ks][0] = q32[qi * 96 + ks * 8 + j4];
                    qf[ks][1] = q32[qi * 96 + ks * 8 + 4 + j4];
                }
            }
            cnt++;
            const uint32_t kb = sb + SM_RING + s * CHUNK;
            float sc[3][4] = {};
            {
                uint32_t a[12][4];
#pragma unroll
                for (int t = 0; t < 3; t++) {
                    const int ln = rowK * 3 + t;
#pragma unroll
                    for (int kk = 0; kk < 4; kk++) ldsm4(a[t * 4 + kk], kb + ln * 128 + (((2 * kk + hiK) ^ (ln & 7)) << 4));
                }
#pragma unroll
                for (int kk = 0; kk < 4; kk++) {
#pragma unroll
                    for (int t = 0; t < 3; t++) mma16816(sc[t], a[t * 4 + kk], qf[t * 4 + kk][0], qf[t * 4 + kk][1]);
                }
            }
            __syncwarp();
            if (lane == 0) mbar_arrive(BAR(B_EMPTY + s));
            int sv = s + 1; uint32_t parv = par;
            if (sv == NSLOT) { sv = 0; parv ^= 1; }
            const float scale = 0.07216878364870322f;
            float s0 = bfr(bfr(sc[0][0] + sc[1][0] + sc[2][0]) * scale);
            float s1 = bfr(bfr(sc[0][2] + sc[1][2] + sc[2][2]) * scale);
            float tm = fmaxf(s0, s1);
            tm = fmaxf(tm, __shfl_xor_sync(0xffffffffu, tm, 4));
            tm = fmaxf(tm, __shfl_xor_sync(0xffffffffu, tm, 8));
            tm = fmaxf(tm, __shfl_xor_sync(0xffffffffu, tm, 16));
            if (tm > m_run) {
                float alpha = ex2((m_run - tm) * LOG2E);
                l_run *= alpha;
#pragma unroll
                for (int i = 0; i < 12; i++) { acc[i][0] *= alpha; acc[i][1] *= alpha; acc[i][2] *= alpha; acc[i][3] *= alpha; }
                m_run = tm;
            }
            float p0 = ex2((s0 - m_run) * LOG2E);
            float p1 = ex2((s1 - m_run) * LOG2E);
            l_run += p0 + p1;
            uint32_t b0 = 0, b1 = 0;
            if (j4 == (g4 >> 1)) {
                uint32_t e0 = pack_bf(p0, 0.f) & 0xffffu, e1 = pack_bf(p1, 0.f) & 0xffffu;
                b0 = (g4 & 1) ? (e0 << 16) : e0;
                b1 = (g4 & 1) ? (e1 << 16) : e1;
            }
            mbar_wait(BAR(B_FULL + sv), parv);
            s += 4;
            if (s >= NSLOT) { s -= NSLOT; par ^= 1; }
            ready = mbar_try(BAR(B_FULL + s), par);
            const uint32_t vb = sb + SM_RING + sv * CHUNK;
            {
                uint32_t a[12][4];
#pragma unroll
                for (int t = 0; t < 3; t++) {
                    const int ln = rowV * 3 + t;
#pragma unroll
                    for (int kk = 0; kk < 4; kk++) ldsm4t(a[t * 4 + kk], vb + ln * 128 + (((2 * kk + hiV) ^ (ln & 7)) << 4));
                }
#pragma unroll
                for (int i = 0; i < 12; i++) mma16816(acc[i], a[i], b0, b1);
            }
            __syncwarp();
            if (lane == 0) mbar_arrive(BAR(B_EMPTY + sv));
        }
        TS(7);
        CLK(18);
    } else if (wid == 4) {
        const float* mb = reinterpret_cast<const float*>(smem + SM_MERGE);
#pragma unroll 1
        for (int f = 0;; f++) {
            mbar_wait(BAR(B_FLF), f & 1);
            const int head = (int)meta[16 + f];
            if (head == 0xFF) break;
            float m0 = mb[0], m1 = mb[200], m2 = mb[400], m3 = mb[600];
            float M = fmaxf(fmaxf(m0, m1), fmaxf(m2, m3));
            float w0 = ex2((m0 - M) * LOG2E), w1 = ex2((m1 - M) * LOG2E);
            float w2 = ex2((m2 - M) * LOG2E), w3 = ex2((m3 - M) * LOG2E);
            const int idx = head < NG * GH ? rank : cta;
            uint4* dst = &g_dat[head][idx][0];
            float o[6];
#pragma unroll
            for (int i = 0; i < 6; i++) {
                int d = 4 + (i < 3 ? 3 * lane + i : 96 + 3 * lane + (i - 3));
                o[i] = w0 * mb[d] + w1 * mb[200 + d] + w2 * mb[400 + d] + w3 * mb[600 + d];
            }
            float L = w0 * mb[1] + w1 * mb[201] + w2 * mb[401] + w3 * mb[601];
            const uint32_t tiles = __float_as_int(mb[2]) + __float_as_int(mb[402]);
            st_pk16(dst + lane, __float_as_uint(o[0]), __float_as_uint(o[1]), __float_as_uint(o[2]), tag);
            st_pk16(dst + 32 + lane, __float_as_uint(o[3]), __float_as_uint(o[4]), __float_as_uint(o[5]), tag);
            if (lane == 0) st_pk16(&g_hdr[head][idx], __float_as_uint(M), __float_as_uint(L), tiles, tag);
            __syncwarp();
            if (lane == 0) mbar_arrive(BAR(B_FLE));
            if (meta[16 + f + 1] == 0xFFu) break;
        }
        TS(8);
        CLK(18);
    } else if (wid >= 6) {
        if (cta < 128) {
            const int t = tid - 192;
            uint32_t* cb32 = reinterpret_cast<uint32_t*>(smem + SM_CB);
            uint32_t* sb32 = reinterpret_cast<uint32_t*>(smem + SM_SB);
            const int col = cta * 5 + t;
            int off[12];
            uint32_t val[12];
#pragma unroll
            for (int rep = 0; rep < 5; rep++) { off[2 * rep] = 960 + t + 64 * rep; off[2 * rep + 1] = 1280 + t + 64 * rep; }
            off[10] = t < 5 ? (1280 + col) >> 1 : 960;
            off[11] = t < 5 ? (3200 + col) >> 1 : 960;
            poll8<12>(g_mod, off, val, tag);
#pragma unroll
            for (int rep = 0; rep < 5; rep++) {
                sb32[t + 64 * rep] = val[2 * rep];
                cb32[t + 64 * rep] = pack_bf(1.0f + bf_lo(val[2 * rep + 1]), 1.0f + bf_hi(val[2 * rep + 1]));
            }
            if (t < 5) {
                own[t] = (col & 1) ? bf_hi(val[10]) : bf_lo(val[10]);
                own[8 + t] = (col & 1) ? bf_hi(val[11]) : bf_lo(val[11]);
                uint32_t xx = x32[col >> 1];
                own[16 + t] = (col & 1) ? bf_hi(xx) : bf_lo(xx);
            }
        }
        live = false;
    }
    const uint32_t sb0 = sb;
    const int tid0 = tid;
#pragma unroll 1
    while (cta < 128) {
        uint32_t sb = sb0; int tid = tid0;
        asm volatile("" : "+r"(sb), "+r"(tid));
        const int wid = tid >> 5, lane = tid & 31;
        const int g4 = lane >> 2, j4 = lane & 3, mi = lane >> 3, l8 = lane & 7;
        CLK(19);
        if (wid >= 5) {
            const int h = cta >> 2, js = cta & 3;
            const bool gl = h >= NG * GH;
            const int ncand = gl ? G : (G - h / GH + NG - 1) / NG;
            const int k = lane & 15, rr = (wid - 5) * 2 + (lane >> 4);
            if (live) {
                const unsigned* cp = &g_ctr[(tag - 1) & 1][(gl ? NG : h / GH) * 32];
                const unsigned thr = ((gl ? h - NG * GH : h % GH) + 1) * TPH;
                uint32_t it = 0;
                while (true) {
                    unsigned v;
                    asm volatile("ld.relaxed.gpu.global.u32 %0, [%1];" : "=r"(v) : "l"(cp) : "memory");
                    if (v >= thr) break;
                    __nanosleep(300);
                    if (++it > SPIN_LIMIT) __trap();
                }
            }
            const uint4* hdr = &g_hdr[h][lane];
            const uint4* dat = &g_dat[h][rr][16 * js + k];
            float* part = stage;
            float L, a0, a1, a2;
            uint32_t it = 0;
            uint4 hd[5], dv[MAXG / 6];
#pragma unroll
            for (int i = 0; i < 5; i++) hd[i] = make_uint4(0, 0, 0, 0);
#pragma unroll
            for (int i = 0; i < MAXG / 6; i++) dv[i] = make_uint4(0, 0, 0, 0);
#pragma unroll 1
            while (true) {
                FreshN<5, 32>::run(hd, hdr, tag, live, lane, 32, ncand);
                FreshN<MAXG / 6, 6 * 64>::run(dv, dat, tag, live, rr, 6, ncand);
                float w[5], M = NEG_BIG;
                int c = 0;
#pragma unroll
                for (int i = 0; i < 5; i++) {
                    const bool v = hd[i].w == tag;
                    w[i] = v ? __uint_as_float(hd[i].x) : NEG_BIG;
                    M = fmaxf(M, w[i]);
                    c += v ? (int)hd[i].z : 0;
                }
                c = __reduce_add_sync(0xffffffffu, c);
                if (++it > SPIN_LIMIT) __trap();
                if (live && c != TPH) continue;
                CLK(1);
#pragma unroll
                for (int o = 16; o > 0; o >>= 1) M = fmaxf(M, __shfl_xor_sync(0xffffffffu, M, o));
                float ls = 0.f;
#pragma unroll
                for (int i = 0; i < 5; i++) {
                    const bool v = w[i] != NEG_BIG;
                    const float e = ex2((w[i] - M) * LOG2E);
                    w[i] = v ? e : -1.0f;
                    if (v) ls = fmaf(e, __uint_as_float(hd[i].y), ls);
                }
                bool bad = false;
                a0 = a1 = a2 = 0.f;
#pragma unroll
                for (int i = 0; i < MAXG / 6; i++) {
                    const int r = rr + 6 * i;
                    float wi = __shfl_sync(0xffffffffu, w[(6 * i) >> 5], r);
                    if ((((6 * i) >> 5) != ((6 * i + 5) >> 5))) {
                        const float wj = __shfl_sync(0xffffffffu, w[((6 * i + 5) >> 5) < 5 ? ((6 * i + 5) >> 5) : 4], r);
                        if ((r >> 5) != ((6 * i) >> 5)) wi = wj;
                    }
                    if (wi >= 0.f) {
                        bad = bad || dv[i].w != tag;
                        a0 = fmaf(wi, __uint_as_float(dv[i].x), a0);
                        a1 = fmaf(wi, __uint_as_float(dv[i].y), a1);
                        a2 = fmaf(wi, __uint_as_float(dv[i].z), a2);
                    }
                }
                L = warp_sum(ls);
                if (!__any_sync(0xffffffffu, bad) || !live) break;
            }
            a0 += __shfl_xor_sync(0xffffffffu, a0, 16);
            a1 += __shfl_xor_sync(0xffffffffu, a1, 16);
            a2 += __shfl_xor_sync(0xffffffffu, a2, 16);
            CLK(2);
            if (live && lane < 16) { float* pp = part + (wid - 5) * 48 + 3 * k; pp[0] = a0; pp[1] = a1; pp[2] = a2; }
            if (live) asm volatile("bar.sync 2, 96;" ::: "memory");
            if (wid == 5 || !live) {
                uint16_t* osw = reinterpret_cast<uint16_t*>(smem + SM_SC);
                const float inv = __fdividef(1.0f, L);
                const float o0 = (part[lane] + part[48 + lane]) + part[96 + lane];
                const float o1 = (part[32 + (lane & 15)] + part[80 + (lane & 15)]) + part[128 + (lane & 15)];
                if (live) { osw[lane] = (uint16_t)(__float_as_uint(bfr(o0 * inv)) >> 16); if (lane < 16) osw[32 + lane] = (uint16_t)(__float_as_uint(bfr(o1 * inv)) >> 16); }
            }
            if (live) TS(10);
        }
        if (wid < 5 || !live) {
            const int w5 = wid < 5 ? wid : wid - 5;
            uint32_t wa[8][3][4];
            if (live) mbar_wait(BAR(B_WO + w5), 0);
#pragma unroll
            for (int i = 0; i < 8; i++) {
                const int cc = 2 * (i & 3) + (mi & 1);
#pragma unroll
                for (int ks = 0; ks < 3; ks++) {
                    const int r = ks * 16 + l8 + 8 * (mi >> 1);
                    ldsm4t(wa[i][ks], sb + SM_WO + (2 * w5 + (i >> 2)) * 6144 + r * 128 + ((cc ^ (r & 7)) << 4));
                }
            }
            if (live) bar_cons();
            if (live) TS(9);
            CLK(3);
            const uint32_t* os32 = reinterpret_cast<const uint32_t*>(smem + SM_SC);
            float acc[8][4] = {};
#pragma unroll
            for (int ks = 0; ks < 3; ks++) {
                const uint32_t b0 = os32[ks * 8 + j4], b1 = os32[ks * 8 + 4 + j4];
#pragma unroll
                for (int i = 0; i < 8; i++) mma16816(acc[i], wa[i][ks], b0, b1);
            }
            if (live && j4 == 0) {
#pragma unroll
                for (int i = 0; i < 8; i++) { stage[(w5 * 8 + i) * 16 + g4] = acc[i][0]; stage[(w5 * 8 + i) * 16 + 8 + g4] = acc[i][2]; }
            }
        } else {
            bar_cons();
        }
        CLK(4);
        if (live) bar_cons();
        {
            const int o = tid >> 1, kk = tid & 1;
            const float* sp = stage + o * 5 + kk * 3;
            float v0 = sp[0], v1 = sp[1], v2 = kk ? 0.f : sp[2];
            if (live) st_pk16(&g_h1[o][cta][kk], __float_as_uint(v0), __float_as_uint(v1), __float_as_uint(v2), tag);
        }
        if (live) TS(11);
        CLK(5);
        if (wid == 0 || !live) {
            const uint4* p = &g_h1[cta][0][0] + lane;
            uint4 v[8];
            uint32_t it = 0;
            while (true) {
                bool ok = true;
                LoadN<8, 32>::run(v, p, live, 0, 0, 1);
#pragma unroll
                for (int j = 0; j < 8; j++) ok = ok && v[j].w == tag;
                if (__all_sync(0xffffffffu, ok) || !live) break;
                if (++it > SPIN_LIMIT) __trap();
            }
            CLK(6);
            float a0 = 0.f, a1 = 0.f, a2 = 0.f;
#pragma unroll
            for (int j = 0; j < 8; j++) { a0 += __uint_as_float(v[j].x); a1 += __uint_as_float(v[j].y); a2 += __uint_as_float(v[j].z); }
#pragma unroll
            for (int o = 2; o <= 16; o <<= 1) {
                a0 += __shfl_xor_sync(0xffffffffu, a0, o);
                a1 += __shfl_xor_sync(0xffffffffu, a1, o);
                a2 += __shfl_xor_sync(0xffffffffu, a2, o);
            }
            const float gx = own[lane & 7], xx = own[16 + (lane & 7)];
            const float t0 = __shfl_sync(0xffffffffu, a0, lane >= 3), t1 = __shfl_sync(0xffffffffu, a1, lane >= 3);
            const float sum = (lane == 0 || lane == 3) ? t0 : (lane == 2 ? a2 : t1);
            const float x2 = bfr(xx + bfr(gx * bfr(sum)));
            if (live && lane < 5) own[24 + lane] = x2;
            const float y1 = __shfl_sync(0xffffffffu, x2, 1), y2 = __shfl_sync(0xffffffffu, x2, 2);
            const float y3 = __shfl_sync(0xffffffffu, x2, 3), y4 = __shfl_sync(0xffffffffu, x2, 4);
            if (live && lane == 0) st_pk16(&g_x2[cta][0], pack_bf(x2, y1), pack_bf(y2, y3), pack_bf(y4, 0.f), tag);
            if (live) TS(13);
        }
        CLK(8);
        if (cta < 96) {
            uint32_t a1[5][4], a3[5][4], a2[5][4];
            if (live) mbar_wait3(BAR(B_W1 + (wid >> 2)), BAR(B_W3 + (wid >> 2)), BAR(B_W2 + (wid >> 2)));
            const uint32_t w2b = sb + SM_RING + meta[10 + (wid >> 2)] % NSLOT * CHUNK;
#pragma unroll
            for (int ks = 0; ks < 5; ks++) {
                const int r = wid * 80 + ks * 16 + l8 + 8 * (mi >> 1);
                const uint32_t off = r * 32 + (((mi & 1) ^ ((r >> 2) & 1)) << 4);
                ldsm4t(a1[ks], sb + SM_W1 + off);
                ldsm4t(a3[ks], sb + SM_W3 + off);
            }
#pragma unroll
            for (int i = 0; i < 5; i++) {
                const int mt = (wid & 3) * 5 + i;
                const int cc = 2 * (mt & 3) + (mi & 1);
                const int r = l8 + 8 * (mi >> 1);
                ldsm4t(a2[i], w2b + (mt >> 2) * 2048 + r * 128 + ((cc ^ (r & 7)) << 4));
            }
            CLK(9);
            float* x2s = reinterpret_cast<float*>(smem + SM_X2);
            float* st8 = red + 256;
            if (wid >= 4) {
                uint4 v = poll16(&g_x2[tid - 128][0], tag, live);
                const float e0 = bf_lo(v.x), e1 = bf_hi(v.x), e2 = bf_lo(v.y), e3 = bf_hi(v.y), e4 = bf_lo(v.z);
                float* d = x2s + (tid - 128) * 5;
                if (live) { d[0] = e0; d[1] = e1; d[2] = e2; d[3] = e3; d[4] = e4; }
                const float pv = __shfl_sync(0xffffffffu, e0, 0);
                const float d0 = e0 - pv, d1 = e1 - pv, d2 = e2 - pv, d3 = e3 - pv, d4 = e4 - pv;
                float s1 = ((d0 + d1) + (d2 + d3)) + d4;
                float s2 = fmaf(d0, d0, fmaf(d1, d1, fmaf(d2, d2, fmaf(d3, d3, d4 * d4))));
#pragma unroll
                for (int o = 16; o > 0; o >>= 1) { s1 += __shfl_xor_sync(0xffffffffu, s1, o); s2 += __shfl_xor_sync(0xffffffffu, s2, o); }
                if (live && lane == 0) { st8[2 * (wid - 4)] = pv + s1 * (1.0f / 160.0f); st8[2 * (wid - 4) + 1] = s2 - s1 * s1 * (1.0f / 160.0f); }
            }
            if (live) bar_cons();
            if (live) TS(14);
            CLK(10);
            const float4 sA = *reinterpret_cast<const float4*>(st8), sB = *reinterpret_cast<const float4*>(st8 + 4);
            const float mean = ((sA.x + sA.z) + (sB.x + sB.z)) * 0.25f;
            const float u0 = sA.x - mean, u1 = sA.z - mean, u2 = sB.x - mean, u3 = sB.z - mean;
            const float m2 = ((sA.y + sA.w) + (sB.y + sB.w)) + 160.0f * ((u0 * u0 + u1 * u1) + (u2 * u2 + u3 * u3));
            const float mean_b = bfr(mean);
            const float rden = __fdividef(1.0f, bfr(fsqrt(bfr(bfr(m2 * (1.0f / 640.0f)) + 1e-5f))));
            const uint32_t* cb32 = reinterpret_cast<const uint32_t*>(smem + SM_CB);
            const uint32_t* sb32 = reinterpret_cast<const uint32_t*>(smem + SM_SB);
#pragma unroll
            for (int rep = 0; rep < 2; rep++) {
                const int p = lane + 32 * rep;
                if (p < 40) {
                    int pp = wid * 40 + p;
                    const float2 xv = *reinterpret_cast<const float2*>(x2s + 2 * pp);
                    uint32_t cv = cb32[pp], sv = sb32[pp];
                    float n0 = bfr(bfr(xv.x - mean_b) * rden), n1 = bfr(bfr(xv.y - mean_b) * rden);
                    uint32_t hv = pack_bf(bfr(n0 * bf_lo(cv)) + bf_lo(sv), bfr(n1 * bf_hi(cv)) + bf_hi(sv));
                    if (live) h32[pp] = hv;
                }
            }
            __syncwarp();
            CLK(11);
            float ag[2][4] = {}, au[2][4] = {};
#pragma unroll
            for (int ks = 0; ks < 5; ks++) {
                const int r0 = wid * 80 + ks * 16;
                const uint32_t b0 = h32[(r0 >> 1) + j4], b1 = h32[(r0 >> 1) + 4 + j4];
                mma16816(ag[ks & 1], a1[ks], b0, b1);
                mma16816(au[ks & 1], a3[ks], b0, b1);
            }
            if (live && j4 == 0) {
                red[wid * 32 + g4] = ag[0][0] + ag[1][0]; red[wid * 32 + 8 + g4] = ag[0][2] + ag[1][2];
                red[wid * 32 + 16 + g4] = au[0][0] + au[1][0]; red[wid * 32 + 24 + g4] = au[0][2] + au[1][2];
            }
            CLK(12);
            if (live) bar_cons();
            if (live) TS(15);
            CLK(13);
            float v = 0.f;
#pragma unroll
            for (int w = 0; w < 8; w++) v += red[w * 32 + lane];
            v = bfr(v);
            float up = __shfl_down_sync(0xffffffffu, v, 16);
            float hact = bfr(bfr(silu(v)) * up);
            float e0 = __shfl_sync(0xffffffffu, hact, 2 * j4), e1 = __shfl_sync(0xffffffffu, hact, 2 * j4 + 1);
            float e2 = __shfl_sync(0xffffffffu, hact, 2 * j4 + 8), e3 = __shfl_sync(0xffffffffu, hact, 2 * j4 + 9);
            const uint32_t b0 = pack_bf(e0, e1), b1 = pack_bf(e2, e3);
            float acc[5][4] = {};
#pragma unroll
            for (int i = 0; i < 5; i++) mma16816(acc[i], a2[i], b0, b1);
            if (live && j4 == 0) {
#pragma unroll
                for (int i = 0; i < 5; i++) { stage[(wid * 5 + i) * 16 + g4] = acc[i][0]; stage[(wid * 5 + i) * 16 + 8 + g4] = acc[i][2]; }
            }
            CLK(14);
            if (live) bar_cons();
            const int o = tid >> 1, k = tid & 1;
            const float* sp = stage + o * 5 + k * 3;
            float v0 = sp[0], v1 = sp[1], v2 = k ? 0.f : sp[2];
            if (live) st_pk16(&g_h3[o][cta][k], __float_as_uint(v0), __float_as_uint(v1), __float_as_uint(v2), tag);
        }
        if (live) TS(16);
        CLK(15);
        if (wid == 0 || !live) {
            const uint4* p = &g_h3[cta][0][0] + lane;
            uint4 v[6];
            uint32_t it = 0;
            if (live && cta < 96) spin(P_DLY);
            while (true) {
                bool ok = true;
                LoadN<6, 32>::run(v, p, live, 0, 0, 1);
#pragma unroll
                for (int j = 0; j < 6; j++) ok = ok && v[j].w == tag;
                if (__all_sync(0xffffffffu, ok) || !live) break;
                if (++it > SPIN_LIMIT) __trap();
            }
            CLK(16);
            float a0 = 0.f, a1 = 0.f, a2 = 0.f;
#pragma unroll
            for (int j = 0; j < 6; j++) { a0 += __uint_as_float(v[j].x); a1 += __uint_as_float(v[j].y); a2 += __uint_as_float(v[j].z); }
#pragma unroll
            for (int o = 2; o <= 16; o <<= 1) {
                a0 += __shfl_xor_sync(0xffffffffu, a0, o);
                a1 += __shfl_xor_sync(0xffffffffu, a1, o);
                a2 += __shfl_xor_sync(0xffffffffu, a2, o);
            }
            const float gx = own[8 + (lane & 7)], xx = own[24 + (lane & 7)];
            const float t0 = __shfl_sync(0xffffffffu, a0, lane >= 3), t1 = __shfl_sync(0xffffffffu, a1, lane >= 3);
            const float sum = (lane == 0 || lane == 3) ? t0 : (lane == 2 ? a2 : t1);
            const float y = xx + bfr(gx * bfr(sum));
            if (live && lane < 5) reinterpret_cast<uint16_t*>(out)[cta * 5 + lane] = (uint16_t)(__float_as_uint(bfr(y)) >> 16);
            if (live && cta == 0 && lane == 0) g_epoch = tag;
        }
        CLK(17);
        if (live) { TS(18); break; }
        live = true;
    }
    }
}

typedef CUresult (*EncodeFn)(CUtensorMap*, CUtensorMapDataType, cuuint32_t, void*, const cuuint64_t*, const cuuint64_t*,
                             const cuuint32_t*, const cuuint32_t*, CUtensorMapInterleave, CUtensorMapSwizzle,
                             CUtensorMapL2promotion, CUtensorMapFloatOOBfill);

void make_map(EncodeFn enc, CUtensorMap* tm, const void* ptr, uint64_t cols, uint64_t rows, uint32_t box_c, uint32_t box_r,
              CUtensorMapSwizzle sw, CUtensorMapL2promotion prom) {
    cuuint64_t dims[2] = {cols, rows};
    cuuint64_t strides[1] = {cols * 2};
    cuuint32_t box[2] = {box_c, box_r};
    cuuint32_t es[2] = {1, 1};
    enc(tm, CU_TENSOR_MAP_DATA_TYPE_BFLOAT16, 2, const_cast<void*>(ptr), dims, strides, box, es,
        CU_TENSOR_MAP_INTERLEAVE_NONE, sw, prom, CU_TENSOR_MAP_FLOAT_OOB_FILL_NONE);
}

}

extern "C" void kernel_launch(void* const* d_in, const int* in_sizes, int n_in, void* d_out, int out_size) {
    (void)in_sizes; (void)n_in; (void)out_size;
    static EncodeFn enc = nullptr;
    static int num_sms = 0;
    if (!enc) {
        void* fn = nullptr;
        cudaDriverEntryPointQueryResult qr;
        cudaGetDriverEntryPoint("cuTensorMapEncodeTiled", &fn, cudaEnableDefault, &qr);
        enc = (EncodeFn)fn;
        cudaDeviceGetAttribute(&num_sms, cudaDevAttrMultiProcessorCount, 0);
        cudaFuncSetAttribute(fused_decode_kernel, cudaFuncAttributeMaxDynamicSharedMemorySize, SM_TOTAL);
    }
    CUtensorMap tmK, tmV, tmMod, tmWq, tmWo, tmW1, tmW3, tmW2;
    const uint64_t kv_lines = (uint64_t)NH * SK * 3;
    make_map(enc, &tmK, d_in[1], 64, kv_lines, 64, 96, CU_TENSOR_MAP_SWIZZLE_128B, CU_TENSOR_MAP_L2_PROMOTION_L2_128B);
    make_map(enc, &tmV, d_in[2], 64, kv_lines, 64, 96, CU_TENSOR_MAP_SWIZZLE_128B, CU_TENSOR_MAP_L2_PROMOTION_L2_128B);
    make_map(enc, &tmWq, d_in[3], NH * DH, D, 48, 128, CU_TENSOR_MAP_SWIZZLE_NONE, CU_TENSOR_MAP_L2_PROMOTION_L2_128B);
    make_map(enc, &tmWo, d_in[4], D, NH * DH, 64, 48, CU_TENSOR_MAP_SWIZZLE_128B, CU_TENSOR_MAP_L2_PROMOTION_L2_128B);
    make_map(enc, &tmW1, d_in[6], FF, D, 16, 160, CU_TENSOR_MAP_SWIZZLE_32B, CU_TENSOR_MAP_L2_PROMOTION_L2_128B);
    make_map(enc, &tmW3, d_in[7], FF, D, 16, 160, CU_TENSOR_MAP_SWIZZLE_32B, CU_TENSOR_MAP_L2_PROMOTION_L2_128B);
    make_map(enc, &tmW2, d_in[8], D, FF, 64, 16, CU_TENSOR_MAP_SWIZZLE_128B, CU_TENSOR_MAP_L2_PROMOTION_L2_128B);
    make_map(enc, &tmMod, d_in[10], 6 * D, D, 32, 160, CU_TENSOR_MAP_SWIZZLE_64B, CU_TENSOR_MAP_L2_PROMOTION_L2_128B);
    int grid = num_sms < MAXG ? num_sms : MAXG;
    fused_decode_kernel<<<grid, NTHREADS, SM_TOTAL, cudaStreamPerThread>>>(
        tmK, tmV, tmMod, tmWq, tmWo, tmW1, tmW3, tmW2, (const __nv_bfloat16*)d_in[0], (const __nv_bfloat16*)d_in[9],
        (__nv_bfloat16*)d_out);
}
```

```cpp
#include <cuda_runtime.h>
#include <cuda_bf16.h>
#include <cuda.h>
#include <stdint.h>

namespace {

constexpr int D = 640, NH = 32, SK = 8192, DH = 192, FF = 1536;
constexpr int NG = 4;
constexpr int GH = 7;
constexpr int NGLOB = NH - NG * GH;
constexpr int NQH = GH + NGLOB;
constexpr int TILE = 32;
constexpr int TPH = SK / TILE;
constexpr int GT = GH * TPH;
constexpr int PT = NGLOB * TPH;
constexpr int CHUNK = TILE * DH * 2;
#define P_NSLOT 8
#define P_WIN 3
#define P_URG 132
#define P_HOLD 0
#define P_DLY 450
constexpr int NSLOT = P_NSLOT;
constexpr int WIN = P_WIN;
constexpr int MAXG = 132;
constexpr int NTHREADS = 288;
constexpr float NEG_BIG = -3.402823466e38f;

constexpr int SM_WMOD = 0;
constexpr int SM_WQ = 40960;
constexpr int SM_WO = 0;
constexpr int SM_W1 = 61440;
constexpr int SM_W3 = 81920;
constexpr int SM_RING = 102400;
constexpr int SM_MISC = SM_RING + NSLOT * CHUNK;
constexpr int SM_BARS = SM_MISC;
constexpr int SM_META = SM_BARS + 512;
constexpr int SM_Q = SM_META + 128;
constexpr int SM_SC = SM_Q + NQH * DH * 2;
constexpr int SM_H = SM_SC + 1280;
constexpr int SM_X = SM_H + 1280;
constexpr int SM_CB = SM_X + 1280;
constexpr int SM_SB = SM_CB + 1280;
constexpr int SM_OWN = SM_SB + 1280;
constexpr int SM_RED = SM_OWN + 128;
constexpr int SM_MERGE = SM_RED + 2048;
constexpr int SM_STAGE = SM_MERGE + 3200;
constexpr int SM_X2 = SM_STAGE + 2560;
constexpr int SM_FIN = SM_X2 + 2560;
constexpr int SM_TOTAL = SM_FIN + 256;
static_assert(SM_TOTAL <= 232448, "shared memory budget");

constexpr int B_FULL = 0;
constexpr int B_EMPTY = 8;
constexpr int B_MOD = 16;
constexpr int B_WQ = 20;
constexpr int B_WO = 25;
constexpr int B_W1 = 30;
constexpr int B_W3 = 32;
constexpr int B_W2 = 34;
constexpr int B_FLF = 36, B_FLE = 37, B_PRO = 38, B_DUMMY = 39;
static_assert(NSLOT <= 8 && NSLOT >= 6 && WIN <= 4 && WIN <= NSLOT - 3, "barrier map / end markers vs window");
constexpr uint32_t META_END = 0x10000u;

__device__ unsigned g_epoch;
__device__ unsigned g_ctr[2][(NG + 1) * 32];
__device__ __align__(128) unsigned long long g_mod[1920];
__device__ __align__(128) unsigned long long g_q[3072];
__device__ __align__(128) uint4 g_hdr[NH][MAXG];
__device__ __align__(128) uint4 g_dat[NH][MAXG][64];
__device__ __align__(128) uint4 g_h1[128][128][2];
__device__ __align__(128) uint4 g_x2[128][2];
__device__ __align__(128) uint4 g_h3[128][96][2];

#define TS(k) do {} while (0)
#define DBG(k) do {} while (0)
#define CLK(k) do {} while (0)

__device__ __forceinline__ uint32_t smem_u32(const void* p) { return (uint32_t)__cvta_generic_to_shared(p); }
__device__ __forceinline__ void mbar_init(uint32_t bar, uint32_t cnt) {
    asm volatile("mbarrier.init.shared::cta.b64 [%0], %1;" ::"r"(bar), "r"(cnt) : "memory");
}
__device__ __forceinline__ void mbar_expect_tx(uint32_t bar, uint32_t bytes) {
    asm volatile("mbarrier.arrive.expect_tx.shared::cta.b64 _, [%0], %1;" ::"r"(bar), "r"(bytes) : "memory");
}
__device__ __forceinline__ void mbar_arrive(uint32_t bar) {
    asm volatile("mbarrier.arrive.shared::cta.b64 _, [%0];" ::"r"(bar) : "memory");
}
constexpr uint32_t SPIN_LIMIT = 1u << 22;
__device__ __forceinline__ void mbar_wait(uint32_t bar, uint32_t parity) {
    asm volatile(
        "{\n.reg .pred p;\n.reg .u32 c;\nmov.u32 c, 0;\n"
        "LW:\nmbarrier.try_wait.parity.shared::cta.b64 p, [%0], %1;\n@p bra LD;\n"
        "add.u32 c, c, 1;\nsetp.lt.u32 p, c, 0x400000;\n@p bra LW;\ntrap;\nLD:\n}" ::"r"(bar), "r"(parity)
        : "memory");
}
__device__ __forceinline__ uint32_t mbar_try(uint32_t bar, uint32_t parity) {
    uint32_t ok;
    asm volatile("{\n.reg .pred p;\nmbarrier.try_wait.parity.shared::cta.b64 p, [%1], %2;\nselp.u32 %0, 1, 0, p;\n}"
                 : "=r"(ok) : "r"(bar), "r"(parity) : "memory");
    return ok;
}
__device__ __forceinline__ void mbar_wait3(uint32_t b0, uint32_t b1, uint32_t b2) {
    asm volatile(
        "{\n.reg .pred p, q, r;\n.reg .u32 c;\nmov.u32 c, 0;\n"
        "LW:\nmbarrier.try_wait.parity.shared::cta.b64 p, [%0], 0;\n"
        "mbarrier.try_wait.parity.shared::cta.b64 q, [%1], 0;\n"
        "mbarrier.try_wait.parity.shared::cta.b64 r, [%2], 0;\n"
        "and.pred p, p, q;\nand.pred p, p, r;\n@p bra LD;\n"
        "add.u32 c, c, 1;\nsetp.lt.u32 p, c, 0x400000;\n@p bra LW;\ntrap;\nLD:\n}" ::"r"(b0), "r"(b1), "r"(b2)
        : "memory");
}
__device__ __forceinline__ void tma2d(uint32_t dst, const CUtensorMap* tm, int c0, int c1, uint32_t bar) {
    asm volatile(
        "cp.async.bulk.tensor.2d.shared::cluster.global.mbarrier::complete_tx::bytes [%0], [%1, {%3, %4}], [%2];" ::"r"(dst),
        "l"(tm), "r"(bar), "r"(c0), "r"(c1)
        : "memory");
}
__device__ __forceinline__ void tma2d_hint(uint32_t dst, const CUtensorMap* tm, int c0, int c1, uint32_t bar, uint64_t pol) {
    asm volatile(
        "cp.async.bulk.tensor.2d.shared::cluster.global.mbarrier::complete_tx::bytes.L2::cache_hint [%0], [%1, {%3, %4}], [%2], %5;" ::"r"(dst),
        "l"(tm), "r"(bar), "r"(c0), "r"(c1), "l"(pol)
        : "memory");
}
__device__ __forceinline__ void prefetch_tm(const CUtensorMap* tm) {
    asm volatile("prefetch.tensormap [%0];" ::"l"(tm) : "memory");
}
__device__ __forceinline__ void ldsm4(uint32_t (&r)[4], uint32_t addr) {
    asm volatile("ldmatrix.sync.aligned.m8n8.x4.shared.b16 {%0,%1,%2,%3}, [%4];"
                 : "=r"(r[0]), "=r"(r[1]), "=r"(r[2]), "=r"(r[3])
                 : "r"(addr));
}
__device__ __forceinline__ void ldsm4t(uint32_t (&r)[4], uint32_t addr) {
    asm volatile("ldmatrix.sync.aligned.m8n8.x4.trans.shared.b16 {%0,%1,%2,%3}, [%4];"
                 : "=r"(r[0]), "=r"(r[1]), "=r"(r[2]), "=r"(r[3])
                 : "r"(addr));
}
__device__ __forceinline__ void mma16816(float (&d)[4], const uint32_t (&a)[4], uint32_t b0, uint32_t b1) {
    asm volatile(
        "mma.sync.aligned.m16n8k16.row.col.f32.bf16.bf16.f32 {%0,%1,%2,%3}, {%4,%5,%6,%7}, {%8,%9}, {%0,%1,%2,%3};"
        : "+f"(d[0]), "+f"(d[1]), "+f"(d[2]), "+f"(d[3])
        : "r"(a[0]), "r"(a[1]), "r"(a[2]), "r"(a[3]), "r"(b0), "r"(b1));
}
__device__ __forceinline__ void bar_cons() { asm volatile("bar.sync 1, 256;" ::: "memory"); }
__device__ __forceinline__ void spin(int cycles) {
    long long t0 = clock64();
    while (clock64() - t0 < cycles) {}
}

__device__ __forceinline__ float bfr(float x) {
    uint32_t r;
    asm("cvt.rn.bf16x2.f32 %0, %1, %2;" : "=r"(r) : "f"(x), "f"(0.0f));
    return __uint_as_float(r);
}
__device__ __forceinline__ uint32_t pack_bf(float lo, float hi) {
    __nv_bfloat162 t = __floats2bfloat162_rn(lo, hi);
    return *reinterpret_cast<uint32_t*>(&t);
}
__device__ __forceinline__ float bf_lo(uint32_t v) { return __uint_as_float(v << 16); }
__device__ __forceinline__ float bf_hi(uint32_t v) { return __uint_as_float(v & 0xffff0000u); }

__device__ __forceinline__ void st_pk8(unsigned long long* p, uint32_t v, uint32_t tag) {
    unsigned long long w = ((unsigned long long)tag << 32) | v;
    asm volatile("st.relaxed.gpu.global.b64 [%0], %1;" ::"l"(p), "l"(w) : "memory");
}
__device__ __forceinline__ unsigned long long ld_raw8(const unsigned long long* p) {
    unsigned long long w;
    asm volatile("ld.relaxed.gpu.global.b64 %0, [%1];" : "=l"(w) : "l"(p) : "memory");
    return w;
}
template <int N>
__device__ __forceinline__ void poll8(const unsigned long long* base, const int (&off)[N], uint32_t (&val)[N], uint32_t tag) {
    uint32_t it = 0;
    while (true) {
        unsigned long long w[N];
#pragma unroll
        for (int i = 0; i < N; i++) w[i] = ld_raw8(base + off[i]);
        bool ok = true;
#pragma unroll
        for (int i = 0; i < N; i++) { ok = ok && ((uint32_t)(w[i] >> 32) == tag); val[i] = (uint32_t)w[i]; }
        if (__all_sync(0xffffffffu, ok)) break;
        if (++it > SPIN_LIMIT) __trap();
    }
}
__device__ __forceinline__ void st_pk16(uint4* p, uint32_t a, uint32_t b, uint32_t c, uint32_t tag) {
    asm volatile(
        "{\n.reg .b128 t;\n.reg .b64 lo, hi;\nmov.b64 lo, {%1, %2};\nmov.b64 hi, {%3, %4};\nmov.b128 t, {lo, hi};\n"
        "st.relaxed.gpu.global.b128 [%0], t;\n}" ::"l"(p), "r"(a), "r"(b), "r"(c), "r"(tag)
        : "memory");
}
template <int OFF = 0>
__device__ __forceinline__ uint4 ld_raw16p(const uint4* p, uint32_t on) {
    uint4 v;
    asm volatile(
        "{\n.reg .b128 t;\n.reg .b64 lo, hi;\n.reg .pred q;\nsetp.ne.u32 q, %5, 0;\n"
        "mov.b64 lo, 0;\nmov.b128 t, {lo, lo};\n"
        "@q ld.relaxed.gpu.global.b128 t, [%4 + %6];\nmov.b128 {lo, hi}, t;\n"
        "mov.b64 {%0, %1}, lo;\nmov.b64 {%2, %3}, hi;\n}"
        : "=r"(v.x), "=r"(v.y), "=r"(v.z), "=r"(v.w)
        : "l"(p), "r"(on), "n"(OFF * 16)
        : "memory");
    return v;
}
template <int OFF>
__device__ __forceinline__ void ld_fresh16(uint4& v, const uint4* p, uint32_t tag, uint32_t on) {
    asm volatile(
        "{\n.reg .b128 t;\n.reg .b64 lo, hi;\n.reg .pred q;\nsetp.ne.u32 q, %3, %5;\nsetp.ne.and.u32 q, %6, 0, q;\n"
        "mov.b64 lo, {%0, %1};\nmov.b64 hi, {%2, %3};\nmov.b128 t, {lo, hi};\n"
        "@q ld.relaxed.gpu.global.b128 t, [%4 + %7];\nmov.b128 {lo, hi}, t;\n"
        "mov.b64 {%0, %1}, lo;\nmov.b64 {%2, %3}, hi;\n}"
        : "+r"(v.x), "+r"(v.y), "+r"(v.z), "+r"(v.w)
        : "l"(p), "r"(tag), "r"(on), "n"(OFF * 16)
        : "memory");
}
template <int N, int STRIDE, int I = 0>
struct FreshN {
    static __device__ __forceinline__ void run(uint4* v, const uint4* p, uint32_t tag, bool live, int base, int step, int lim) {
        ld_fresh16<I * STRIDE>(v[I], p, tag, live && base + step * I < lim);
        FreshN<N, STRIDE, I + 1>::run(v, p, tag, live, base, step, lim);
    }
};
template <int N, int STRIDE>
struct FreshN<N, STRIDE, N> {
    static __device__ __forceinline__ void run(uint4*, const uint4*, uint32_t, bool, int, int, int) {}
};
template <int N, int STRIDE, int I = 0>
struct LoadN {
    static __device__ __forceinline__ void run(uint4* v, const uint4* p, bool live, int base, int step, int lim) {
        v[I] = ld_raw16p<I * STRIDE>(p, live && base + step * I < lim);
        LoadN<N, STRIDE, I + 1>::run(v, p, live, base, step, lim);
    }
};
template <int N, int STRIDE>
struct LoadN<N, STRIDE, N> {
    static __device__ __forceinline__ void run(uint4*, const uint4*, bool, int, int, int) {}
};
__device__ __forceinline__ uint4 poll16(const uint4* p, uint32_t tag, bool live) {
    uint32_t it = 0;
    uint4 v;
    while (true) {
        v = ld_raw16p(p, live);
        if (__all_sync(0xffffffffu, v.w == tag) || !live) break;
        if (++it > SPIN_LIMIT) __trap();
    }
    return v;
}
__device__ __forceinline__ void st_zero16(void* p) {
    asm volatile("st.relaxed.gpu.global.v4.u32 [%0], {%1, %1, %1, %1};" ::"l"(p), "r"(0u) : "memory");
}
__device__ __forceinline__ float ex2(float x) {
    float y;
    asm("ex2.approx.ftz.f32 %0, %1;" : "=f"(y) : "f"(x));
    return y;
}
__device__ __forceinline__ float fsqrt(float x) {
    float y;
    asm("sqrt.approx.f32 %0, %1;" : "=f"(y) : "f"(x));
    return y;
}
constexpr float LOG2E = 1.4426950408889634f;
__device__ __forceinline__ float silu(float a) { return __fdividef(a, 1.0f + ex2(-a * LOG2E)); }
__device__ __forceinline__ float warp_sum(float v) {
#pragma unroll
    for (int o = 16; o > 0; o >>= 1) v += __shfl_xor_sync(0xffffffffu, v, o);
    return v;
}

__device__ __forceinline__ void ln_stats(const float (&v)[20], float& mean_b, float& den_b) {
    float s = 0.f;
#pragma unroll
    for (int i = 0; i < 20; i++) s += v[i];
    s = warp_sum(s);
    float mean = s * (1.0f / 640.0f);
    float q = 0.f;
#pragma unroll
    for (int i = 0; i < 20; i++) { float d = v[i] - mean; q += d * d; }
    q = warp_sum(q);
    float var_b = bfr(q * (1.0f / 640.0f));
    mean_b = bfr(mean);
    den_b = bfr(fsqrt(bfr(var_b + 1e-5f)));
}

struct Window {
    uint32_t bar[WIN];
    uint32_t par[WIN];
    __device__ __forceinline__ void init(uint32_t dummy) {
#pragma unroll
        for (int i = 0; i < WIN; i++) { bar[i] = dummy; par[i] = 1; }
    }
    __device__ __forceinline__ void push(uint32_t b, uint32_t p, bool wait = true) {
        if (wait) mbar_wait(bar[0], par[0]);
#pragma unroll
        for (int i = 0; i + 1 < WIN; i++) { bar[i] = bar[i + 1]; par[i] = par[i + 1]; }
        bar[WIN - 1] = b; par[WIN - 1] = p;
    }
};

__global__ void __launch_bounds__(NTHREADS, 1)
fused_decode_kernel(const __grid_constant__ CUtensorMap tmK, const __grid_constant__ CUtensorMap tmV,
                    const __grid_constant__ CUtensorMap tmMod, const __grid_constant__ CUtensorMap tmWq,
                    const __grid_constant__ CUtensorMap tmWo, const __grid_constant__ CUtensorMap tmW1,
                    const __grid_constant__ CUtensorMap tmW3, const __grid_constant__ CUtensorMap tmW2,
                    const __nv_bfloat16* __restrict__ x_in, const __nv_bfloat16* __restrict__ c_in,
                    __nv_bfloat16* __restrict__ out) {
    extern __shared__ __align__(1024) uint8_t smem[];
    const uint32_t sb = smem_u32(smem);
    const int tid = threadIdx.x, wid = tid >> 5, lane = tid & 31;
    const int cta = blockIdx.x, G = gridDim.x;
    const int grp = cta % NG, rank = cta / NG;
    const uint32_t bars = sb + SM_BARS;
    auto BAR = [&](int i) { return bars + 8u * i; };
    volatile uint32_t* meta = reinterpret_cast<volatile uint32_t*>(smem + SM_META);

    if (wid == 8) {
        Window win;
        unsigned epoch = 0;
        if (tid == 256) {
            TS(0);
            if (sb & 1023u) __trap();
            asm volatile("ld.relaxed.gpu.global.u32 %0, [%1];" : "=r"(epoch) : "l"(&g_epoch) : "memory");
            prefetch_tm(&tmMod); prefetch_tm(&tmWq); prefetch_tm(&tmK); prefetch_tm(&tmV);
#pragma unroll
            for (int i = 0; i < 4; i++) mbar_init(BAR(B_MOD + i), 1);
            mbar_init(BAR(B_DUMMY), 1);
            asm volatile("fence.mbarrier_init.release.cluster;" ::: "memory");
            asm volatile("fence.proxy.async.shared::cta;" ::: "memory");
            win.init(BAR(B_DUMMY));
            if (cta < 120) {
#pragma unroll 1
                for (int i = 0; i < WIN; i++) {
                    win.push(BAR(B_MOD + i), 0);
                    mbar_expect_tx(BAR(B_MOD + i), 10240);
                    tma2d(sb + SM_WMOD + i * 10240, &tmMod, cta * 32, i * 160, BAR(B_MOD + i));
                }
            }
#pragma unroll 1
            for (int i = 0; i < B_DUMMY; i++) {
                if (i >= B_MOD && i < B_MOD + 4) continue;
                int cnt = (i >= B_EMPTY && i < B_MOD) ? 2 : (i == B_FLF ? 4 : 1);
                mbar_init(BAR(i), cnt);
            }
            asm volatile("fence.mbarrier_init.release.cluster;" ::: "memory");
            asm volatile("fence.proxy.async.shared::cta;" ::: "memory");
        }
        __syncwarp();
        __syncthreads();
        if (tid == 256) {
            prefetch_tm(&tmWo); prefetch_tm(&tmW1); prefetch_tm(&tmW3); prefetch_tm(&tmW2);
            unsigned* ctr = &g_ctr[epoch & 1][grp * 32];
            unsigned* gctr = &g_ctr[epoch & 1][NG * 32];
            if (cta == 0) {
                for (int g = 0; g <= NG; g++) g_ctr[(epoch + 1) & 1][g * 32] = 0;
            }
            unsigned pend = atomicAdd(ctr, 1);
            if (cta < 120) {
#pragma unroll 1
                for (int i = WIN; i < 4; i++) {
                    win.push(BAR(B_MOD + i), 0);
                    mbar_expect_tx(BAR(B_MOD + i), 10240);
                    tma2d(sb + SM_WMOD + i * 10240, &tmMod, cta * 32, i * 160, BAR(B_MOD + i));
                }
            }
            if (cta < 128) {
#pragma unroll 1
                for (int i = 0; i < 5; i++) {
                    win.push(BAR(B_WQ + i), 0);
                    mbar_expect_tx(BAR(B_WQ + i), 12288);
                    tma2d(sb + SM_WQ + i * 12288, &tmWq, cta * 48, i * 128, BAR(B_WQ + i));
                }
            }
            uint64_t pol;
            asm volatile("createpolicy.fractional.L2::evict_first.b64 %0, 1.0;" : "=l"(pol));
            int s = 0; uint32_t par = 0;
            int ntiles = 0, run = -1, last_head = -1;
            bool glob = false;
#pragma unroll 1
            while (true) {
                unsigned t = pend;
                DBG(8);
                if (!glob && t >= (unsigned)GT) { glob = true; t = atomicAdd(gctr, 1); }
                if (glob && t >= (unsigned)PT) break;
                pend = atomicAdd(glob ? gctr : ctr, 1);
                ntiles++;
                const int hl = t / TPH, tile = t % TPH;
                const int head = glob ? NG * GH + hl : grp * GH + hl;
                const int qidx = glob ? GH + hl : hl;
                if (head != last_head) { last_head = head; run++; meta[16 + run] = head; }
                const int line0 = (head * SK + tile * TILE) * 3;
                const bool urgent = glob && t >= (unsigned)(PT - P_URG);
#pragma unroll 1
                for (int kv = 0; kv < 2; kv++) {
                    win.push(BAR(B_FULL + s), par, !urgent);
                    mbar_wait(BAR(B_EMPTY + s), par ^ 1);
                    meta[s] = run | (qidx << 8);
                    mbar_expect_tx(BAR(B_FULL + s), CHUNK);
                    tma2d_hint(sb + SM_RING + s * CHUNK, kv ? &tmV : &tmK, 0, line0, BAR(B_FULL + s), pol);
                    DBG(6 + kv);
                    if (++s == NSLOT) { s = 0; par ^= 1; }
                }
            }
            TS(5);
            meta[16 + run + 1] = 0xFFu;
#pragma unroll 1
            for (int e = 0; e < 2; e++) {
                mbar_wait(BAR(B_EMPTY + s), par ^ 1);
                meta[s] = (run + 1) | META_END;
                mbar_arrive(BAR(B_FULL + s));
                if (++s == NSLOT) { s = 0; par ^= 1; }
                if (++s == NSLOT) { s = 0; par ^= 1; }
            }
#pragma unroll
            for (int i = 0; i < WIN - P_HOLD; i++) mbar_wait(win.bar[i], win.par[i]);
            if (cta < 128) {
                mbar_wait(BAR(B_PRO), 0);
#pragma unroll 1
                for (int i = 0; i < 5; i++) {
                    win.push(BAR(B_WO + i), 0);
                    mbar_expect_tx(BAR(B_WO + i), 12288);
                    tma2d(sb + SM_WO + (2 * i) * 6144, &tmWo, (2 * i) * 64, cta * 48, BAR(B_WO + i));
                    tma2d(sb + SM_WO + (2 * i + 1) * 6144, &tmWo, (2 * i + 1) * 64, cta * 48, BAR(B_WO + i));
                }
                if (cta < 96) {
#pragma unroll 1
                    for (int i = 0; i < 4; i++) {
                        const int m = i & 1, hf = i >> 1;
                        const uint32_t bar = BAR((m ? B_W3 : B_W1) + hf);
                        const uint32_t dst = sb + (m ? SM_W3 : SM_W1) + hf * 10240;
                        const CUtensorMap* tm = m ? &tmW3 : &tmW1;
                        win.push(bar, 0);
                        mbar_expect_tx(bar, 10240);
                        tma2d(dst, tm, cta * 16, hf * 320, bar);
                        tma2d(dst + 5120, tm, cta * 16, hf * 320 + 160, bar);
                    }
#pragma unroll 1
                    for (int i = 0; i < 2; i++) {
                        win.push(BAR(B_W2 + i), 0);
                        mbar_wait(BAR(B_EMPTY + s), par ^ 1);
                        meta[10 + i] = s;
                        mbar_expect_tx(BAR(B_W2 + i), 10240);
#pragma unroll 1
                        for (int b = 0; b < 5; b++)
                            tma2d(sb + SM_RING + s * CHUNK + b * 2048, &tmW2, (5 * i + b) * 64, cta * 16, BAR(B_W2 + i));
                        if (++s == NSLOT) { s = 0; par ^= 1; }
                    }
                }
            }
            TS(6);
        }
    } else {
    const int g4 = lane >> 2, j4 = lane & 3, mi = lane >> 3, l8 = lane & 7;
    uint32_t* sc32 = reinterpret_cast<uint32_t*>(smem + SM_SC);
    uint32_t* h32 = reinterpret_cast<uint32_t*>(smem + SM_H);
    uint32_t* x32 = reinterpret_cast<uint32_t*>(smem + SM_X);
    uint32_t* q32 = reinterpret_cast<uint32_t*>(smem + SM_Q);
    float* red = reinterpret_cast<float*>(smem + SM_RED);
    float* stage = reinterpret_cast<float*>(smem + SM_STAGE);
    float* own = reinterpret_cast<float*>(smem + SM_OWN);

    uint32_t tag;
    bool live = true;
    if (wid == 9) { __syncthreads(); tag = meta[8]; live = false; } else {
    {
        const uint32_t* cg = reinterpret_cast<const uint32_t*>(c_in);
        const uint32_t* xg = reinterpret_cast<const uint32_t*>(x_in);
        uint32_t c0 = cg[tid], x0 = xg[tid], c1 = 0, x1 = 0;
        if (tid < 64) { c1 = cg[256 + tid]; x1 = xg[256 + tid]; }
        unsigned epoch = 0;
        if (tid == 0) asm volatile("ld.relaxed.gpu.global.u32 %0, [%1];" : "=r"(epoch) : "l"(&g_epoch) : "memory");
        if (cta < 120 && tid < 8) st_zero16(reinterpret_cast<uint4*>(&g_mod[cta * 16]) + tid);
        if (cta < 128 && tid >= 32 && tid < 44) st_zero16(reinterpret_cast<uint4*>(&g_q[cta * 24]) + (tid - 32));
        if (cta < 128) {
            if (tid >= 64 && tid < 66) st_zero16(&g_x2[cta][tid - 64]);
            st_zero16(&g_h1[tid >> 1][cta][tid & 1]);
            if (cta < 96) st_zero16(&g_h3[tid >> 1][cta][tid & 1]);
        }
#pragma unroll 1
        for (int f = tid >> 6; f < NQH; f += 4) {
            const int head = f < GH ? grp * GH + f : NG * GH + (f - GH);
            const int idx = f < GH ? rank : cta;
            st_zero16(&g_dat[head][idx][tid & 63]);
            if ((tid & 63) == 0) st_zero16(&g_hdr[head][idx]);
        }
        sc32[tid] = pack_bf(silu(bf_lo(c0)), silu(bf_hi(c0))); x32[tid] = x0;
        if (tid < 64) { sc32[256 + tid] = pack_bf(silu(bf_lo(c1)), silu(bf_hi(c1))); x32[256 + tid] = x1; }
        if (tid == 0) meta[8] = epoch + 1;
    }
    __syncthreads();
    tag = meta[8];

    float mean_x = 0.f, rden_x = 1.f;
    if (cta < 128) {
        float xv[20];
#pragma unroll
        for (int i = 0; i < 10; i++) { uint32_t v = x32[lane + 32 * i]; xv[2 * i] = bf_lo(v); xv[2 * i + 1] = bf_hi(v); }
        float den;
        ln_stats(xv, mean_x, den);
        rden_x = __fdividef(1.0f, den);
    }

    if (cta < 120) {
        float acc[2][4] = {};
        uint32_t a[5][2][4], bb[5][2];
        const uint32_t base = sb + SM_WMOD + (wid >> 1) * 10240;
#pragma unroll
        for (int ks = 0; ks < 5; ks++) {
            const int r0 = wid * 80 + ks * 16;
            bb[ks][0] = sc32[(r0 >> 1) + j4]; bb[ks][1] = sc32[(r0 >> 1) + 4 + j4];
        }
        mbar_wait(BAR(B_MOD + (wid >> 1)), 0);
#pragma unroll
        for (int ks = 0; ks < 5; ks++) {
            const int r = (wid & 1) * 80 + ks * 16 + l8 + 8 * (mi >> 1);
#pragma unroll
            for (int mt = 0; mt < 2; mt++) ldsm4t(a[ks][mt], base + r * 64 + (((2 * mt + (mi & 1)) ^ ((r >> 1) & 3)) << 4));
        }
#pragma unroll
        for (int ks = 0; ks < 5; ks++) { mma16816(acc[0], a[ks][0], bb[ks][0], bb[ks][1]); mma16816(acc[1], a[ks][1], bb[ks][0], bb[ks][1]); }
        if (j4 == 0) {
#pragma unroll
            for (int mt = 0; mt < 2; mt++) { red[wid * 64 + mt * 16 + g4] = acc[mt][0]; red[wid * 64 + mt * 16 + 8 + g4] = acc[mt][2]; }
        }
        bar_cons();
        if (wid == 0) {
            float v = 0.f;
#pragma unroll
            for (int w = 0; w < 8; w++) v += red[w * 64 + lane];
            float o = __shfl_down_sync(0xffffffffu, v, 1);
            if (!(lane & 1)) st_pk8(&g_mod[cta * 16 + (lane >> 1)], pack_bf(v, o), tag);
        }
    }
    TS(1);

    if (cta < 128) {
        {
            const int off[4] = {tid, 320 + tid, tid < 64 ? 256 + tid : tid, tid < 64 ? 576 + tid : 320 + tid};
            uint32_t val[4];
            poll8<4>(g_mod, off, val, tag);
#pragma unroll
            for (int rep = 0; rep < 2; rep++) {
                int p = tid + rep * 256;
                if (p < 320) {
                    uint32_t sa = val[2 * rep], ca = val[2 * rep + 1];
                    uint32_t xx = x32[p];
                    float n0 = bfr(bfr(bf_lo(xx) - mean_x) * rden_x), n1 = bfr(bfr(bf_hi(xx) - mean_x) * rden_x);
                    float h0 = bfr(n0 * bfr(1.0f + bf_lo(ca))) + bf_lo(sa);
                    float h1 = bfr(n1 * bfr(1.0f + bf_hi(ca))) + bf_hi(sa);
                    h32[p] = pack_bf(h0, h1);
                }
            }
        }
        bar_cons();
        TS(2);
        float acc[3][4] = {};
        uint32_t a[5][3][4], bb[5][2];
#pragma unroll
        for (int ks = 0; ks < 5; ks++) {
            const int r0 = wid * 80 + ks * 16;
            bb[ks][0] = h32[(r0 >> 1) + j4]; bb[ks][1] = h32[(r0 >> 1) + 4 + j4];
        }
        mbar_wait(BAR(B_WQ + ((wid * 80) >> 7)), 0);
        mbar_wait(BAR(B_WQ + ((wid * 80 + 79) >> 7)), 0);
#pragma unroll
        for (int ks = 0; ks < 5; ks++) {
            const int r = wid * 80 + ks * 16 + l8 + 8 * (mi >> 1);
#pragma unroll
            for (int mt = 0; mt < 3; mt++) ldsm4t(a[ks][mt], sb + SM_WQ + r * 96 + ((2 * mt + (mi & 1)) << 4));
        }
#pragma unroll
        for (int ks = 0; ks < 5; ks++) {
#pragma unroll
            for (int mt = 0; mt < 3; mt++) mma16816(acc[mt], a[ks][mt], bb[ks][0], bb[ks][1]);
        }
        if (j4 == 0) {
#pragma unroll
            for (int mt = 0; mt < 3; mt++) { red[wid * 64 + mt * 16 + g4] = acc[mt][0]; red[wid * 64 + mt * 16 + 8 + g4] = acc[mt][2]; }
        }
        bar_cons();
        if (tid < 64) {
            float v = 0.f;
            if (tid < 48) {
#pragma unroll
                for (int w = 0; w < 8; w++) v += red[w * 64 + tid];
            }
            float o = __shfl_down_sync(0xffffffffu, v, 1);
            if (tid < 48 && !(tid & 1)) st_pk8(&g_q[cta * 24 + (tid >> 1)], pack_bf(v, o), tag);
        }
        TS(3);
    }
    {
        int off[5];
#pragma unroll
        for (int j = 0; j < 5; j++) {
            int p = tid + 256 * j;
            if (p >= NQH * 96) p = tid;
            off[j] = p < GH * 96 ? grp * GH * 96 + p : NG * GH * 96 + (p - GH * 96);
        }
        uint32_t val[5];
        poll8<5>(g_q, off, val, tag);
#pragma unroll
        for (int j = 0; j < 5; j++)
            if (tid + 256 * j < NQH * 96) q32[tid + 256 * j] = val[j];
    }
    bar_cons();
    if (tid == 0) mbar_arrive(BAR(B_PRO));
    TS(4);

    if (wid < 4) {
        const int pair = wid >> 1, half = wid & 1;
        uint32_t offK[3], offV[3];
        {
            const int rowK = half * 16 + l8 + 8 * (mi & 1), hiK = mi >> 1;
            const int rowV = half * 16 + l8 + 8 * (mi >> 1), hiV = mi & 1;
#pragma unroll
            for (int t = 0; t < 3; t++) {
                offK[t] = (rowK * 3 + t) * 128 + ((hiK ^ ((rowK * 3 + t) & 7)) << 4);
                offV[t] = (rowV * 3 + t) * 128 + ((hiV ^ ((rowV * 3 + t) & 7)) << 4);
                asm volatile("" : "+r"(offK[t]), "+r"(offV[t]));
            }
        }
        float acc[12][4];
#pragma unroll
        for (int i = 0; i < 12; i++) { acc[i][0] = acc[i][1] = acc[i][2] = acc[i][3] = 0.f; }
        float m_run = NEG_BIG, l_run = 0.f;
        uint32_t qf[12][2];
#pragma unroll
        for (int i = 0; i < 12; i++) { qf[i][0] = qf[i][1] = 0; }
        int cur = -1, flushed = 0, cnt = 0;
        int s = 2 * pair; uint32_t par = 0;
        float* mb = reinterpret_cast<float*>(smem + SM_MERGE) + wid * 200;
        uint32_t ready = 0;
#pragma unroll 1
        while (true) {
            if (!ready) mbar_wait(BAR(B_FULL + s), par);
            const uint32_t mt_ = meta[s];
            const int run = mt_ & 0xff;
            if (mt_ & META_END) CLK(20);
            if ((mt_ & META_END) && half == 0) DBG(4 + pair);
            if (run != cur) {
#pragma unroll 1
                while (flushed < run) {
                    const uint32_t fle = mbar_try(BAR(B_FLE), (flushed & 1) ^ 1);
                    if (flushed != cur) {
#pragma unroll
                        for (int i = 0; i < 12; i++) { acc[i][0] = acc[i][2] = 0.f; }
                        m_run = NEG_BIG; l_run = 0.f; cnt = 0;
                    }
                    float l = l_run;
                    l += __shfl_xor_sync(0xffffffffu, l, 4);
                    l += __shfl_xor_sync(0xffffffffu, l, 8);
                    l += __shfl_xor_sync(0xffffffffu, l, 16);
                    if (!fle) mbar_wait(BAR(B_FLE), (flushed & 1) ^ 1);
                    if (j4 == 0) {
#pragma unroll
                        for (int i = 0; i < 12; i++) { mb[4 + 16 * i + g4] = acc[i][0]; mb[4 + 16 * i + 8 + g4] = acc[i][2]; }
                    }
                    if (lane == 0) { mb[0] = m_run; mb[1] = l; mb[2] = __int_as_float(cnt); }
                    __syncwarp();
                    if (lane == 0) mbar_arrive(BAR(B_FLF));
                    flushed++;
                    cur = -1;
                }
                if (mt_ & META_END) {
                    CLK(21);
                    if (flushed == 0 && lane == 0) mbar_arrive(BAR(B_FLF));
                    break;
                }
                cur = run;
                const int qi = (mt_ >> 8) & 0xff;
#pragma unroll
                for (int i = 0; i < 12; i++) { acc[i][0] = acc[i][1] = acc[i][2] = acc[i][3] = 0.f; }
                m_run = NEG_BIG; l_run = 0.f; cnt = 0;
#pragma unroll
                for (int ks = 0; ks < 12; ks++) {
                    qf[ks][0] = q32[qi * 96 + ks * 8 + j4];
                    qf[ks][1] = q32[qi * 96 + ks * 8 + 4 + j4];
                }
            }
            cnt++;
            if (half == 0) DBG(pair);
            const uint32_t kb = sb + SM_RING + s * CHUNK;
            int sv = s + 1; uint32_t parv = par;
            if (sv == NSLOT) { sv = 0; parv ^= 1; }
            float sc[6][4] = {};
            uint32_t vready;
            {
                uint32_t a[12][4];
#pragma unroll
                for (int t = 0; t < 3; t++) {
                    const uint32_t bt = kb + offK[t];
#pragma unroll
                    for (int kk = 0; kk < 4; kk++) ldsm4(a[t * 4 + kk], bt ^ (kk << 5));
                }
                vready = mbar_try(BAR(B_FULL + sv), parv);
#pragma unroll
                for (int i = 0; i < 12; i++) mma16816(sc[i % 6], a[i], qf[i][0], qf[i][1]);
            }
            __syncwarp();
            if (lane == 0) mbar_arrive(BAR(B_EMPTY + s));
            const float scale = 0.07216878364870322f;
            float s0 = bfr(bfr(((sc[0][0] + sc[1][0]) + (sc[2][0] + sc[3][0])) + (sc[4][0] + sc[5][0])) * scale);
            float s1 = bfr(bfr(((sc[0][2] + sc[1][2]) + (sc[2][2] + sc[3][2])) + (sc[4][2] + sc[5][2])) * scale);
            float tm = fmaxf(s0, s1);
            tm = fmaxf(tm, __shfl_xor_sync(0xffffffffu, tm, 4));
            tm = fmaxf(tm, __shfl_xor_sync(0xffffffffu, tm, 8));
            tm = fmaxf(tm, __shfl_xor_sync(0xffffffffu, tm, 16));
            if (tm > m_run) {
                float alpha = ex2((m_run - tm) * LOG2E);
                l_run *= alpha;
#pragma unroll
                for (int i = 0; i < 12; i++) { acc[i][0] *= alpha; acc[i][1] *= alpha; acc[i][2] *= alpha; acc[i][3] *= alpha; }
                m_run = tm;
            }
            float p0 = ex2((s0 - m_run) * LOG2E);
            float p1 = ex2((s1 - m_run) * LOG2E);
            l_run += p0 + p1;
            const uint32_t pw = pack_bf(p0, p1);
            const uint32_t pa = __shfl_sync(0xffffffffu, pw, 8 * j4), pb = __shfl_sync(0xffffffffu, pw, 8 * j4 + 4);
            const uint32_t b0 = __byte_perm(pa, pb, 0x5410), b1 = __byte_perm(pa, pb, 0x7632);
            if (!vready) mbar_wait(BAR(B_FULL + sv), parv);
            s += 4;
            if (s >= NSLOT) { s -= NSLOT; par ^= 1; }
            if (half == 0) DBG(2 + pair);
            ready = mbar_try(BAR(B_FULL + s), par);
            const uint32_t vb = sb + SM_RING + sv * CHUNK;
            {
                uint32_t a[12][4];
#pragma unroll
                for (int t = 0; t < 3; t++) {
                    const uint32_t bt = vb + offV[t];
#pragma unroll
                    for (int kk = 0; kk < 4; kk++) ldsm4t(a[t * 4 + kk], bt ^ (kk << 5));
                }
#pragma unroll
                for (int i = 0; i < 12; i++) mma16816(acc[i], a[i], b0, b1);
            }
            __syncwarp();
            if (lane == 0) mbar_arrive(BAR(B_EMPTY + sv));
        }
        TS(7);
        CLK(18);
    } else if (wid == 4) {
        const float* mb = reinterpret_cast<const float*>(smem + SM_MERGE);
#pragma unroll 1
        for (int f = 0;; f++) {
            mbar_wait(BAR(B_FLF), f & 1);
            const int head = (int)meta[16 + f];
            if (head == 0xFF) break;
            float m0 = mb[0], m1 = mb[200], m2 = mb[400], m3 = mb[600];
            float M = fmaxf(fmaxf(m0, m1), fmaxf(m2, m3));
            float w0 = ex2((m0 - M) * LOG2E), w1 = ex2((m1 - M) * LOG2E);
            float w2 = ex2((m2 - M) * LOG2E), w3 = ex2((m3 - M) * LOG2E);
            const int idx = head < NG * GH ? rank : cta;
            uint4* dst = &g_dat[head][idx][0];
            float o[6];
#pragma unroll
            for (int i = 0; i < 6; i++) {
                int d = 4 + (i < 3 ? 3 * lane + i : 96 + 3 * lane + (i - 3));
                o[i] = w0 * mb[d] + w1 * mb[200 + d] + w2 * mb[400 + d] + w3 * mb[600 + d];
            }
            float L = w0 * mb[1] + w1 * mb[201] + w2 * mb[401] + w3 * mb[601];
            const uint32_t tiles = __float_as_int(mb[2]) + __float_as_int(mb[402]);
            st_pk16(dst + lane, __float_as_uint(o[0]), __float_as_uint(o[1]), __float_as_uint(o[2]), tag);
            st_pk16(dst + 32 + lane, __float_as_uint(o[3]), __float_as_uint(o[4]), __float_as_uint(o[5]), tag);
            if (lane == 0) st_pk16(&g_hdr[head][idx], __float_as_uint(M), __float_as_uint(L), tiles, tag);
            __syncwarp();
            if (lane == 0) mbar_arrive(BAR(B_FLE));
            if (meta[16 + f + 1] == 0xFFu) break;
        }
        TS(8);
        CLK(18);
    } else if (wid >= 6) {
        if (cta < 128) {
            const int t = tid - 192;
            uint32_t* cb32 = reinterpret_cast<uint32_t*>(smem + SM_CB);
            uint32_t* sb32 = reinterpret_cast<uint32_t*>(smem + SM_SB);
            const int col = cta * 5 + t;
            int off[12];
            uint32_t val[12];
#pragma unroll
            for (int rep = 0; rep < 5; rep++) { off[2 * rep] = 960 + t + 64 * rep; off[2 * rep + 1] = 1280 + t + 64 * rep; }
            off[10] = t < 5 ? (1280 + col) >> 1 : 960;
            off[11] = t < 5 ? (3200 + col) >> 1 : 960;
            poll8<12>(g_mod, off, val, tag);
#pragma unroll
            for (int rep = 0; rep < 5; rep++) {
                sb32[t + 64 * rep] = val[2 * rep];
                cb32[t + 64 * rep] = pack_bf(1.0f + bf_lo(val[2 * rep + 1]), 1.0f + bf_hi(val[2 * rep + 1]));
            }
            if (t < 5) {
                own[t] = (col & 1) ? bf_hi(val[10]) : bf_lo(val[10]);
                own[8 + t] = (col & 1) ? bf_hi(val[11]) : bf_lo(val[11]);
                uint32_t xx = x32[col >> 1];
                own[16 + t] = (col & 1) ? bf_hi(xx) : bf_lo(xx);
            }
        }
        live = false;
    }
    }
    const uint32_t sb0 = sb;
    const bool warmer = wid == 9;
    const int tid0 = warmer ? tid - 64 : tid;
#pragma unroll 1
    while (cta < 128) {
        uint32_t sb = sb0; int tid = tid0;
        asm volatile("" : "+r"(sb), "+r"(tid));
        const int wid = tid >> 5, lane = tid & 31;
        const int g4 = lane >> 2, j4 = lane & 3, mi = lane >> 3, l8 = lane & 7;
        CLK(19);
        if (wid >= 5) {
            const int h = cta >> 2, js = cta & 3;
            const bool gl = h >= NG * GH;
            const int ncand = gl ? G : (G - h / GH + NG - 1) / NG;
            const int k = lane & 15, rr = (wid - 5) * 2 + (lane >> 4);
            if (live) {
                const unsigned* cp = &g_ctr[(tag - 1) & 1][(gl ? NG : h / GH) * 32];
                const unsigned thr = ((gl ? h - NG * GH : h % GH) + 1) * TPH;
                uint32_t it = 0;
                while (true) {
                    unsigned v;
                    asm volatile("ld.relaxed.gpu.global.u32 %0, [%1];" : "=r"(v) : "l"(cp) : "memory");
                    if (v >= thr) break;
                    __nanosleep(300);
                    if (++it > SPIN_LIMIT) __trap();
                }
            }
            const uint4* hdr = &g_hdr[h][lane];
            const uint4* dat = &g_dat[h][rr][16 * js + k];
            float* part = stage;
            float L, a0, a1, a2;
            uint32_t it = 0;
            uint4 hd[5], dv[MAXG / 6];
#pragma unroll
            for (int i = 0; i < 5; i++) hd[i] = make_uint4(0, 0, 0, 0);
#pragma unroll
            for (int i = 0; i < MAXG / 6; i++) dv[i] = make_uint4(0, 0, 0, 0);
#pragma unroll 1
            while (true) {
                FreshN<5, 32>::run(hd, hdr, tag, live, lane, 32, ncand);
                FreshN<MAXG / 6, 6 * 64>::run(dv, dat, tag, live, rr, 6, ncand);
                float w[5], M = NEG_BIG;
                int c = 0;
#pragma unroll
                for (int i = 0; i < 5; i++) {
                    const bool v = hd[i].w == tag;
                    w[i] = v ? __uint_as_float(hd[i].x) : NEG_BIG;
                    M = fmaxf(M, w[i]);
                    c += v ? (int)hd[i].z : 0;
                }
                c = __reduce_add_sync(0xffffffffu, c);
                if (++it > SPIN_LIMIT) __trap();
                if (live && c != TPH) continue;
                CLK(1);
#pragma unroll
                for (int o = 16; o > 0; o >>= 1) M = fmaxf(M, __shfl_xor_sync(0xffffffffu, M, o));
                float ls = 0.f;
#pragma unroll
                for (int i = 0; i < 5; i++) {
                    const bool v = w[i] != NEG_BIG;
                    const float e = ex2((w[i] - M) * LOG2E);
                    w[i] = v ? e : -0.0f;
                    ls = fmaf(w[i], __uint_as_float(hd[i].y), ls);
                }
                float* wsm = reinterpret_cast<float*>(smem + SM_X2) + (wid - 5) * 160;
                if (live) {
#pragma unroll
                    for (int i = 0; i < 5; i++) wsm[lane + 32 * i] = w[i];
                }
                __syncwarp();
                uint32_t badm = 0;
                a0 = a1 = a2 = 0.f;
#pragma unroll
                for (int i = 0; i < MAXG / 6; i++) {
                    const float wi = wsm[rr + 6 * i];
                    badm |= (dv[i].w ^ tag) & ~(uint32_t)(__float_as_int(wi) >> 31);
                    a0 = fmaf(wi, __uint_as_float(dv[i].x), a0);
                    a1 = fmaf(wi, __uint_as_float(dv[i].y), a1);
                    a2 = fmaf(wi, __uint_as_float(dv[i].z), a2);
                }
                const bool bad = badm != 0;
                __syncwarp();
                L = warp_sum(ls);
                if (!__any_sync(0xffffffffu, bad) || !live) break;
            }
            a0 += __shfl_xor_sync(0xffffffffu, a0, 16);
            a1 += __shfl_xor_sync(0xffffffffu, a1, 16);
            a2 += __shfl_xor_sync(0xffffffffu, a2, 16);
            CLK(2);
            if (live && lane < 16) { float* pp = part + (wid - 5) * 48 + 3 * k; pp[0] = a0; pp[1] = a1; pp[2] = a2; }
            if (live) asm volatile("bar.sync 2, 96;" ::: "memory");
            if (wid == 5 || !live) {
                uint16_t* osw = reinterpret_cast<uint16_t*>(smem + SM_SC);
                const float inv = __fdividef(1.0f, L);
                const float o0 = (part[lane] + part[48 + lane]) + part[96 + lane];
                const float o1 = (part[32 + (lane & 15)] + part[80 + (lane & 15)]) + part[128 + (lane & 15)];
                if (live) { osw[lane] = (uint16_t)(__float_as_uint(bfr(o0 * inv)) >> 16); if (lane < 16) osw[32 + lane] = (uint16_t)(__float_as_uint(bfr(o1 * inv)) >> 16); }
            }
            if (live) TS(10);
        }
        if (wid < 5 || !live) {
            const int w5 = wid < 5 ? wid : wid - 5;
            uint32_t wa[8][3][4];
            if (live) mbar_wait(BAR(B_WO + w5), 0);
#pragma unroll
            for (int i = 0; i < 8; i++) {
                const int cc = 2 * (i & 3) + (mi & 1);
#pragma unroll
                for (int ks = 0; ks < 3; ks++) {
                    const int r = ks * 16 + l8 + 8 * (mi >> 1);
                    ldsm4t(wa[i][ks], sb + SM_WO + (2 * w5 + (i >> 2)) * 6144 + r * 128 + ((cc ^ (r & 7)) << 4));
                }
            }
            if (live) bar_cons();
            if (live) TS(9);
            CLK(3);
            const uint32_t* os32 = reinterpret_cast<const uint32_t*>(smem + SM_SC);
            float acc[8][4] = {};
#pragma unroll
            for (int ks = 0; ks < 3; ks++) {
                const uint32_t b0 = os32[ks * 8 + j4], b1 = os32[ks * 8 + 4 + j4];
#pragma unroll
                for (int i = 0; i < 8; i++) mma16816(acc[i], wa[i][ks], b0, b1);
            }
            if (live && j4 == 0) {
#pragma unroll
                for (int i = 0; i < 8; i++) { stage[(w5 * 8 + i) * 16 + g4] = acc[i][0]; stage[(w5 * 8 + i) * 16 + 8 + g4] = acc[i][2]; }
            }
        } else {
            bar_cons();
        }
        CLK(4);
        if (live) bar_cons();
        {
            const int o = tid >> 1, kk = tid & 1;
            const float* sp = stage + o * 5 + kk * 3;
            float v0 = sp[0], v1 = sp[1], v2 = kk ? 0.f : sp[2];
            if (live) st_pk16(&g_h1[o][cta][kk], __float_as_uint(v0), __float_as_uint(v1), __float_as_uint(v2), tag);
        }
        if (live) TS(11);
        CLK(5);
        if (wid == 0 || !live) {
            const uint4* p = &g_h1[cta][0][0] + lane;
            uint4 v[8];
            uint32_t it = 0;
            while (true) {
                bool ok = true;
                LoadN<8, 32>::run(v, p, live, 0, 0, 1);
#pragma unroll
                for (int j = 0; j < 8; j++) ok = ok && v[j].w == tag;
                if (__all_sync(0xffffffffu, ok) || !live) break;
                if (++it > SPIN_LIMIT) __trap();
            }
            CLK(6);
            float a0 = 0.f, a1 = 0.f, a2 = 0.f;
#pragma unroll
            for (int j = 0; j < 8; j++) { a0 += __uint_as_float(v[j].x); a1 += __uint_as_float(v[j].y); a2 += __uint_as_float(v[j].z); }
#pragma unroll
            for (int o = 2; o <= 16; o <<= 1) {
                a0 += __shfl_xor_sync(0xffffffffu, a0, o);
                a1 += __shfl_xor_sync(0xffffffffu, a1, o);
                a2 += __shfl_xor_sync(0xffffffffu, a2, o);
            }
            const float gx = own[lane & 7], xx = own[16 + (lane & 7)];
            const float t0 = __shfl_sync(0xffffffffu, a0, lane >= 3), t1 = __shfl_sync(0xffffffffu, a1, lane >= 3);
            const float sum = (lane == 0 || lane == 3) ? t0 : (lane == 2 ? a2 : t1);
            const float x2 = bfr(xx + bfr(gx * bfr(sum)));
            if (live && lane < 5) own[24 + lane] = x2;
            const float y1 = __shfl_sync(0xffffffffu, x2, 1), y2 = __shfl_sync(0xffffffffu, x2, 2);
            const float y3 = __shfl_sync(0xffffffffu, x2, 3), y4 = __shfl_sync(0xffffffffu, x2, 4);
            if (live && lane == 0) st_pk16(&g_x2[cta][0], pack_bf(x2, y1), pack_bf(y2, y3), pack_bf(y4, 0.f), tag);
            if (live) TS(13);
        }
        CLK(8);
        if (cta < 96) {
            uint32_t a1[5][4], a3[5][4], a2[5][4];
            if (live) mbar_wait3(BAR(B_W1 + (wid >> 2)), BAR(B_W3 + (wid >> 2)), BAR(B_W2 + (wid >> 2)));
            const uint32_t w2b = sb + SM_RING + meta[10 + (wid >> 2)] % NSLOT * CHUNK;
#pragma unroll
            for (int ks = 0; ks < 5; ks++) {
                const int r = wid * 80 + ks * 16 + l8 + 8 * (mi >> 1);
                const uint32_t off = r * 32 + (((mi & 1) ^ ((r >> 2) & 1)) << 4);
                ldsm4t(a1[ks], sb + SM_W1 + off);
                ldsm4t(a3[ks], sb + SM_W3 + off);
            }
#pragma unroll
            for (int i = 0; i < 5; i++) {
                const int mt = (wid & 3) * 5 + i;
                const int cc = 2 * (mt & 3) + (mi & 1);
                const int r = l8 + 8 * (mi >> 1);
                ldsm4t(a2[i], w2b + (mt >> 2) * 2048 + r * 128 + ((cc ^ (r & 7)) << 4));
            }
            CLK(9);
            float* x2s = reinterpret_cast<float*>(smem + SM_X2);
            float* st8 = red + 256;
            if (wid >= 4) {
                uint4 v = poll16(&g_x2[tid - 128][0], tag, live);
                const float e0 = bf_lo(v.x), e1 = bf_hi(v.x), e2 = bf_lo(v.y), e3 = bf_hi(v.y), e4 = bf_lo(v.z);
                float* d = x2s + (tid - 128) * 5;
                if (live) { d[0] = e0; d[1] = e1; d[2] = e2; d[3] = e3; d[4] = e4; }
                const float pv = __shfl_sync(0xffffffffu, e0, 0);
                const float d0 = e0 - pv, d1 = e1 - pv, d2 = e2 - pv, d3 = e3 - pv, d4 = e4 - pv;
                float s1 = ((d0 + d1) + (d2 + d3)) + d4;
                float s2 = fmaf(d0, d0, fmaf(d1, d1, fmaf(d2, d2, fmaf(d3, d3, d4 * d4))));
#pragma unroll
                for (int o = 16; o > 0; o >>= 1) { s1 += __shfl_xor_sync(0xffffffffu, s1, o); s2 += __shfl_xor_sync(0xffffffffu, s2, o); }
                if (live && lane == 0) { st8[2 * (wid - 4)] = pv + s1 * (1.0f / 160.0f); st8[2 * (wid - 4) + 1] = s2 - s1 * s1 * (1.0f / 160.0f); }
            }
            if (live) bar_cons();
            if (live) TS(14);
            CLK(10);
            const float4 sA = *reinterpret_cast<const float4*>(st8), sB = *reinterpret_cast<const float4*>(st8 + 4);
            const float mean = ((sA.x + sA.z) + (sB.x + sB.z)) * 0.25f;
            const float u0 = sA.x - mean, u1 = sA.z - mean, u2 = sB.x - mean, u3 = sB.z - mean;
            const float m2 = ((sA.y + sA.w) + (sB.y + sB.w)) + 160.0f * ((u0 * u0 + u1 * u1) + (u2 * u2 + u3 * u3));
            const float mean_b = bfr(mean);
            const float rden = __fdividef(1.0f, bfr(fsqrt(bfr(bfr(m2 * (1.0f / 640.0f)) + 1e-5f))));
            const uint32_t* cb32 = reinterpret_cast<const uint32_t*>(smem + SM_CB);
            const uint32_t* sb32 = reinterpret_cast<const uint32_t*>(smem + SM_SB);
#pragma unroll
            for (int rep = 0; rep < 2; rep++) {
                const int p = lane + 32 * rep;
                if (p < 40) {
                    int pp = wid * 40 + p;
                    const float2 xv = *reinterpret_cast<const float2*>(x2s + 2 * pp);
                    uint32_t cv = cb32[pp], sv = sb32[pp];
                    float n0 = bfr(bfr(xv.x - mean_b) * rden), n1 = bfr(bfr(xv.y - mean_b) * rden);
                    uint32_t hv = pack_bf(bfr(n0 * bf_lo(cv)) + bf_lo(sv), bfr(n1 * bf_hi(cv)) + bf_hi(sv));
                    if (live) h32[pp] = hv;
                }
            }
            __syncwarp();
            CLK(11);
            float ag[2][4] = {}, au[2][4] = {};
#pragma unroll
            for (int ks = 0; ks < 5; ks++) {
                const int r0 = wid * 80 + ks * 16;
                const uint32_t b0 = h32[(r0 >> 1) + j4], b1 = h32[(r0 >> 1) + 4 + j4];
                mma16816(ag[ks & 1], a1[ks], b0, b1);
                mma16816(au[ks & 1], a3[ks], b0, b1);
            }
            if (live && j4 == 0) {
                red[wid * 32 + g4] = ag[0][0] + ag[1][0]; red[wid * 32 + 8 + g4] = ag[0][2] + ag[1][2];
                red[wid * 32 + 16 + g4] = au[0][0] + au[1][0]; red[wid * 32 + 24 + g4] = au[0][2] + au[1][2];
            }
            CLK(12);
            if (live) bar_cons();
            if (live) TS(15);
            CLK(13);
            float v = 0.f;
#pragma unroll
            for (int w = 0; w < 8; w++) v += red[w * 32 + lane];
            v = bfr(v);
            float up = __shfl_down_sync(0xffffffffu, v, 16);
            float hact = bfr(bfr(silu(v)) * up);
            float e0 = __shfl_sync(0xffffffffu, hact, 2 * j4), e1 = __shfl_sync(0xffffffffu, hact, 2 * j4 + 1);
            float e2 = __shfl_sync(0xffffffffu, hact, 2 * j4 + 8), e3 = __shfl_sync(0xffffffffu, hact, 2 * j4 + 9);
            const uint32_t b0 = pack_bf(e0, e1), b1 = pack_bf(e2, e3);
            float acc[5][4] = {};
#pragma unroll
            for (int i = 0; i < 5; i++) mma16816(acc[i], a2[i], b0, b1);
            if (live && j4 == 0) {
#pragma unroll
                for (int i = 0; i < 5; i++) { stage[(wid * 5 + i) * 16 + g4] = acc[i][0]; stage[(wid * 5 + i) * 16 + 8 + g4] = acc[i][2]; }
            }
            CLK(14);
            if (live) bar_cons();
            const int o = tid >> 1, k = tid & 1;
            const float* sp = stage + o * 5 + k * 3;
            float v0 = sp[0], v1 = sp[1], v2 = k ? 0.f : sp[2];
            if (live) st_pk16(&g_h3[o][cta][k], __float_as_uint(v0), __float_as_uint(v1), __float_as_uint(v2), tag);
        }
        if (live) TS(16);
        CLK(15);
        if (wid == 0 || !live) {
            const uint4* p = &g_h3[cta][0][0] + lane;
            uint4 v[6];
            uint32_t it = 0;
            if (live && cta < 96) spin(P_DLY);
            while (true) {
                bool ok = true;
                LoadN<6, 32>::run(v, p, live, 0, 0, 1);
#pragma unroll
                for (int j = 0; j < 6; j++) ok = ok && v[j].w == tag;
                if (__all_sync(0xffffffffu, ok) || !live) break;
                if (++it > SPIN_LIMIT) __trap();
            }
            CLK(16);
            float a0 = 0.f, a1 = 0.f, a2 = 0.f;
#pragma unroll
            for (int j = 0; j < 6; j++) { a0 += __uint_as_float(v[j].x); a1 += __uint_as_float(v[j].y); a2 += __uint_as_float(v[j].z); }
#pragma unroll
            for (int o = 2; o <= 16; o <<= 1) {
                a0 += __shfl_xor_sync(0xffffffffu, a0, o);
                a1 += __shfl_xor_sync(0xffffffffu, a1, o);
                a2 += __shfl_xor_sync(0xffffffffu, a2, o);
            }
            const float gx = own[8 + (lane & 7)], xx = own[24 + (lane & 7)];
            const float t0 = __shfl_sync(0xffffffffu, a0, lane >= 3), t1 = __shfl_sync(0xffffffffu, a1, lane >= 3);
            const float sum = (lane == 0 || lane == 3) ? t0 : (lane == 2 ? a2 : t1);
            const float y = xx + bfr(gx * bfr(sum));
            if (live && lane < 5) reinterpret_cast<uint16_t*>(out)[cta * 5 + lane] = (uint16_t)(__float_as_uint(bfr(y)) >> 16);
            if (live && cta == 0 && lane == 0) g_epoch = tag;
        }
        CLK(17);
        if (live) { TS(18); break; }
        live = true;
    }
    }
}

typedef CUresult (*EncodeFn)(CUtensorMap*, CUtensorMapDataType, cuuint32_t, void*, const cuuint64_t*, const cuuint64_t*,
                             const cuuint32_t*, const cuuint32_t*, CUtensorMapInterleave, CUtensorMapSwizzle,
                             CUtensorMapL2promotion, CUtensorMapFloatOOBfill);

void make_map(EncodeFn enc, CUtensorMap* tm, const void* ptr, uint64_t cols, uint64_t rows, uint32_t box_c, uint32_t box_r,
              CUtensorMapSwizzle sw, CUtensorMapL2promotion prom) {
    cuuint64_t dims[2] = {cols, rows};
    cuuint64_t strides[1] = {cols * 2};
    cuuint32_t box[2] = {box_c, box_r};
    cuuint32_t es[2] = {1, 1};
    enc(tm, CU_TENSOR_MAP_DATA_TYPE_BFLOAT16, 2, const_cast<void*>(ptr), dims, strides, box, es,
        CU_TENSOR_MAP_INTERLEAVE_NONE, sw, prom, CU_TENSOR_MAP_FLOAT_OOB_FILL_NONE);
}

}

extern "C" void kernel_launch(void* const* d_in, const int* in_sizes, int n_in, void* d_out, int out_size) {
    (void)in_sizes; (void)n_in; (void)out_size;
    static EncodeFn enc = nullptr;
    static int num_sms = 0;
    if (!enc) {
        void* fn = nullptr;
        cudaDriverEntryPointQueryResult qr;
        cudaGetDriverEntryPoint("cuTensorMapEncodeTiled", &fn, cudaEnableDefault, &qr);
        enc = (EncodeFn)fn;
        cudaDeviceGetAttribute(&num_sms, cudaDevAttrMultiProcessorCount, 0);
        cudaFuncSetAttribute(fused_decode_kernel, cudaFuncAttributeMaxDynamicSharedMemorySize, SM_TOTAL);
    }
    CUtensorMap tmK, tmV, tmMod, tmWq, tmWo, tmW1, tmW3, tmW2;
    const uint64_t kv_lines = (uint64_t)NH * SK * 3;
    make_map(enc, &tmK, d_in[1], 64, kv_lines, 64, 96, CU_TENSOR_MAP_SWIZZLE_128B, CU_TENSOR_MAP_L2_PROMOTION_L2_128B);
    make_map(enc, &tmV, d_in[2], 64, kv_lines, 64, 96, CU_TENSOR_MAP_SWIZZLE_128B, CU_TENSOR_MAP_L2_PROMOTION_L2_128B);
    make_map(enc, &tmWq, d_in[3], NH * DH, D, 48, 128, CU_TENSOR_MAP_SWIZZLE_NONE, CU_TENSOR_MAP_L2_PROMOTION_L2_128B);
    make_map(enc, &tmWo, d_in[4], D, NH * DH, 64, 48, CU_TENSOR_MAP_SWIZZLE_128B, CU_TENSOR_MAP_L2_PROMOTION_L2_128B);
    make_map(enc, &tmW1, d_in[6], FF, D, 16, 160, CU_TENSOR_MAP_SWIZZLE_32B, CU_TENSOR_MAP_L2_PROMOTION_L2_128B);
    make_map(enc, &tmW3, d_in[7], FF, D, 16, 160, CU_TENSOR_MAP_SWIZZLE_32B, CU_TENSOR_MAP_L2_PROMOTION_L2_128B);
    make_map(enc, &tmW2, d_in[8], D, FF, 64, 16, CU_TENSOR_MAP_SWIZZLE_128B, CU_TENSOR_MAP_L2_PROMOTION_L2_128B);
    make_map(enc, &tmMod, d_in[10], 6 * D, D, 32, 160, CU_TENSOR_MAP_SWIZZLE_64B, CU_TENSOR_MAP_L2_PROMOTION_L2_128B);
    int grid = num_sms < MAXG ? num_sms : MAXG;
    fused_decode_kernel<<<grid, NTHREADS, SM_TOTAL, cudaStreamPerThread>>>(
        tmK, tmV, tmMod, tmWq, tmWo, tmW1, tmW3, tmW2, (const __nv_bfloat16*)d_in[0], (const __nv_bfloat16*)d_in[9],
        (__nv_bfloat16*)d_out);
}
```

```cpp
#include <cuda_runtime.h>
#include <cuda_bf16.h>
#include <cuda.h>
#include <stdint.h>

namespace {

constexpr int D = 640, NH = 32, SK = 8192, DH = 192, FF = 1536;
constexpr int NG = 4;
constexpr int GH = 7;
constexpr int NGLOB = NH - NG * GH;
constexpr int NQH = GH + NGLOB;
constexpr int TILE = 32;
constexpr int TPH = SK / TILE;
constexpr int GT = GH * TPH;
constexpr int PT = NGLOB * TPH;
constexpr int CHUNK = TILE * DH * 2;
#define P_NSLOT 8
#define P_WIN 3
#define P_URG 0
#define P_HOLD 3
#define P_TWIN P_WIN
#define P_PRO0 4
#define P_DLY 450
constexpr int NSLOT = P_NSLOT;
constexpr int WIN = P_WIN;
#define P_NBUF 3
constexpr int NBUF = P_NBUF;
constexpr int MAXG = 132;
constexpr int NTHREADS = 288;
constexpr float NEG_BIG = -3.402823466e38f;

constexpr int SM_WMOD = 0;
constexpr int SM_WQ = 40960;
constexpr int SM_WO = 0;
constexpr int SM_W1 = 61440;
constexpr int SM_W3 = 81920;
constexpr int SM_RING = 102400;
constexpr int SM_MISC = SM_RING + NSLOT * CHUNK;
constexpr int SM_BARS = SM_MISC;
constexpr int SM_META = SM_BARS + 512;
constexpr int SM_Q = SM_META + 128;
constexpr int SM_SC = SM_Q + NQH * DH * 2;
constexpr int SM_H = SM_SC + 1280;
constexpr int SM_X = SM_H + 1280;
constexpr int SM_CB = SM_X + 1280;
constexpr int SM_SB = SM_CB + 1280;
constexpr int SM_OWN = SM_SB + 1280;
constexpr int SM_RED = SM_OWN + 128;
constexpr int SM_MERGE = SM_RED + 2048;
constexpr int SM_STAGE = SM_MERGE + NBUF * 3200;
constexpr int SM_X2 = SM_STAGE + 2560;
constexpr int SM_FIN = SM_X2 + 2560;
constexpr int SM_TOTAL = SM_FIN + 512;
static_assert(SM_TOTAL <= 232448, "shared memory budget");

constexpr int B_FULL = 0;
constexpr int B_EMPTY = 8;
constexpr int B_MOD = 16;
constexpr int B_WQ = 20;
constexpr int B_WO = 25;
constexpr int B_W1 = 30;
constexpr int B_W3 = 32;
constexpr int B_W2 = 34;
constexpr int B_PRO = 36, B_DUMMY = 37;
constexpr int B_FLF = 40, B_FLE = 44;
constexpr int B_LAST = 48;
static_assert(NSLOT <= 8 && NSLOT >= 6 && WIN <= 4 && WIN <= NSLOT - 3, "barrier map / end markers vs window");
constexpr uint32_t META_END = 0x10000u;

__device__ unsigned g_epoch;
__device__ unsigned g_ctr[2][(NG + 1) * 32];
__device__ __align__(128) unsigned long long g_mod[1920];
__device__ __align__(128) unsigned long long g_q[3072];
__device__ __align__(128) uint4 g_hdr[NH][MAXG];
__device__ __align__(128) uint4 g_dat[NH][MAXG][64];
__device__ __align__(128) uint4 g_h1[128][128][2];
__device__ __align__(128) uint4 g_x2[128][2];
__device__ __align__(128) uint4 g_h3[128][96][2];

#define TS(k) do {} while (0)
#define DBG(k) do {} while (0)
#define CLK(k) do {} while (0)

__device__ __forceinline__ uint32_t smem_u32(const void* p) { return (uint32_t)__cvta_generic_to_shared(p); }
__device__ __forceinline__ void mbar_init(uint32_t bar, uint32_t cnt) {
    asm volatile("mbarrier.init.shared::cta.b64 [%0], %1;" ::"r"(bar), "r"(cnt) : "memory");
}
__device__ __forceinline__ void mbar_expect_tx(uint32_t bar, uint32_t bytes) {
    asm volatile("mbarrier.arrive.expect_tx.shared::cta.b64 _, [%0], %1;" ::"r"(bar), "r"(bytes) : "memory");
}
__device__ __forceinline__ void mbar_arrive(uint32_t bar) {
    asm volatile("mbarrier.arrive.shared::cta.b64 _, [%0];" ::"r"(bar) : "memory");
}
constexpr uint32_t SPIN_LIMIT = 1u << 22;
__device__ __forceinline__ void mbar_wait(uint32_t bar, uint32_t parity) {
    asm volatile(
        "{\n.reg .pred p;\n.reg .u32 c;\nmov.u32 c, 0;\n"
        "LW:\nmbarrier.try_wait.parity.shared::cta.b64 p, [%0], %1;\n@p bra LD;\n"
        "add.u32 c, c, 1;\nsetp.lt.u32 p, c, 0x400000;\n@p bra LW;\ntrap;\nLD:\n}" ::"r"(bar), "r"(parity)
        : "memory");
}
__device__ __forceinline__ uint32_t mbar_try(uint32_t bar, uint32_t parity) {
    uint32_t ok;
    asm volatile("{\n.reg .pred p;\nmbarrier.try_wait.parity.shared::cta.b64 p, [%1], %2;\nselp.u32 %0, 1, 0, p;\n}"
                 : "=r"(ok) : "r"(bar), "r"(parity) : "memory");
    return ok;
}
__device__ __forceinline__ void mbar_wait3(uint32_t b0, uint32_t b1, uint32_t b2) {
    asm volatile(
        "{\n.reg .pred p, q, r;\n.reg .u32 c;\nmov.u32 c, 0;\n"
        "LW:\nmbarrier.try_wait.parity.shared::cta.b64 p, [%0], 0;\n"
        "mbarrier.try_wait.parity.shared::cta.b64 q, [%1], 0;\n"
        "mbarrier.try_wait.parity.shared::cta.b64 r, [%2], 0;\n"
        "and.pred p, p, q;\nand.pred p, p, r;\n@p bra LD;\n"
        "add.u32 c, c, 1;\nsetp.lt.u32 p, c, 0x400000;\n@p bra LW;\ntrap;\nLD:\n}" ::"r"(b0), "r"(b1), "r"(b2)
        : "memory");
}
__device__ __forceinline__ void tma2d(uint32_t dst, const CUtensorMap* tm, int c0, int c1, uint32_t bar) {
    asm volatile(
        "cp.async.bulk.tensor.2d.shared::cluster.global.mbarrier::complete_tx::bytes [%0], [%1, {%3, %4}], [%2];" ::"r"(dst),
        "l"(tm), "r"(bar), "r"(c0), "r"(c1)
        : "memory");
}
__device__ __forceinline__ void tma2d_hint(uint32_t dst, const CUtensorMap* tm, int c0, int c1, uint32_t bar, uint64_t pol) {
    asm volatile(
        "cp.async.bulk.tensor.2d.shared::cluster.global.mbarrier::complete_tx::bytes.L2::cache_hint [%0], [%1, {%3, %4}], [%2], %5;" ::"r"(dst),
        "l"(tm), "r"(bar), "r"(c0), "r"(c1), "l"(pol)
        : "memory");
}
__device__ __forceinline__ void prefetch_tm(const CUtensorMap* tm) {
    asm volatile("prefetch.tensormap [%0];" ::"l"(tm) : "memory");
}
__device__ __forceinline__ void ldsm4(uint32_t (&r)[4], uint32_t addr) {
    asm volatile("ldmatrix.sync.aligned.m8n8.x4.shared.b16 {%0,%1,%2,%3}, [%4];"
                 : "=r"(r[0]), "=r"(r[1]), "=r"(r[2]), "=r"(r[3])
                 : "r"(addr));
}
__device__ __forceinline__ void ldsm4t(uint32_t (&r)[4], uint32_t addr) {
    asm volatile("ldmatrix.sync.aligned.m8n8.x4.trans.shared.b16 {%0,%1,%2,%3}, [%4];"
                 : "=r"(r[0]), "=r"(r[1]), "=r"(r[2]), "=r"(r[3])
                 : "r"(addr));
}
__device__ __forceinline__ void mma16816(float (&d)[4], const uint32_t (&a)[4], uint32_t b0, uint32_t b1) {
    asm volatile(
        "mma.sync.aligned.m16n8k16.row.col.f32.bf16.bf16.f32 {%0,%1,%2,%3}, {%4,%5,%6,%7}, {%8,%9}, {%0,%1,%2,%3};"
        : "+f"(d[0]), "+f"(d[1]), "+f"(d[2]), "+f"(d[3])
        : "r"(a[0]), "r"(a[1]), "r"(a[2]), "r"(a[3]), "r"(b0), "r"(b1));
}
__device__ __forceinline__ void bar_cons() { asm volatile("bar.sync 1, 256;" ::: "memory"); }
__device__ __forceinline__ void spin(int cycles) {
    long long t0 = clock64();
    while (clock64() - t0 < cycles) {}
}

__device__ __forceinline__ float bfr(float x) {
    uint32_t r;
    asm("cvt.rn.bf16x2.f32 %0, %1, %2;" : "=r"(r) : "f"(x), "f"(0.0f));
    return __uint_as_float(r);
}
__device__ __forceinline__ uint32_t pack_bf(float lo, float hi) {
    __nv_bfloat162 t = __floats2bfloat162_rn(lo, hi);
    return *reinterpret_cast<uint32_t*>(&t);
}
__device__ __forceinline__ float bf_lo(uint32_t v) { return __uint_as_float(v << 16); }
__device__ __forceinline__ float bf_hi(uint32_t v) { return __uint_as_float(v & 0xffff0000u); }

__device__ __forceinline__ void st_pk8(unsigned long long* p, uint32_t v, uint32_t tag) {
    unsigned long long w = ((unsigned long long)tag << 32) | v;
    asm volatile("st.relaxed.gpu.global.b64 [%0], %1;" ::"l"(p), "l"(w) : "memory");
}
__device__ __forceinline__ unsigned long long ld_raw8(const unsigned long long* p) {
    unsigned long long w;
    asm volatile("ld.relaxed.gpu.global.b64 %0, [%1];" : "=l"(w) : "l"(p) : "memory");
    return w;
}
template <int N>
__device__ __forceinline__ void poll8(const unsigned long long* base, const int (&off)[N], uint32_t (&val)[N], uint32_t tag) {
    uint32_t it = 0;
    while (true) {
        unsigned long long w[N];
#pragma unroll
        for (int i = 0; i < N; i++) w[i] = ld_raw8(base + off[i]);
        bool ok = true;
#pragma unroll
        for (int i = 0; i < N; i++) { ok = ok && ((uint32_t)(w[i] >> 32) == tag); val[i] = (uint32_t)w[i]; }
        if (__all_sync(0xffffffffu, ok)) break;
        if (++it > SPIN_LIMIT) __trap();
    }
}
__device__ __forceinline__ void st_pk16(uint4* p, uint32_t a, uint32_t b, uint32_t c, uint32_t tag) {
    asm volatile(
        "{\n.reg .b128 t;\n.reg .b64 lo, hi;\nmov.b64 lo, {%1, %2};\nmov.b64 hi, {%3, %4};\nmov.b128 t, {lo, hi};\n"
        "st.relaxed.gpu.global.b128 [%0], t;\n}" ::"l"(p), "r"(a), "r"(b), "r"(c), "r"(tag)
        : "memory");
}
template <int OFF = 0>
__device__ __forceinline__ uint4 ld_raw16p(const uint4* p, uint32_t on) {
    uint4 v;
    asm volatile(
        "{\n.reg .b128 t;\n.reg .b64 lo, hi;\n.reg .pred q;\nsetp.ne.u32 q, %5, 0;\n"
        "mov.b64 lo, 0;\nmov.b128 t, {lo, lo};\n"
        "@q ld.relaxed.gpu.global.b128 t, [%4 + %6];\nmov.b128 {lo, hi}, t;\n"
        "mov.b64 {%0, %1}, lo;\nmov.b64 {%2, %3}, hi;\n}"
        : "=r"(v.x), "=r"(v.y), "=r"(v.z), "=r"(v.w)
        : "l"(p), "r"(on), "n"(OFF * 16)
        : "memory");
    return v;
}
template <int OFF>
__device__ __forceinline__ void ld_fresh16(uint4& v, const uint4* p, uint32_t tag, uint32_t on) {
    asm volatile(
        "{\n.reg .b128 t;\n.reg .b64 lo, hi;\n.reg .pred q;\nsetp.ne.u32 q, %3, %5;\nsetp.ne.and.u32 q, %6, 0, q;\n"
        "mov.b64 lo, {%0, %1};\nmov.b64 hi, {%2, %3};\nmov.b128 t, {lo, hi};\n"
        "@q ld.relaxed.gpu.global.b128 t, [%4 + %7];\nmov.b128 {lo, hi}, t;\n"
        "mov.b64 {%0, %1}, lo;\nmov.b64 {%2, %3}, hi;\n}"
        : "+r"(v.x), "+r"(v.y), "+r"(v.z), "+r"(v.w)
        : "l"(p), "r"(tag), "r"(on), "n"(OFF * 16)
        : "memory");
}
template <int N, int STRIDE, int I = 0>
struct FreshN {
    static __device__ __forceinline__ void run(uint4* v, const uint4* p, uint32_t tag, bool live, int base, int step, int lim) {
        ld_fresh16<I * STRIDE>(v[I], p, tag, live && base + step * I < lim);
        FreshN<N, STRIDE, I + 1>::run(v, p, tag, live, base, step, lim);
    }
};
template <int N, int STRIDE>
struct FreshN<N, STRIDE, N> {
    static __device__ __forceinline__ void run(uint4*, const uint4*, uint32_t, bool, int, int, int) {}
};
template <int N, int STRIDE, int I = 0>
struct LoadN {
    static __device__ __forceinline__ void run(uint4* v, const uint4* p, bool live, int base, int step, int lim) {
        v[I] = ld_raw16p<I * STRIDE>(p, live && base + step * I < lim);
        LoadN<N, STRIDE, I + 1>::run(v, p, live, base, step, lim);
    }
};
template <int N, int STRIDE>
struct LoadN<N, STRIDE, N> {
    static __device__ __forceinline__ void run(uint4*, const uint4*, bool, int, int, int) {}
};
__device__ __forceinline__ uint4 poll16(const uint4* p, uint32_t tag, bool live) {
    uint32_t it = 0;
    uint4 v;
    while (true) {
        v = ld_raw16p(p, live);
        if (__all_sync(0xffffffffu, v.w == tag) || !live) break;
        if (++it > SPIN_LIMIT) __trap();
    }
    return v;
}
__device__ __forceinline__ void st_zero16(void* p) {
    asm volatile("st.relaxed.gpu.global.v4.u32 [%0], {%1, %1, %1, %1};" ::"l"(p), "r"(0u) : "memory");
}
__device__ __forceinline__ float ex2(float x) {
    float y;
    asm("ex2.approx.ftz.f32 %0, %1;" : "=f"(y) : "f"(x));
    return y;
}
__device__ __forceinline__ float fsqrt(float x) {
    float y;
    asm("sqrt.approx.f32 %0, %1;" : "=f"(y) : "f"(x));
    return y;
}
constexpr float LOG2E = 1.4426950408889634f;
__device__ __forceinline__ float silu(float a) { return __fdividef(a, 1.0f + ex2(-a * LOG2E)); }
__device__ __forceinline__ float warp_sum(float v) {
#pragma unroll
    for (int o = 16; o > 0; o >>= 1) v += __shfl_xor_sync(0xffffffffu, v, o);
    return v;
}

__device__ __forceinline__ void ln_stats(const float (&v)[20], float& mean_b, float& den_b) {
    float s = 0.f;
#pragma unroll
    for (int i = 0; i < 20; i++) s += v[i];
    s = warp_sum(s);
    float mean = s * (1.0f / 640.0f);
    float q = 0.f;
#pragma unroll
    for (int i = 0; i < 20; i++) { float d = v[i] - mean; q += d * d; }
    q = warp_sum(q);
    float var_b = bfr(q * (1.0f / 640.0f));
    mean_b = bfr(mean);
    den_b = bfr(fsqrt(bfr(var_b + 1e-5f)));
}

struct Window {
    uint32_t bar[WIN];
    uint32_t par[WIN];
    __device__ __forceinline__ void init(uint32_t dummy) {
#pragma unroll
        for (int i = 0; i < WIN; i++) { bar[i] = dummy; par[i] = 1; }
    }
    __device__ __forceinline__ void push_tail(uint32_t b, uint32_t p) {
#pragma unroll
        for (int i = 1; i <= WIN - P_TWIN; i++) mbar_wait(bar[i], par[i]);
        push(b, p);
    }
    __device__ __forceinline__ void push(uint32_t b, uint32_t p, bool wait = true) {
        if (wait) mbar_wait(bar[0], par[0]);
#pragma unroll
        for (int i = 0; i + 1 < WIN; i++) { bar[i] = bar[i + 1]; par[i] = par[i + 1]; }
        bar[WIN - 1] = b; par[WIN - 1] = p;
    }
};

__global__ void __launch_bounds__(NTHREADS, 1)
fused_decode_kernel(const __grid_constant__ CUtensorMap tmK, const __grid_constant__ CUtensorMap tmV,
                    const __grid_constant__ CUtensorMap tmMod, const __grid_constant__ CUtensorMap tmWq,
                    const __grid_constant__ CUtensorMap tmWo, const __grid_constant__ CUtensorMap tmW1,
                    const __grid_constant__ CUtensorMap tmW3, const __grid_constant__ CUtensorMap tmW2,
                    const __nv_bfloat16* __restrict__ x_in, const __nv_bfloat16* __restrict__ c_in,
                    __nv_bfloat16* __restrict__ out) {
    extern __shared__ __align__(1024) uint8_t smem[];
    const uint32_t sb = smem_u32(smem);
    const int tid = threadIdx.x, wid = tid >> 5, lane = tid & 31;
    const int cta = blockIdx.x, G = gridDim.x;
    const int grp = cta % NG, rank = cta / NG;
    const uint32_t bars = sb + SM_BARS;
    auto BAR = [&](int i) { return bars + 8u * i; };
    volatile uint32_t* meta = reinterpret_cast<volatile uint32_t*>(smem + SM_META);

    if (wid == 8) {
        Window win;
        unsigned epoch = 0;
        int nmod = 0, nwq = 0, pro_i = 0;
        auto pro_issue = [&](int i, bool wait) {
            const bool is_mod = cta < 40 ? i < nmod : i >= nwq;
            const int j = cta < 40 ? (is_mod ? i : i - nmod) : (is_mod ? i - nwq : i);
            const uint32_t bar = BAR((is_mod ? B_MOD : B_WQ) + j);
            win.push(bar, 0, wait);
            mbar_expect_tx(bar, is_mod ? 10240 : 12288);
            if (is_mod) tma2d(sb + SM_WMOD + j * 10240, &tmMod, cta * 32, j * 160, bar);
            else tma2d(sb + SM_WQ + j * 12288, &tmWq, cta * 48, j * 128, bar);
        };
        if (tid == 256) {
            TS(0);
            if (sb & 1023u) __trap();
            asm volatile("ld.relaxed.gpu.global.u32 %0, [%1];" : "=r"(epoch) : "l"(&g_epoch) : "memory");
            prefetch_tm(&tmMod); prefetch_tm(&tmWq); prefetch_tm(&tmK); prefetch_tm(&tmV);
#pragma unroll
            for (int i = 0; i < 9; i++) mbar_init(BAR(B_MOD + i), 1);
            mbar_init(BAR(B_DUMMY), 1);
            asm volatile("fence.mbarrier_init.release.cluster;" ::: "memory");
            asm volatile("fence.proxy.async.shared::cta;" ::: "memory");
            win.init(BAR(B_DUMMY));
            nmod = cta < 120 ? 4 : 0; nwq = cta < 128 ? 5 : 0;
            pro_i = 0;
#pragma unroll 1
            for (; pro_i < P_PRO0 && pro_i < nmod + nwq; pro_i++) pro_issue(pro_i, false);
#pragma unroll 1
            for (int i = 0; i < B_LAST; i++) {
                if ((i >= B_MOD && i < B_MOD + 9) || i == B_DUMMY) continue;
                int cnt = (i >= B_EMPTY && i < B_MOD) ? 2 : ((i >= B_FLF && i < B_FLE) ? 4 : 1);
                mbar_init(BAR(i), cnt);
            }
            asm volatile("fence.mbarrier_init.release.cluster;" ::: "memory");
            asm volatile("fence.proxy.async.shared::cta;" ::: "memory");
        }
        __syncwarp();
        __syncthreads();
        if (tid == 256) {
            prefetch_tm(&tmWo); prefetch_tm(&tmW1); prefetch_tm(&tmW3); prefetch_tm(&tmW2);
            unsigned* ctr = &g_ctr[epoch & 1][grp * 32];
            unsigned* gctr = &g_ctr[epoch & 1][NG * 32];
            if (cta == 0) {
                for (int g = 0; g <= NG; g++) g_ctr[(epoch + 1) & 1][g * 32] = 0;
            }
            unsigned pend = atomicAdd(ctr, 1);
#pragma unroll 1
            for (; pro_i < nmod + nwq; pro_i++) pro_issue(pro_i, true);
            uint64_t pol;
            asm volatile("createpolicy.fractional.L2::evict_first.b64 %0, 1.0;" : "=l"(pol));
            int s = 0; uint32_t par = 0;
            int ntiles = 0, run = -1, last_head = -1;
            bool glob = false;
#pragma unroll 1
            while (true) {
                unsigned t = pend;
                DBG(8);
                if (!glob && t >= (unsigned)GT) { glob = true; t = atomicAdd(gctr, 1); }
                if (glob && t >= (unsigned)PT) break;
                pend = atomicAdd(glob ? gctr : ctr, 1);
                ntiles++;
                const int hl = t / TPH, tile = t % TPH;
                const int head = glob ? NG * GH + hl : grp * GH + hl;
                const int qidx = glob ? GH + hl : hl;
                if (head != last_head) { last_head = head; run++; meta[16 + run] = head; }
                const int line0 = (head * SK + tile * TILE) * 3;
                const bool urgent = glob && t >= (unsigned)(PT - P_URG);
#pragma unroll 1
                for (int kv = 0; kv < 2; kv++) {
                    win.push(BAR(B_FULL + s), par, !urgent);
                    mbar_wait(BAR(B_EMPTY + s), par ^ 1);
                    meta[s] = run | (qidx << 8);
                    mbar_expect_tx(BAR(B_FULL + s), CHUNK);
                    tma2d_hint(sb + SM_RING + s * CHUNK, kv ? &tmV : &tmK, 0, line0, BAR(B_FULL + s), pol);
                    DBG(6 + kv);
                    if (++s == NSLOT) { s = 0; par ^= 1; }
                }
            }
            TS(5);
            meta[16 + run + 1] = 0xFFu;
#pragma unroll 1
            for (int e = 0; e < 2; e++) {
                mbar_wait(BAR(B_EMPTY + s), par ^ 1);
                meta[s] = (run + 1) | META_END;
                mbar_arrive(BAR(B_FULL + s));
                if (++s == NSLOT) { s = 0; par ^= 1; }
                if (++s == NSLOT) { s = 0; par ^= 1; }
            }
#pragma unroll
            for (int i = 0; i < WIN - P_HOLD; i++) mbar_wait(win.bar[i], win.par[i]);
            TS(12);
            if (cta < 128) {
                mbar_wait(BAR(B_PRO), 0);
#pragma unroll 1
                for (int i = 0; i < 5; i++) {
                    win.push_tail(BAR(B_WO + i), 0);
                    mbar_expect_tx(BAR(B_WO + i), 12288);
                    tma2d(sb + SM_WO + (2 * i) * 6144, &tmWo, (2 * i) * 64, cta * 48, BAR(B_WO + i));
                    tma2d(sb + SM_WO + (2 * i + 1) * 6144, &tmWo, (2 * i + 1) * 64, cta * 48, BAR(B_WO + i));
                }
                if (cta < 96) {
#pragma unroll 1
                    for (int i = 0; i < 4; i++) {
                        const int m = i & 1, hf = i >> 1;
                        const uint32_t bar = BAR((m ? B_W3 : B_W1) + hf);
                        const uint32_t dst = sb + (m ? SM_W3 : SM_W1) + hf * 10240;
                        const CUtensorMap* tm = m ? &tmW3 : &tmW1;
                        win.push_tail(bar, 0);
                        mbar_expect_tx(bar, 10240);
                        tma2d(dst, tm, cta * 16, hf * 320, bar);
                        tma2d(dst + 5120, tm, cta * 16, hf * 320 + 160, bar);
                    }
#pragma unroll 1
                    for (int i = 0; i < 2; i++) {
                        win.push_tail(BAR(B_W2 + i), 0);
                        mbar_wait(BAR(B_EMPTY + s), par ^ 1);
                        meta[10 + i] = s;
                        mbar_expect_tx(BAR(B_W2 + i), 10240);
#pragma unroll 1
                        for (int b = 0; b < 5; b++)
                            tma2d(sb + SM_RING + s * CHUNK + b * 2048, &tmW2, (5 * i + b) * 64, cta * 16, BAR(B_W2 + i));
                        if (++s == NSLOT) { s = 0; par ^= 1; }
                    }
                }
            }
            TS(6);
        }
    } else {
    const int g4 = lane >> 2, j4 = lane & 3, mi = lane >> 3, l8 = lane & 7;
    uint32_t* sc32 = reinterpret_cast<uint32_t*>(smem + SM_SC);
    uint32_t* h32 = reinterpret_cast<uint32_t*>(smem + SM_H);
    uint32_t* x32 = reinterpret_cast<uint32_t*>(smem + SM_X);
    uint32_t* q32 = reinterpret_cast<uint32_t*>(smem + SM_Q);
    float* red = reinterpret_cast<float*>(smem + SM_RED);
    float* stage = reinterpret_cast<float*>(smem + SM_STAGE);
    float* own = reinterpret_cast<float*>(smem + SM_OWN);

    uint32_t tag;
    bool live = true;
    if (wid == 9) { __syncthreads(); tag = meta[8]; live = false; } else {
    {
        const uint32_t* cg = reinterpret_cast<const uint32_t*>(c_in);
        const uint32_t* xg = reinterpret_cast<const uint32_t*>(x_in);
        uint32_t c0 = cg[tid], x0 = xg[tid], c1 = 0, x1 = 0;
        if (tid < 64) { c1 = cg[256 + tid]; x1 = xg[256 + tid]; }
        unsigned epoch = 0;
        if (tid == 0) asm volatile("ld.relaxed.gpu.global.u32 %0, [%1];" : "=r"(epoch) : "l"(&g_epoch) : "memory");
        if (cta < 120 && tid < 8) st_zero16(reinterpret_cast<uint4*>(&g_mod[cta * 16]) + tid);
        if (cta < 128 && tid >= 32 && tid < 44) st_zero16(reinterpret_cast<uint4*>(&g_q[cta * 24]) + (tid - 32));
        if (cta < 128) {
            if (tid >= 64 && tid < 66) st_zero16(&g_x2[cta][tid - 64]);
            st_zero16(&g_h1[tid >> 1][cta][tid & 1]);
            if (cta < 96) st_zero16(&g_h3[tid >> 1][cta][tid & 1]);
        }
#pragma unroll 1
        for (int f = tid >> 6; f < NQH; f += 4) {
            const int head = f < GH ? grp * GH + f : NG * GH + (f - GH);
            const int idx = f < GH ? rank : cta;
            st_zero16(&g_dat[head][idx][tid & 63]);
            if ((tid & 63) == 0) st_zero16(&g_hdr[head][idx]);
        }
        sc32[tid] = pack_bf(silu(bf_lo(c0)), silu(bf_hi(c0))); x32[tid] = x0;
        if (tid < 64) { sc32[256 + tid] = pack_bf(silu(bf_lo(c1)), silu(bf_hi(c1))); x32[256 + tid] = x1; }
        if (tid == 0) meta[8] = epoch + 1;
    }
    __syncthreads();
    tag = meta[8];

    float mean_x = 0.f, rden_x = 1.f;
    if (cta < 128) {
        float xv[20];
#pragma unroll
        for (int i = 0; i < 10; i++) { uint32_t v = x32[lane + 32 * i]; xv[2 * i] = bf_lo(v); xv[2 * i + 1] = bf_hi(v); }
        float den;
        ln_stats(xv, mean_x, den);
        rden_x = __fdividef(1.0f, den);
    }

#pragma unroll 1
    for (int step = 0; step < 2; step++) {
    if (wid >= 4 && (step == 0 ? cta < 40 : (cta >= 40 && cta < 120))) {
        const int w4 = wid - 4;
        float acc[2][4] = {};
        const uint32_t base = sb + SM_WMOD + w4 * 10240;
        mbar_wait(BAR(B_MOD + w4), 0);
#pragma unroll
        for (int hf = 0; hf < 2; hf++) {
            uint32_t a[5][2][4], bb[5][2];
#pragma unroll
            for (int ks = 0; ks < 5; ks++) {
                const int r0 = w4 * 160 + hf * 80 + ks * 16;
                bb[ks][0] = sc32[(r0 >> 1) + j4]; bb[ks][1] = sc32[(r0 >> 1) + 4 + j4];
                const int r = hf * 80 + ks * 16 + l8 + 8 * (mi >> 1);
#pragma unroll
                for (int mt = 0; mt < 2; mt++) ldsm4t(a[ks][mt], base + r * 64 + (((2 * mt + (mi & 1)) ^ ((r >> 1) & 3)) << 4));
            }
#pragma unroll
            for (int ks = 0; ks < 5; ks++) { mma16816(acc[0], a[ks][0], bb[ks][0], bb[ks][1]); mma16816(acc[1], a[ks][1], bb[ks][0], bb[ks][1]); }
        }
        float* red2 = reinterpret_cast<float*>(smem + SM_FIN);
        if (j4 == 0) {
#pragma unroll
            for (int mt = 0; mt < 2; mt++) { red2[w4 * 32 + mt * 16 + g4] = acc[mt][0]; red2[w4 * 32 + mt * 16 + 8 + g4] = acc[mt][2]; }
        }
        asm volatile("bar.sync 3, 128;" ::: "memory");
        if (wid == 4) {
            float v = (red2[lane] + red2[32 + lane]) + (red2[64 + lane] + red2[96 + lane]);
            float o = __shfl_down_sync(0xffffffffu, v, 1);
            if (!(lane & 1)) st_pk8(&g_mod[cta * 16 + (lane >> 1)], pack_bf(v, o), tag);
            if (step == 1 && lane == 0) mbar_arrive(BAR(B_PRO));
        }
        TS(1);
    }
    if (step == 1) break;
    if (cta < 128) {
        {
            const int off[4] = {tid, 320 + tid, tid < 64 ? 256 + tid : tid, tid < 64 ? 576 + tid : 320 + tid};
            uint32_t val[4];
            poll8<4>(g_mod, off, val, tag);
#pragma unroll
            for (int rep = 0; rep < 2; rep++) {
                int p = tid + rep * 256;
                if (p < 320) {
                    uint32_t sa = val[2 * rep], ca = val[2 * rep + 1];
                    uint32_t xx = x32[p];
                    float n0 = bfr(bfr(bf_lo(xx) - mean_x) * rden_x), n1 = bfr(bfr(bf_hi(xx) - mean_x) * rden_x);
                    float h0 = bfr(n0 * bfr(1.0f + bf_lo(ca))) + bf_lo(sa);
                    float h1 = bfr(n1 * bfr(1.0f + bf_hi(ca))) + bf_hi(sa);
                    h32[p] = pack_bf(h0, h1);
                }
            }
        }
        bar_cons();
        TS(2);
        float acc[3][4] = {};
        uint32_t a[5][3][4], bb[5][2];
#pragma unroll
        for (int ks = 0; ks < 5; ks++) {
            const int r0 = wid * 80 + ks * 16;
            bb[ks][0] = h32[(r0 >> 1) + j4]; bb[ks][1] = h32[(r0 >> 1) + 4 + j4];
        }
        mbar_wait(BAR(B_WQ + ((wid * 80) >> 7)), 0);
        mbar_wait(BAR(B_WQ + ((wid * 80 + 79) >> 7)), 0);
#pragma unroll
        for (int ks = 0; ks < 5; ks++) {
            const int r = wid * 80 + ks * 16 + l8 + 8 * (mi >> 1);
#pragma unroll
            for (int mt = 0; mt < 3; mt++) ldsm4t(a[ks][mt], sb + SM_WQ + r * 96 + ((2 * mt + (mi & 1)) << 4));
        }
#pragma unroll
        for (int ks = 0; ks < 5; ks++) {
#pragma unroll
            for (int mt = 0; mt < 3; mt++) mma16816(acc[mt], a[ks][mt], bb[ks][0], bb[ks][1]);
        }
        if (j4 == 0) {
#pragma unroll
            for (int mt = 0; mt < 3; mt++) { red[wid * 64 + mt * 16 + g4] = acc[mt][0]; red[wid * 64 + mt * 16 + 8 + g4] = acc[mt][2]; }
        }
        bar_cons();
        if (tid < 64) {
            float v = 0.f;
            if (tid < 48) {
#pragma unroll
                for (int w = 0; w < 8; w++) v += red[w * 64 + tid];
            }
            float o = __shfl_down_sync(0xffffffffu, v, 1);
            if (tid < 48 && !(tid & 1)) st_pk8(&g_q[cta * 24 + (tid >> 1)], pack_bf(v, o), tag);
        }
        TS(3);
    }
    {
        int off[5];
#pragma unroll
        for (int j = 0; j < 5; j++) {
            int p = tid + 256 * j;
            if (p >= NQH * 96) p = tid;
            off[j] = p < GH * 96 ? grp * GH * 96 + p : NG * GH * 96 + (p - GH * 96);
        }
        uint32_t val[5];
        poll8<5>(g_q, off, val, tag);
#pragma unroll
        for (int j = 0; j < 5; j++)
            if (tid + 256 * j < NQH * 96) q32[tid + 256 * j] = val[j];
    }
    bar_cons();
    if (tid == 0 && !(cta >= 40 && cta < 120)) mbar_arrive(BAR(B_PRO));
    TS(4);
    }

    if (wid < 4) {
        const int pair = wid >> 1, half = wid & 1;
        uint32_t offK[3], offV[3];
        {
            const int rowK = half * 16 + l8 + 8 * (mi & 1), hiK = mi >> 1;
            const int rowV = half * 16 + l8 + 8 * (mi >> 1), hiV = mi & 1;
#pragma unroll
            for (int t = 0; t < 3; t++) {
                offK[t] = (rowK * 3 + t) * 128 + ((hiK ^ ((rowK * 3 + t) & 7)) << 4);
                offV[t] = (rowV * 3 + t) * 128 + ((hiV ^ ((rowV * 3 + t) & 7)) << 4);
                asm volatile("" : "+r"(offK[t]), "+r"(offV[t]));
            }
        }
        float acc[12][4];
#pragma unroll
        for (int i = 0; i < 12; i++) { acc[i][0] = acc[i][1] = acc[i][2] = acc[i][3] = 0.f; }
        float m_run = NEG_BIG, l_run = 0.f;
        uint32_t qf[12][2];
#pragma unroll
        for (int i = 0; i < 12; i++) { qf[i][0] = qf[i][1] = 0; }
        int cur = -1, flushed = 0, cnt = 0;
        int s = 2 * pair; uint32_t par = 0;
        int fb = 0; uint32_t fpar = 1;
        uint32_t ready = 0;
#pragma unroll 1
        while (true) {
            if (!ready) mbar_wait(BAR(B_FULL + s), par);
            const uint32_t mt_ = meta[s];
            const int run = mt_ & 0xff;
            if (mt_ & META_END) CLK(20);
            if ((mt_ & META_END) && half == 0) DBG(4 + pair);
            if (run != cur) {
#pragma unroll 1
                while (flushed < run) {
                    const uint32_t fle = mbar_try(BAR(B_FLE + fb), fpar);
                    float* mb = reinterpret_cast<float*>(smem + SM_MERGE) + (fb * 4 + wid) * 200;
                    if (flushed != cur) {
#pragma unroll
                        for (int i = 0; i < 12; i++) { acc[i][0] = acc[i][2] = 0.f; }
                        m_run = NEG_BIG; l_run = 0.f; cnt = 0;
                    }
                    float l = l_run;
                    l += __shfl_xor_sync(0xffffffffu, l, 4);
                    l += __shfl_xor_sync(0xffffffffu, l, 8);
                    l += __shfl_xor_sync(0xffffffffu, l, 16);
                    if (!fle) mbar_wait(BAR(B_FLE + fb), fpar);
                    if (j4 == 0) {
#pragma unroll
                        for (int i = 0; i < 12; i++) { mb[4 + 16 * i + g4] = acc[i][0]; mb[4 + 16 * i + 8 + g4] = acc[i][2]; }
                    }
                    if (lane == 0) { mb[0] = m_run; mb[1] = l; mb[2] = __int_as_float(cnt); }
                    __syncwarp();
                    if (lane == 0) mbar_arrive(BAR(B_FLF + fb));
                    if (++fb == NBUF) { fb = 0; fpar ^= 1; }
                    flushed++;
                    cur = -1;
                }
                if (mt_ & META_END) {
                    CLK(21);
                    if (flushed == 0 && lane == 0) mbar_arrive(BAR(B_FLF));
                    break;
                }
                cur = run;
                const int qi = (mt_ >> 8) & 0xff;
#pragma unroll
                for (int i = 0; i < 12; i++) { acc[i][0] = acc[i][1] = acc[i][2] = acc[i][3] = 0.f; }
                m_run = NEG_BIG; l_run = 0.f; cnt = 0;
#pragma unroll
                for (int ks = 0; ks < 12; ks++) {
                    qf[ks][0] = q32[qi * 96 + ks * 8 + j4];
                    qf[ks][1] = q32[qi * 96 + ks * 8 + 4 + j4];
                }
            }
            cnt++;
            if (half == 0) DBG(pair);
            const uint32_t kb = sb + SM_RING + s * CHUNK;
            int sv = s + 1; uint32_t parv = par;
            if (sv == NSLOT) { sv = 0; parv ^= 1; }
            float sc[6][4] = {};
            uint32_t vready;
            {
                uint32_t a[12][4];
#pragma unroll
                for (int t = 0; t < 3; t++) {
                    const uint32_t bt = kb + offK[t];
#pragma unroll
                    for (int kk = 0; kk < 4; kk++) ldsm4(a[t * 4 + kk], bt ^ (kk << 5));
                }
                vready = mbar_try(BAR(B_FULL + sv), parv);
#pragma unroll
                for (int i = 0; i < 12; i++) mma16816(sc[i % 6], a[i], qf[i][0], qf[i][1]);
            }
            __syncwarp();
            if (lane == 0) mbar_arrive(BAR(B_EMPTY + s));
            const float scale = 0.07216878364870322f;
            float s0 = bfr(bfr(((sc[0][0] + sc[1][0]) + (sc[2][0] + sc[3][0])) + (sc[4][0] + sc[5][0])) * scale);
            float s1 = bfr(bfr(((sc[0][2] + sc[1][2]) + (sc[2][2] + sc[3][2])) + (sc[4][2] + sc[5][2])) * scale);
            float tm = fmaxf(s0, s1);
            tm = fmaxf(tm, __shfl_xor_sync(0xffffffffu, tm, 4));
            tm = fmaxf(tm, __shfl_xor_sync(0xffffffffu, tm, 8));
            tm = fmaxf(tm, __shfl_xor_sync(0xffffffffu, tm, 16));
            if (tm > m_run) {
                float alpha = ex2((m_run - tm) * LOG2E);
                l_run *= alpha;
#pragma unroll
                for (int i = 0; i < 12; i++) { acc[i][0] *= alpha; acc[i][1] *= alpha; acc[i][2] *= alpha; acc[i][3] *= alpha; }
                m_run = tm;
            }
            float p0 = ex2((s0 - m_run) * LOG2E);
            float p1 = ex2((s1 - m_run) * LOG2E);
            l_run += p0 + p1;
            const uint32_t pw = pack_bf(p0, p1);
            const uint32_t pa = __shfl_sync(0xffffffffu, pw, 8 * j4), pb = __shfl_sync(0xffffffffu, pw, 8 * j4 + 4);
            const uint32_t b0 = __byte_perm(pa, pb, 0x5410), b1 = __byte_perm(pa, pb, 0x7632);
            if (!vready) mbar_wait(BAR(B_FULL + sv), parv);
            s += 4;
            if (s >= NSLOT) { s -= NSLOT; par ^= 1; }
            if (half == 0) DBG(2 + pair);
            ready = mbar_try(BAR(B_FULL + s), par);
            const uint32_t vb = sb + SM_RING + sv * CHUNK;
            {
                uint32_t a[12][4];
#pragma unroll
                for (int t = 0; t < 3; t++) {
                    const uint32_t bt = vb + offV[t];
#pragma unroll
                    for (int kk = 0; kk < 4; kk++) ldsm4t(a[t * 4 + kk], bt ^ (kk << 5));
                }
#pragma unroll
                for (int i = 0; i < 12; i++) mma16816(acc[i], a[i], b0, b1);
            }
            __syncwarp();
            if (lane == 0) mbar_arrive(BAR(B_EMPTY + sv));
        }
        TS(7);
        CLK(18);
    } else if (wid == 4) {
        int fb = 0; uint32_t fpar = 0;
#pragma unroll 1
        for (int f = 0;; f++) {
            const float* mb = reinterpret_cast<const float*>(smem + SM_MERGE) + fb * 800;
            mbar_wait(BAR(B_FLF + fb), fpar);
            const int head = (int)meta[16 + f];
            if (head == 0xFF) break;
            float m0 = mb[0], m1 = mb[200], m2 = mb[400], m3 = mb[600];
            float M = fmaxf(fmaxf(m0, m1), fmaxf(m2, m3));
            float w0 = ex2((m0 - M) * LOG2E), w1 = ex2((m1 - M) * LOG2E);
            float w2 = ex2((m2 - M) * LOG2E), w3 = ex2((m3 - M) * LOG2E);
            const int idx = head < NG * GH ? rank : cta;
            uint4* dst = &g_dat[head][idx][0];
            float o[6];
#pragma unroll
            for (int i = 0; i < 6; i++) {
                int d = 4 + (i < 3 ? 3 * lane + i : 96 + 3 * lane + (i - 3));
                o[i] = w0 * mb[d] + w1 * mb[200 + d] + w2 * mb[400 + d] + w3 * mb[600 + d];
            }
            float L = w0 * mb[1] + w1 * mb[201] + w2 * mb[401] + w3 * mb[601];
            const uint32_t tiles = __float_as_int(mb[2]) + __float_as_int(mb[402]);
            st_pk16(dst + lane, __float_as_uint(o[0]), __float_as_uint(o[1]), __float_as_uint(o[2]), tag);
            st_pk16(dst + 32 + lane, __float_as_uint(o[3]), __float_as_uint(o[4]), __float_as_uint(o[5]), tag);
            if (lane == 0) st_pk16(&g_hdr[head][idx], __float_as_uint(M), __float_as_uint(L), tiles, tag);
            __syncwarp();
            if (lane == 0) mbar_arrive(BAR(B_FLE + fb));
            if (++fb == NBUF) { fb = 0; fpar ^= 1; }
            if (meta[16 + f + 1] == 0xFFu) break;
        }
        TS(8);
        CLK(18);
    } else if (wid >= 6) {
        if (cta < 128) {
            const int t = tid - 192;
            uint32_t* cb32 = reinterpret_cast<uint32_t*>(smem + SM_CB);
            uint32_t* sb32 = reinterpret_cast<uint32_t*>(smem + SM_SB);
            const int col = cta * 5 + t;
            int off[12];
            uint32_t val[12];
#pragma unroll
            for (int rep = 0; rep < 5; rep++) { off[2 * rep] = 960 + t + 64 * rep; off[2 * rep + 1] = 1280 + t + 64 * rep; }
            off[10] = t < 5 ? (1280 + col) >> 1 : 960;
            off[11] = t < 5 ? (3200 + col) >> 1 : 960;
            poll8<12>(g_mod, off, val, tag);
#pragma unroll
            for (int rep = 0; rep < 5; rep++) {
                sb32[t + 64 * rep] = val[2 * rep];
                cb32[t + 64 * rep] = pack_bf(1.0f + bf_lo(val[2 * rep + 1]), 1.0f + bf_hi(val[2 * rep + 1]));
            }
            if (t < 5) {
                own[t] = (col & 1) ? bf_hi(val[10]) : bf_lo(val[10]);
                own[8 + t] = (col & 1) ? bf_hi(val[11]) : bf_lo(val[11]);
                uint32_t xx = x32[col >> 1];
                own[16 + t] = (col & 1) ? bf_hi(xx) : bf_lo(xx);
            }
        }
        live = false;
    }
    }
    const uint32_t sb0 = sb;
    const bool warmer = wid == 9;
    const int tid0 = warmer ? tid - 64 : tid;
#pragma unroll 1
    while (cta < 128) {
        uint32_t sb = sb0; int tid = tid0;
        asm volatile("" : "+r"(sb), "+r"(tid));
        const int wid = tid >> 5, lane = tid & 31;
        const int g4 = lane >> 2, j4 = lane & 3, mi = lane >> 3, l8 = lane & 7;
        CLK(19);
        if (wid >= 5) {
            const int h = cta >> 2, js = cta & 3;
            const bool gl = h >= NG * GH;
            const int ncand = gl ? G : (G - h / GH + NG - 1) / NG;
            const int k = lane & 15, rr = (wid - 5) * 2 + (lane >> 4);
            if (live) {
                const unsigned* cp = &g_ctr[(tag - 1) & 1][(gl ? NG : h / GH) * 32];
                const unsigned thr = ((gl ? h - NG * GH : h % GH) + 1) * TPH;
                uint32_t it = 0;
                while (true) {
                    unsigned v;
                    asm volatile("ld.relaxed.gpu.global.u32 %0, [%1];" : "=r"(v) : "l"(cp) : "memory");
                    if (v >= thr) break;
                    __nanosleep(300);
                    if (++it > SPIN_LIMIT) __trap();
                }
            }
            const uint4* hdr = &g_hdr[h][lane];
            const uint4* dat = &g_dat[h][rr][16 * js + k];
            float* part = stage;
            float L, a0, a1, a2;
            uint32_t it = 0;
            uint4 hd[5], dv[MAXG / 6];
#pragma unroll
            for (int i = 0; i < 5; i++) hd[i] = make_uint4(0, 0, 0, 0);
#pragma unroll
            for (int i = 0; i < MAXG / 6; i++) dv[i] = make_uint4(0, 0, 0, 0);
#pragma unroll 1
            while (true) {
                FreshN<5, 32>::run(hd, hdr, tag, live, lane, 32, ncand);
                FreshN<MAXG / 6, 6 * 64>::run(dv, dat, tag, live, rr, 6, ncand);
                float w[5], M = NEG_BIG;
                int c = 0;
#pragma unroll
                for (int i = 0; i < 5; i++) {
                    const bool v = hd[i].w == tag;
                    w[i] = v ? __uint_as_float(hd[i].x) : NEG_BIG;
                    M = fmaxf(M, w[i]);
                    c += v ? (int)hd[i].z : 0;
                }
                c = __reduce_add_sync(0xffffffffu, c);
                if (++it > SPIN_LIMIT) __trap();
                if (live && c != TPH) continue;
                CLK(1);
#pragma unroll
                for (int o = 16; o > 0; o >>= 1) M = fmaxf(M, __shfl_xor_sync(0xffffffffu, M, o));
                float ls = 0.f;
#pragma unroll
                for (int i = 0; i < 5; i++) {
                    const bool v = w[i] != NEG_BIG;
                    const float e = ex2((w[i] - M) * LOG2E);
                    w[i] = v ? e : -0.0f;
                    ls = fmaf(w[i], __uint_as_float(hd[i].y), ls);
                }
                float* wsm = reinterpret_cast<float*>(smem + SM_X2) + (wid - 5) * 160;
                if (live) {
#pragma unroll
                    for (int i = 0; i < 5; i++) wsm[lane + 32 * i] = w[i];
                }
                __syncwarp();
                uint32_t badm = 0;
                a0 = a1 = a2 = 0.f;
#pragma unroll
                for (int i = 0; i < MAXG / 6; i++) {
                    const float wi = wsm[rr + 6 * i];
                    badm |= (dv[i].w ^ tag) & ~(uint32_t)(__float_as_int(wi) >> 31);
                    a0 = fmaf(wi, __uint_as_float(dv[i].x), a0);
                    a1 = fmaf(wi, __uint_as_float(dv[i].y), a1);
                    a2 = fmaf(wi, __uint_as_float(dv[i].z), a2);
                }
                const bool bad = badm != 0;
                __syncwarp();
                L = warp_sum(ls);
                if (!__any_sync(0xffffffffu, bad) || !live) break;
            }
            a0 += __shfl_xor_sync(0xffffffffu, a0, 16);
            a1 += __shfl_xor_sync(0xffffffffu, a1, 16);
            a2 += __shfl_xor_sync(0xffffffffu, a2, 16);
            CLK(2);
            if (live && lane < 16) { float* pp = part + (wid - 5) * 48 + 3 * k; pp[0] = a0; pp[1] = a1; pp[2] = a2; }
            if (live) asm volatile("bar.sync 2, 96;" ::: "memory");
            if (wid == 5 || !live) {
                uint16_t* osw = reinterpret_cast<uint16_t*>(smem + SM_SC);
                const float inv = __fdividef(1.0f, L);
                const float o0 = (part[lane] + part[48 + lane]) + part[96 + lane];
                const float o1 = (part[32 + (lane & 15)] + part[80 + (lane & 15)]) + part[128 + (lane & 15)];
                if (live) { osw[lane] = (uint16_t)(__float_as_uint(bfr(o0 * inv)) >> 16); if (lane < 16) osw[32 + lane] = (uint16_t)(__float_as_uint(bfr(o1 * inv)) >> 16); }
            }
            if (live) TS(10);
        }
        if (wid < 5 || !live) {
            const int w5 = wid < 5 ? wid : wid - 5;
            uint32_t wa[8][3][4];
            if (live) mbar_wait(BAR(B_WO + w5), 0);
#pragma unroll
            for (int i = 0; i < 8; i++) {
                const int cc = 2 * (i & 3) + (mi & 1);
#pragma unroll
                for (int ks = 0; ks < 3; ks++) {
                    const int r = ks * 16 + l8 + 8 * (mi >> 1);
                    ldsm4t(wa[i][ks], sb + SM_WO + (2 * w5 + (i >> 2)) * 6144 + r * 128 + ((cc ^ (r & 7)) << 4));
                }
            }
            if (live) bar_cons();
            if (live) TS(9);
            CLK(3);
            const uint32_t* os32 = reinterpret_cast<const uint32_t*>(smem + SM_SC);
            float acc[8][4] = {};
#pragma unroll
            for (int ks = 0; ks < 3; ks++) {
                const uint32_t b0 = os32[ks * 8 + j4], b1 = os32[ks * 8 + 4 + j4];
#pragma unroll
                for (int i = 0; i < 8; i++) mma16816(acc[i], wa[i][ks], b0, b1);
            }
            if (live && j4 == 0) {
#pragma unroll
                for (int i = 0; i < 8; i++) { stage[(w5 * 8 + i) * 16 + g4] = acc[i][0]; stage[(w5 * 8 + i) * 16 + 8 + g4] = acc[i][2]; }
            }
        } else {
            bar_cons();
        }
        CLK(4);
        if (live) bar_cons();
        {
            const int o = tid >> 1, kk = tid & 1;
            const float* sp = stage + o * 5 + kk * 3;
            float v0 = sp[0], v1 = sp[1], v2 = kk ? 0.f : sp[2];
            if (live) st_pk16(&g_h1[o][cta][kk], __float_as_uint(v0), __float_as_uint(v1), __float_as_uint(v2), tag);
        }
        if (live) TS(11);
        CLK(5);
        if (wid == 0 || !live) {
            const uint4* p = &g_h1[cta][0][0] + lane;
            uint4 v[8];
            uint32_t it = 0;
            while (true) {
                bool ok = true;
                LoadN<8, 32>::run(v, p, live, 0, 0, 1);
#pragma unroll
                for (int j = 0; j < 8; j++) ok = ok && v[j].w == tag;
                if (__all_sync(0xffffffffu, ok) || !live) break;
                if (++it > SPIN_LIMIT) __trap();
            }
            CLK(6);
            float a0 = 0.f, a1 = 0.f, a2 = 0.f;
#pragma unroll
            for (int j = 0; j < 8; j++) { a0 += __uint_as_float(v[j].x); a1 += __uint_as_float(v[j].y); a2 += __uint_as_float(v[j].z); }
#pragma unroll
            for (int o = 2; o <= 16; o <<= 1) {
                a0 += __shfl_xor_sync(0xffffffffu, a0, o);
                a1 += __shfl_xor_sync(0xffffffffu, a1, o);
                a2 += __shfl_xor_sync(0xffffffffu, a2, o);
            }
            const float gx = own[lane & 7], xx = own[16 + (lane & 7)];
            const float t0 = __shfl_sync(0xffffffffu, a0, lane >= 3), t1 = __shfl_sync(0xffffffffu, a1, lane >= 3);
            const float sum = (lane == 0 || lane == 3) ? t0 : (lane == 2 ? a2 : t1);
            const float x2 = bfr(xx + bfr(gx * bfr(sum)));
            if (live && lane < 5) own[24 + lane] = x2;
            const float y1 = __shfl_sync(0xffffffffu, x2, 1), y2 = __shfl_sync(0xffffffffu, x2, 2);
            const float y3 = __shfl_sync(0xffffffffu, x2, 3), y4 = __shfl_sync(0xffffffffu, x2, 4);
            if (live && lane == 0) st_pk16(&g_x2[cta][0], pack_bf(x2, y1), pack_bf(y2, y3), pack_bf(y4, 0.f), tag);
            if (live) TS(13);
        }
        CLK(8);
        if (cta < 96) {
            uint32_t a1[5][4], a3[5][4], a2[5][4];
            if (live) mbar_wait3(BAR(B_W1 + (wid >> 2)), BAR(B_W3 + (wid >> 2)), BAR(B_W2 + (wid >> 2)));
            const uint32_t w2b = sb + SM_RING + meta[10 + (wid >> 2)] % NSLOT * CHUNK;
#pragma unroll
            for (int ks = 0; ks < 5; ks++) {
                const int r = wid * 80 + ks * 16 + l8 + 8 * (mi >> 1);
                const uint32_t off = r * 32 + (((mi & 1) ^ ((r >> 2) & 1)) << 4);
                ldsm4t(a1[ks], sb + SM_W1 + off);
                ldsm4t(a3[ks], sb + SM_W3 + off);
            }
#pragma unroll
            for (int i = 0; i < 5; i++) {
                const int mt = (wid & 3) * 5 + i;
                const int cc = 2 * (mt & 3) + (mi & 1);
                const int r = l8 + 8 * (mi >> 1);
                ldsm4t(a2[i], w2b + (mt >> 2) * 2048 + r * 128 + ((cc ^ (r & 7)) << 4));
            }
            CLK(9);
            float* x2s = reinterpret_cast<float*>(smem + SM_X2);
            float* st8 = red + 256;
            if (wid >= 4) {
                uint4 v = poll16(&g_x2[tid - 128][0], tag, live);
                const float e0 = bf_lo(v.x), e1 = bf_hi(v.x), e2 = bf_lo(v.y), e3 = bf_hi(v.y), e4 = bf_lo(v.z);
                float* d = x2s + (tid - 128) * 5;
                if (live) { d[0] = e0; d[1] = e1; d[2] = e2; d[3] = e3; d[4] = e4; }
                const float pv = __shfl_sync(0xffffffffu, e0, 0);
                const float d0 = e0 - pv, d1 = e1 - pv, d2 = e2 - pv, d3 = e3 - pv, d4 = e4 - pv;
                float s1 = ((d0 + d1) + (d2 + d3)) + d4;
                float s2 = fmaf(d0, d0, fmaf(d1, d1, fmaf(d2, d2, fmaf(d3, d3, d4 * d4))));
#pragma unroll
                for (int o = 16; o > 0; o >>= 1) { s1 += __shfl_xor_sync(0xffffffffu, s1, o); s2 += __shfl_xor_sync(0xffffffffu, s2, o); }
                if (live && lane == 0) { st8[2 * (wid - 4)] = pv + s1 * (1.0f / 160.0f); st8[2 * (wid - 4) + 1] = s2 - s1 * s1 * (1.0f / 160.0f); }
            }
            if (live) bar_cons();
            if (live) TS(14);
            CLK(10);
            const float4 sA = *reinterpret_cast<const float4*>(st8), sB = *reinterpret_cast<const float4*>(st8 + 4);
            const float mean = ((sA.x + sA.z) + (sB.x + sB.z)) * 0.25f;
            const float u0 = sA.x - mean, u1 = sA.z - mean, u2 = sB.x - mean, u3 = sB.z - mean;
            const float m2 = ((sA.y + sA.w) + (sB.y + sB.w)) + 160.0f * ((u0 * u0 + u1 * u1) + (u2 * u2 + u3 * u3));
            const float mean_b = bfr(mean);
            const float rden = __fdividef(1.0f, bfr(fsqrt(bfr(bfr(m2 * (1.0f / 640.0f)) + 1e-5f))));
            const uint32_t* cb32 = reinterpret_cast<const uint32_t*>(smem + SM_CB);
            const uint32_t* sb32 = reinterpret_cast<const uint32_t*>(smem + SM_SB);
#pragma unroll
            for (int rep = 0; rep < 2; rep++) {
                const int p = lane + 32 * rep;
                if (p < 40) {
                    int pp = wid * 40 + p;
                    const float2 xv = *reinterpret_cast<const float2*>(x2s + 2 * pp);
                    uint32_t cv = cb32[pp], sv = sb32[pp];
                    float n0 = bfr(bfr(xv.x - mean_b) * rden), n1 = bfr(bfr(xv.y - mean_b) * rden);
                    uint32_t hv = pack_bf(bfr(n0 * bf_lo(cv)) + bf_lo(sv), bfr(n1 * bf_hi(cv)) + bf_hi(sv));
                    if (live) h32[pp] = hv;
                }
            }
            __syncwarp();
            CLK(11);
            float ag[2][4] = {}, au[2][4] = {};
#pragma unroll
            for (int ks = 0; ks < 5; ks++) {
                const int r0 = wid * 80 + ks * 16;
                const uint32_t b0 = h32[(r0 >> 1) + j4], b1 = h32[(r0 >> 1) + 4 + j4];
                mma16816(ag[ks & 1], a1[ks], b0, b1);
                mma16816(au[ks & 1], a3[ks], b0, b1);
            }
            if (live && j4 == 0) {
                red[wid * 32 + g4] = ag[0][0] + ag[1][0]; red[wid * 32 + 8 + g4] = ag[0][2] + ag[1][2];
                red[wid * 32 + 16 + g4] = au[0][0] + au[1][0]; red[wid * 32 + 24 + g4] = au[0][2] + au[1][2];
            }
            CLK(12);
            if (live) bar_cons();
            if (live) TS(15);
            CLK(13);
            float v = 0.f;
#pragma unroll
            for (int w = 0; w < 8; w++) v += red[w * 32 + lane];
            v = bfr(v);
            float up = __shfl_down_sync(0xffffffffu, v, 16);
            float hact = bfr(bfr(silu(v)) * up);
            float e0 = __shfl_sync(0xffffffffu, hact, 2 * j4), e1 = __shfl_sync(0xffffffffu, hact, 2 * j4 + 1);
            float e2 = __shfl_sync(0xffffffffu, hact, 2 * j4 + 8), e3 = __shfl_sync(0xffffffffu, hact, 2 * j4 + 9);
            const uint32_t b0 = pack_bf(e0, e1), b1 = pack_bf(e2, e3);
            float acc[5][4] = {};
#pragma unroll
            for (int i = 0; i < 5; i++) mma16816(acc[i], a2[i], b0, b1);
            if (live && j4 == 0) {
#pragma unroll
                for (int i = 0; i < 5; i++) { stage[(wid * 5 + i) * 16 + g4] = acc[i][0]; stage[(wid * 5 + i) * 16 + 8 + g4] = acc[i][2]; }
            }
            CLK(14);
            if (live) bar_cons();
            const int o = tid >> 1, k = tid & 1;
            const float* sp = stage + o * 5 + k * 3;
            float v0 = sp[0], v1 = sp[1], v2 = k ? 0.f : sp[2];
            if (live) st_pk16(&g_h3[o][cta][k], __float_as_uint(v0), __float_as_uint(v1), __float_as_uint(v2), tag);
        }
        if (live) TS(16);
        CLK(15);
        if (wid == 0 || !live) {
            const uint4* p = &g_h3[cta][0][0] + lane;
            uint4 v[6];
            uint32_t it = 0;
            if (live && cta < 96) spin(P_DLY);
            while (true) {
                bool ok = true;
                LoadN<6, 32>::run(v, p, live, 0, 0, 1);
#pragma unroll
                for (int j = 0; j < 6; j++) ok = ok && v[j].w == tag;
                if (__all_sync(0xffffffffu, ok) || !live) break;
                if (++it > SPIN_LIMIT) __trap();
            }
            CLK(16);
            float a0 = 0.f, a1 = 0.f, a2 = 0.f;
#pragma unroll
            for (int j = 0; j < 6; j++) { a0 += __uint_as_float(v[j].x); a1 += __uint_as_float(v[j].y); a2 += __uint_as_float(v[j].z); }
#pragma unroll
            for (int o = 2; o <= 16; o <<= 1) {
                a0 += __shfl_xor_sync(0xffffffffu, a0, o);
                a1 += __shfl_xor_sync(0xffffffffu, a1, o);
                a2 += __shfl_xor_sync(0xffffffffu, a2, o);
            }
            const float gx = own[8 + (lane & 7)], xx = own[24 + (lane & 7)];
            const float t0 = __shfl_sync(0xffffffffu, a0, lane >= 3), t1 = __shfl_sync(0xffffffffu, a1, lane >= 3);
            const float sum = (lane == 0 || lane == 3) ? t0 : (lane == 2 ? a2 : t1);
            const float y = xx + bfr(gx * bfr(sum));
            if (live && lane < 5) reinterpret_cast<uint16_t*>(out)[cta * 5 + lane] = (uint16_t)(__float_as_uint(bfr(y)) >> 16);
            if (live && cta == 0 && lane == 0) g_epoch = tag;
        }
        CLK(17);
        if (live) { TS(18); break; }
        live = true;
    }
    }
}

typedef CUresult (*EncodeFn)(CUtensorMap*, CUtensorMapDataType, cuuint32_t, void*, const cuuint64_t*, const cuuint64_t*,
                             const cuuint32_t*, const cuuint32_t*, CUtensorMapInterleave, CUtensorMapSwizzle,
                             CUtensorMapL2promotion, CUtensorMapFloatOOBfill);

void make_map(EncodeFn enc, CUtensorMap* tm, const void* ptr, uint64_t cols, uint64_t rows, uint32_t box_c, uint32_t box_r,
              CUtensorMapSwizzle sw, CUtensorMapL2promotion prom) {
    cuuint64_t dims[2] = {cols, rows};
    cuuint64_t strides[1] = {cols * 2};
    cuuint32_t box[2] = {box_c, box_r};
    cuuint32_t es[2] = {1, 1};
    enc(tm, CU_TENSOR_MAP_DATA_TYPE_BFLOAT16, 2, const_cast<void*>(ptr), dims, strides, box, es,
        CU_TENSOR_MAP_INTERLEAVE_NONE, sw, prom, CU_TENSOR_MAP_FLOAT_OOB_FILL_NONE);
}

}

extern "C" void kernel_launch(void* const* d_in, const int* in_sizes, int n_in, void* d_out, int out_size) {
    (void)in_sizes; (void)n_in; (void)out_size;
    static EncodeFn enc = nullptr;
    static int num_sms = 0;
    if (!enc) {
        void* fn = nullptr;
        cudaDriverEntryPointQueryResult qr;
        cudaGetDriverEntryPoint("cuTensorMapEncodeTiled", &fn, cudaEnableDefault, &qr);
        enc = (EncodeFn)fn;
        cudaDeviceGetAttribute(&num_sms, cudaDevAttrMultiProcessorCount, 0);
        cudaFuncSetAttribute(fused_decode_kernel, cudaFuncAttributeMaxDynamicSharedMemorySize, SM_TOTAL);
    }
    CUtensorMap tmK, tmV, tmMod, tmWq, tmWo, tmW1, tmW3, tmW2;
    const uint64_t kv_lines = (uint64_t)NH * SK * 3;
    make_map(enc, &tmK, d_in[1], 64, kv_lines, 64, 96, CU_TENSOR_MAP_SWIZZLE_128B, CU_TENSOR_MAP_L2_PROMOTION_L2_128B);
    make_map(enc, &tmV, d_in[2], 64, kv_lines, 64, 96, CU_TENSOR_MAP_SWIZZLE_128B, CU_TENSOR_MAP_L2_PROMOTION_L2_128B);
    make_map(enc, &tmWq, d_in[3], NH * DH, D, 48, 128, CU_TENSOR_MAP_SWIZZLE_NONE, CU_TENSOR_MAP_L2_PROMOTION_L2_128B);
    make_map(enc, &tmWo, d_in[4], D, NH * DH, 64, 48, CU_TENSOR_MAP_SWIZZLE_128B, CU_TENSOR_MAP_L2_PROMOTION_L2_128B);
    make_map(enc, &tmW1, d_in[6], FF, D, 16, 160, CU_TENSOR_MAP_SWIZZLE_32B, CU_TENSOR_MAP_L2_PROMOTION_L2_128B);
    make_map(enc, &tmW3, d_in[7], FF, D, 16, 160, CU_TENSOR_MAP_SWIZZLE_32B, CU_TENSOR_MAP_L2_PROMOTION_L2_128B);
    make_map(enc, &tmW2, d_in[8], D, FF, 64, 16, CU_TENSOR_MAP_SWIZZLE_128B, CU_TENSOR_MAP_L2_PROMOTION_L2_128B);
    make_map(enc, &tmMod, d_in[10], 6 * D, D, 32, 160, CU_TENSOR_MAP_SWIZZLE_64B, CU_TENSOR_MAP_L2_PROMOTION_L2_128B);
    int grid = num_sms < MAXG ? num_sms : MAXG;
    fused_decode_kernel<<<grid, NTHREADS, SM_TOTAL, cudaStreamPerThread>>>(
        tmK, tmV, tmMod, tmWq, tmWo, tmW1, tmW3, tmW2, (const __nv_bfloat16*)d_in[0], (const __nv_bfloat16*)d_in[9],
        (__nv_bfloat16*)d_out);
}
```

```cpp
#include <cuda_runtime.h>
#include <cuda_bf16.h>
#include <cuda.h>
#include <stdint.h>

namespace {

constexpr int D = 640, NH = 32, SK = 8192, DH = 192, FF = 1536;
constexpr int NG = 4;
constexpr int GH = 7;
constexpr int NGLOB = NH - NG * GH;
constexpr int NQH = GH + NGLOB;
constexpr int TILE = 32;
constexpr int TPH = SK / TILE;
constexpr int GT = GH * TPH;
constexpr int PT = NGLOB * TPH;
constexpr int CHUNK = TILE * DH * 2;
#define P_NSLOT 8
#define P_WIN 3
#define P_URG 0
#define P_HOLD 3
#define P_TWIN P_WIN
#define P_DLY 450
constexpr int NSLOT = P_NSLOT;
constexpr int WIN = P_WIN;
#define P_NBUF 3
constexpr int NBUF = P_NBUF;
constexpr int MAXG = 132;
constexpr int NTHREADS = 288;
constexpr float NEG_BIG = -3.402823466e38f;

constexpr int SM_WMOD = 0;
constexpr int SM_WQ = 40960;
constexpr int SM_WO = 0;
constexpr int SM_W1 = 61440;
constexpr int SM_W3 = 81920;
constexpr int SM_RING = 102400;
constexpr int SM_MISC = SM_RING + NSLOT * CHUNK;
constexpr int SM_BARS = SM_MISC;
constexpr int SM_META = SM_BARS + 512;
constexpr int SM_Q = SM_META + 128;
constexpr int SM_SC = SM_Q + NQH * DH * 2;
constexpr int SM_H = SM_SC + 1280;
constexpr int SM_X = SM_H + 1280;
constexpr int SM_CB = SM_X + 1280;
constexpr int SM_SB = SM_CB + 1280;
constexpr int SM_OWN = SM_SB + 1280;
constexpr int SM_RED = SM_OWN + 128;
constexpr int SM_MERGE = SM_RED + 2048;
constexpr int SM_STAGE = SM_MERGE + NBUF * 3200;
constexpr int SM_X2 = SM_STAGE + 2560;
constexpr int SM_FIN = SM_X2 + 2560;
constexpr int SM_TOTAL = SM_FIN + 512;
static_assert(SM_TOTAL <= 232448, "shared memory budget");

constexpr int B_FULL = 0;
constexpr int B_EMPTY = 8;
constexpr int B_MOD = 16;
constexpr int B_WQ = 20;
constexpr int B_WO = 25;
constexpr int B_W1 = 30;
constexpr int B_W3 = 32;
constexpr int B_W2 = 34;
constexpr int B_PRO = 36, B_DUMMY = 37;
constexpr int B_FLF = 40, B_FLE = 44;
constexpr int B_LAST = 48;
static_assert(NSLOT <= 8 && NSLOT >= 6 && WIN <= 4 && WIN <= NSLOT - 3, "barrier map / end markers vs window");
constexpr uint32_t META_END = 0x10000u;

__device__ unsigned g_epoch;
__device__ unsigned g_ctr[2][(NG + 1) * 32];
__device__ __align__(128) unsigned long long g_mod[1920];
__device__ __align__(128) unsigned long long g_q[3072];
__device__ __align__(128) uint4 g_hdr[NH][MAXG];
__device__ __align__(128) uint4 g_dat[NH][MAXG][64];
__device__ __align__(128) uint4 g_h1[128][128][2];
__device__ __align__(128) uint4 g_x2[128][2];
__device__ __align__(128) uint4 g_h3[128][96][2];

#define TS(k) do {} while (0)
#define DBG(k) do {} while (0)
#define EARLY(k) do {} while (0)
#define CLK(k) do {} while (0)

__device__ __forceinline__ uint32_t smem_u32(const void* p) { return (uint32_t)__cvta_generic_to_shared(p); }
__device__ __forceinline__ void mbar_init(uint32_t bar, uint32_t cnt) {
    asm volatile("mbarrier.init.shared::cta.b64 [%0], %1;" ::"r"(bar), "r"(cnt) : "memory");
}
__device__ __forceinline__ void mbar_expect_tx(uint32_t bar, uint32_t bytes) {
    asm volatile("mbarrier.arrive.expect_tx.shared::cta.b64 _, [%0], %1;" ::"r"(bar), "r"(bytes) : "memory");
}
__device__ __forceinline__ void mbar_arrive(uint32_t bar) {
    asm volatile("mbarrier.arrive.shared::cta.b64 _, [%0];" ::"r"(bar) : "memory");
}
constexpr uint32_t SPIN_LIMIT = 1u << 22;
__device__ __forceinline__ void mbar_wait(uint32_t bar, uint32_t parity) {
    asm volatile(
        "{\n.reg .pred p;\n.reg .u32 c;\nmov.u32 c, 0;\n"
        "LW:\nmbarrier.try_wait.parity.shared::cta.b64 p, [%0], %1;\n@p bra LD;\n"
        "add.u32 c, c, 1;\nsetp.lt.u32 p, c, 0x400000;\n@p bra LW;\ntrap;\nLD:\n}" ::"r"(bar), "r"(parity)
        : "memory");
}
__device__ __forceinline__ uint32_t mbar_try(uint32_t bar, uint32_t parity) {
    uint32_t ok;
    asm volatile("{\n.reg .pred p;\nmbarrier.try_wait.parity.shared::cta.b64 p, [%1], %2;\nselp.u32 %0, 1, 0, p;\n}"
                 : "=r"(ok) : "r"(bar), "r"(parity) : "memory");
    return ok;
}
__device__ __forceinline__ void mbar_wait3(uint32_t b0, uint32_t b1, uint32_t b2) {
    asm volatile(
        "{\n.reg .pred p, q, r;\n.reg .u32 c;\nmov.u32 c, 0;\n"
        "LW:\nmbarrier.try_wait.parity.shared::cta.b64 p, [%0], 0;\n"
        "mbarrier.try_wait.parity.shared::cta.b64 q, [%1], 0;\n"
        "mbarrier.try_wait.parity.shared::cta.b64 r, [%2], 0;\n"
        "and.pred p, p, q;\nand.pred p, p, r;\n@p bra LD;\n"
        "add.u32 c, c, 1;\nsetp.lt.u32 p, c, 0x400000;\n@p bra LW;\ntrap;\nLD:\n}" ::"r"(b0), "r"(b1), "r"(b2)
        : "memory");
}
__device__ __forceinline__ void tma2d(uint32_t dst, const CUtensorMap* tm, int c0, int c1, uint32_t bar) {
    asm volatile(
        "cp.async.bulk.tensor.2d.shared::cluster.global.mbarrier::complete_tx::bytes [%0], [%1, {%3, %4}], [%2];" ::"r"(dst),
        "l"(tm), "r"(bar), "r"(c0), "r"(c1)
        : "memory");
}
__device__ __forceinline__ void tma2d_hint(uint32_t dst, const CUtensorMap* tm, int c0, int c1, uint32_t bar, uint64_t pol) {
    asm volatile(
        "cp.async.bulk.tensor.2d.shared::cluster.global.mbarrier::complete_tx::bytes.L2::cache_hint [%0], [%1, {%3, %4}], [%2], %5;" ::"r"(dst),
        "l"(tm), "r"(bar), "r"(c0), "r"(c1), "l"(pol)
        : "memory");
}
__device__ __forceinline__ void prefetch_tm(const CUtensorMap* tm) {
    asm volatile("prefetch.tensormap [%0];" ::"l"(tm) : "memory");
}
__device__ __forceinline__ void ldsm4(uint32_t (&r)[4], uint32_t addr) {
    asm volatile("ldmatrix.sync.aligned.m8n8.x4.shared.b16 {%0,%1,%2,%3}, [%4];"
                 : "=r"(r[0]), "=r"(r[1]), "=r"(r[2]), "=r"(r[3])
                 : "r"(addr));
}
__device__ __forceinline__ void ldsm4t(uint32_t (&r)[4], uint32_t addr) {
    asm volatile("ldmatrix.sync.aligned.m8n8.x4.trans.shared.b16 {%0,%1,%2,%3}, [%4];"
                 : "=r"(r[0]), "=r"(r[1]), "=r"(r[2]), "=r"(r[3])
                 : "r"(addr));
}
__device__ __forceinline__ void mma16816(float (&d)[4], const uint32_t (&a)[4], uint32_t b0, uint32_t b1) {
    asm volatile(
        "mma.sync.aligned.m16n8k16.row.col.f32.bf16.bf16.f32 {%0,%1,%2,%3}, {%4,%5,%6,%7}, {%8,%9}, {%0,%1,%2,%3};"
        : "+f"(d[0]), "+f"(d[1]), "+f"(d[2]), "+f"(d[3])
        : "r"(a[0]), "r"(a[1]), "r"(a[2]), "r"(a[3]), "r"(b0), "r"(b1));
}
__device__ __forceinline__ void bar_cons() { asm volatile("bar.sync 1, 256;" ::: "memory"); }
__device__ __forceinline__ void spin(int cycles) {
    long long t0 = clock64();
    while (clock64() - t0 < cycles) {}
}

__device__ __forceinline__ float bfr(float x) {
    uint32_t r;
    asm("cvt.rn.bf16x2.f32 %0, %1, %2;" : "=r"(r) : "f"(x), "f"(0.0f));
    return __uint_as_float(r);
}
__device__ __forceinline__ uint32_t pack_bf(float lo, float hi) {
    __nv_bfloat162 t = __floats2bfloat162_rn(lo, hi);
    return *reinterpret_cast<uint32_t*>(&t);
}
__device__ __forceinline__ float bf_lo(uint32_t v) { return __uint_as_float(v << 16); }
__device__ __forceinline__ float bf_hi(uint32_t v) { return __uint_as_float(v & 0xffff0000u); }

__device__ __forceinline__ void st_pk8(unsigned long long* p, uint32_t v, uint32_t tag) {
    unsigned long long w = ((unsigned long long)tag << 32) | v;
    asm volatile("st.relaxed.gpu.global.b64 [%0], %1;" ::"l"(p), "l"(w) : "memory");
}
__device__ __forceinline__ unsigned long long ld_raw8(const unsigned long long* p) {
    unsigned long long w;
    asm volatile("ld.relaxed.gpu.global.b64 %0, [%1];" : "=l"(w) : "l"(p) : "memory");
    return w;
}
template <int N>
__device__ __forceinline__ void poll8(const unsigned long long* base, const int (&off)[N], uint32_t (&val)[N], uint32_t tag) {
    uint32_t it = 0;
    while (true) {
        unsigned long long w[N];
#pragma unroll
        for (int i = 0; i < N; i++) w[i] = ld_raw8(base + off[i]);
        bool ok = true;
#pragma unroll
        for (int i = 0; i < N; i++) { ok = ok && ((uint32_t)(w[i] >> 32) == tag); val[i] = (uint32_t)w[i]; }
        if (__all_sync(0xffffffffu, ok)) break;
        if (++it > SPIN_LIMIT) __trap();
    }
}
__device__ __forceinline__ void st_pk16(uint4* p, uint32_t a, uint32_t b, uint32_t c, uint32_t tag) {
    asm volatile(
        "{\n.reg .b128 t;\n.reg .b64 lo, hi;\nmov.b64 lo, {%1, %2};\nmov.b64 hi, {%3, %4};\nmov.b128 t, {lo, hi};\n"
        "st.relaxed.gpu.global.b128 [%0], t;\n}" ::"l"(p), "r"(a), "r"(b), "r"(c), "r"(tag)
        : "memory");
}
template <int OFF = 0>
__device__ __forceinline__ uint4 ld_raw16p(const uint4* p, uint32_t on) {
    uint4 v;
    asm volatile(
        "{\n.reg .b128 t;\n.reg .b64 lo, hi;\n.reg .pred q;\nsetp.ne.u32 q, %5, 0;\n"
        "mov.b64 lo, 0;\nmov.b128 t, {lo, lo};\n"
        "@q ld.relaxed.gpu.global.b128 t, [%4 + %6];\nmov.b128 {lo, hi}, t;\n"
        "mov.b64 {%0, %1}, lo;\nmov.b64 {%2, %3}, hi;\n}"
        : "=r"(v.x), "=r"(v.y), "=r"(v.z), "=r"(v.w)
        : "l"(p), "r"(on), "n"(OFF * 16)
        : "memory");
    return v;
}
template <int OFF>
__device__ __forceinline__ void ld_fresh16(uint4& v, const uint4* p, uint32_t tag, uint32_t on) {
    asm volatile(
        "{\n.reg .b128 t;\n.reg .b64 lo, hi;\n.reg .pred q;\nsetp.ne.u32 q, %3, %5;\nsetp.ne.and.u32 q, %6, 0, q;\n"
        "mov.b64 lo, {%0, %1};\nmov.b64 hi, {%2, %3};\nmov.b128 t, {lo, hi};\n"
        "@q ld.relaxed.gpu.global.b128 t, [%4 + %7];\nmov.b128 {lo, hi}, t;\n"
        "mov.b64 {%0, %1}, lo;\nmov.b64 {%2, %3}, hi;\n}"
        : "+r"(v.x), "+r"(v.y), "+r"(v.z), "+r"(v.w)
        : "l"(p), "r"(tag), "r"(on), "n"(OFF * 16)
        : "memory");
}
template <int N, int STRIDE, int I = 0>
struct FreshN {
    static __device__ __forceinline__ void run(uint4* v, const uint4* p, uint32_t tag, bool live, int base, int step, int lim) {
        ld_fresh16<I * STRIDE>(v[I], p, tag, live && base + step * I < lim);
        FreshN<N, STRIDE, I + 1>::run(v, p, tag, live, base, step, lim);
    }
};
template <int N, int STRIDE>
struct FreshN<N, STRIDE, N> {
    static __device__ __forceinline__ void run(uint4*, const uint4*, uint32_t, bool, int, int, int) {}
};
template <int N, int STRIDE, int I = 0>
struct LoadN {
    static __device__ __forceinline__ void run(uint4* v, const uint4* p, bool live, int base, int step, int lim) {
        v[I] = ld_raw16p<I * STRIDE>(p, live && base + step * I < lim);
        LoadN<N, STRIDE, I + 1>::run(v, p, live, base, step, lim);
    }
};
template <int N, int STRIDE>
struct LoadN<N, STRIDE, N> {
    static __device__ __forceinline__ void run(uint4*, const uint4*, bool, int, int, int) {}
};
__device__ __forceinline__ uint4 poll16(const uint4* p, uint32_t tag, bool live) {
    uint32_t it = 0;
    uint4 v;
    while (true) {
        v = ld_raw16p(p, live);
        if (__all_sync(0xffffffffu, v.w == tag) || !live) break;
        if (++it > SPIN_LIMIT) __trap();
    }
    return v;
}
__device__ __forceinline__ void st_zero16(void* p) {
    asm volatile("st.relaxed.gpu.global.v4.u32 [%0], {%1, %1, %1, %1};" ::"l"(p), "r"(0u) : "memory");
}
__device__ __forceinline__ float ex2(float x) {
    float y;
    asm("ex2.approx.ftz.f32 %0, %1;" : "=f"(y) : "f"(x));
    return y;
}
__device__ __forceinline__ float fsqrt(float x) {
    float y;
    asm("sqrt.approx.f32 %0, %1;" : "=f"(y) : "f"(x));
    return y;
}
constexpr float LOG2E = 1.4426950408889634f;
__device__ __forceinline__ float silu(float a) { return __fdividef(a, 1.0f + ex2(-a * LOG2E)); }
__device__ __forceinline__ float warp_sum(float v) {
#pragma unroll
    for (int o = 16; o > 0; o >>= 1) v += __shfl_xor_sync(0xffffffffu, v, o);
    return v;
}

__device__ __forceinline__ void ln_stats(const float (&v)[20], float& mean_b, float& den_b) {
    float s = 0.f;
#pragma unroll
    for (int i = 0; i < 20; i++) s += v[i];
    s = warp_sum(s);
    float mean = s * (1.0f / 640.0f);
    float q = 0.f;
#pragma unroll
    for (int i = 0; i < 20; i++) { float d = v[i] - mean; q += d * d; }
    q = warp_sum(q);
    float var_b = bfr(q * (1.0f / 640.0f));
    mean_b = bfr(mean);
    den_b = bfr(fsqrt(bfr(var_b + 1e-5f)));
}

struct Window {
    uint32_t bar[WIN];
    uint32_t par[WIN];
    __device__ __forceinline__ void init(uint32_t dummy) {
#pragma unroll
        for (int i = 0; i < WIN; i++) { bar[i] = dummy; par[i] = 1; }
    }
    __device__ __forceinline__ void push_tail(uint32_t b, uint32_t p) {
#pragma unroll
        for (int i = 1; i <= WIN - P_TWIN; i++) mbar_wait(bar[i], par[i]);
        push(b, p);
    }
    __device__ __forceinline__ void push(uint32_t b, uint32_t p, bool wait = true) {
        if (wait) mbar_wait(bar[0], par[0]);
#pragma unroll
        for (int i = 0; i + 1 < WIN; i++) { bar[i] = bar[i + 1]; par[i] = par[i + 1]; }
        bar[WIN - 1] = b; par[WIN - 1] = p;
    }
};

__global__ void __launch_bounds__(NTHREADS, 1)
fused_decode_kernel(const __grid_constant__ CUtensorMap tmK, const __grid_constant__ CUtensorMap tmV,
                    const __grid_constant__ CUtensorMap tmMod, const __grid_constant__ CUtensorMap tmWq,
                    const __grid_constant__ CUtensorMap tmWo, const __grid_constant__ CUtensorMap tmW1,
                    const __grid_constant__ CUtensorMap tmW3, const __grid_constant__ CUtensorMap tmW2,
                    const __nv_bfloat16* __restrict__ x_in, const __nv_bfloat16* __restrict__ c_in,
                    __nv_bfloat16* __restrict__ out) {
    extern __shared__ __align__(1024) uint8_t smem[];
    const uint32_t sb = smem_u32(smem);
    const int tid = threadIdx.x, wid = tid >> 5, lane = tid & 31;
    const int cta = blockIdx.x, G = gridDim.x;
    const int grp = cta % NG, rank = cta / NG;
    const uint32_t bars = sb + SM_BARS;
    auto BAR = [&](int i) { return bars + 8u * i; };
    volatile uint32_t* meta = reinterpret_cast<volatile uint32_t*>(smem + SM_META);

    if (wid == 8) {
        mbar_init(BAR(lane), (lane >= B_EMPTY && lane < B_MOD) ? 2 : 1);
        if (lane < B_LAST - 32) mbar_init(BAR(32 + lane), (32 + lane >= B_FLF && 32 + lane < B_FLE) ? 4 : 1);
        asm volatile("fence.mbarrier_init.release.cluster;" ::: "memory");
        asm volatile("fence.proxy.async.shared::cta;" ::: "memory");
        __syncwarp();
        if (lane == 0 && cta < 128) {
            const bool mf = cta < 40;
            const CUtensorMap* tm = mf ? &tmMod : &tmWq;
#pragma unroll 1
            for (int i = 0; i < 4; i++) {
                const uint32_t bar = BAR((mf ? B_MOD : B_WQ) + i);
                mbar_expect_tx(bar, mf ? 10240 : 12288);
                tma2d(sb + (mf ? SM_WMOD + i * 10240 : SM_WQ + i * 12288), tm, cta * (mf ? 32 : 48), i * (mf ? 160 : 128), bar);
            }
        }
    }
    __syncthreads();
    if (sb & 1023u) __trap();

    if (wid == 8) {
        if (tid == 256) {
            Window win;
            unsigned epoch;
            asm volatile("ld.relaxed.gpu.global.u32 %0, [%1];" : "=r"(epoch) : "l"(&g_epoch) : "memory");
            prefetch_tm(&tmWq); prefetch_tm(&tmMod); prefetch_tm(&tmK); prefetch_tm(&tmV);
            const int nmod = cta < 120 ? 4 : 0, nwq = cta < 128 ? 5 : 0;
            win.init(BAR(B_DUMMY));
            auto pro_issue = [&](int i, bool issue) {
                const bool is_mod = cta < 40 ? i < nmod : i >= nwq;
                const int j = cta < 40 ? (is_mod ? i : i - nmod) : (is_mod ? i - nwq : i);
                const uint32_t bar = BAR((is_mod ? B_MOD : B_WQ) + j);
                win.push(bar, 0, issue);
                if (issue) {
                    mbar_expect_tx(bar, is_mod ? 10240 : 12288);
                    if (is_mod) tma2d(sb + SM_WMOD + j * 10240, &tmMod, cta * 32, j * 160, bar);
                    else tma2d(sb + SM_WQ + j * 12288, &tmWq, cta * 48, j * 128, bar);
                }
            };
            prefetch_tm(&tmWo); prefetch_tm(&tmW1); prefetch_tm(&tmW3); prefetch_tm(&tmW2);
            unsigned* ctr = &g_ctr[epoch & 1][grp * 32];
            unsigned* gctr = &g_ctr[epoch & 1][NG * 32];
            if (cta == 0) {
                for (int g = 0; g <= NG; g++) g_ctr[(epoch + 1) & 1][g * 32] = 0;
            }
            unsigned pend = atomicAdd(ctr, 1);
#pragma unroll 1
            for (int i = 0; i < nmod + nwq; i++) pro_issue(i, i >= 4);
            uint64_t pol;
            asm volatile("createpolicy.fractional.L2::evict_first.b64 %0, 1.0;" : "=l"(pol));
            int s = 0; uint32_t par = 0;
            int ntiles = 0, run = -1, last_head = -1;
            bool glob = false;
#pragma unroll 1
            while (true) {
                unsigned t = pend;
                DBG(8);
                if (!glob && t >= (unsigned)GT) { glob = true; t = atomicAdd(gctr, 1); }
                if (glob && t >= (unsigned)PT) break;
                pend = atomicAdd(glob ? gctr : ctr, 1);
                ntiles++;
                const int hl = t / TPH, tile = t % TPH;
                const int head = glob ? NG * GH + hl : grp * GH + hl;
                const int qidx = glob ? GH + hl : hl;
                if (head != last_head) { last_head = head; run++; meta[16 + run] = head; }
                const int line0 = (head * SK + tile * TILE) * 3;
                const bool urgent = glob && t >= (unsigned)(PT - P_URG);
#pragma unroll 1
                for (int kv = 0; kv < 2; kv++) {
                    win.push(BAR(B_FULL + s), par, !urgent);
                    mbar_wait(BAR(B_EMPTY + s), par ^ 1);
                    meta[s] = run | (qidx << 8);
                    mbar_expect_tx(BAR(B_FULL + s), CHUNK);
                    tma2d_hint(sb + SM_RING + s * CHUNK, kv ? &tmV : &tmK, 0, line0, BAR(B_FULL + s), pol);
                    DBG(6 + kv);
                    if (++s == NSLOT) { s = 0; par ^= 1; }
                }
            }
            TS(5);
            meta[16 + run + 1] = 0xFFu;
#pragma unroll 1
            for (int e = 0; e < 2; e++) {
                mbar_wait(BAR(B_EMPTY + s), par ^ 1);
                meta[s] = (run + 1) | META_END;
                mbar_arrive(BAR(B_FULL + s));
                if (++s == NSLOT) { s = 0; par ^= 1; }
                if (++s == NSLOT) { s = 0; par ^= 1; }
            }
#pragma unroll
            for (int i = 0; i < WIN - P_HOLD; i++) mbar_wait(win.bar[i], win.par[i]);
            TS(12);
            if (cta < 128) {
                mbar_wait(BAR(B_PRO), 0);
#pragma unroll 1
                for (int i = 0; i < 5; i++) {
                    win.push_tail(BAR(B_WO + i), 0);
                    mbar_expect_tx(BAR(B_WO + i), 12288);
                    tma2d(sb + SM_WO + (2 * i) * 6144, &tmWo, (2 * i) * 64, cta * 48, BAR(B_WO + i));
                    tma2d(sb + SM_WO + (2 * i + 1) * 6144, &tmWo, (2 * i + 1) * 64, cta * 48, BAR(B_WO + i));
                }
                if (cta < 96) {
#pragma unroll 1
                    for (int i = 0; i < 4; i++) {
                        const int m = i & 1, hf = i >> 1;
                        const uint32_t bar = BAR((m ? B_W3 : B_W1) + hf);
                        const uint32_t dst = sb + (m ? SM_W3 : SM_W1) + hf * 10240;
                        const CUtensorMap* tm = m ? &tmW3 : &tmW1;
                        win.push_tail(bar, 0);
                        mbar_expect_tx(bar, 10240);
                        tma2d(dst, tm, cta * 16, hf * 320, bar);
                        tma2d(dst + 5120, tm, cta * 16, hf * 320 + 160, bar);
                    }
#pragma unroll 1
                    for (int i = 0; i < 2; i++) {
                        win.push_tail(BAR(B_W2 + i), 0);
                        mbar_wait(BAR(B_EMPTY + s), par ^ 1);
                        meta[10 + i] = s;
                        mbar_expect_tx(BAR(B_W2 + i), 10240);
#pragma unroll 1
                        for (int b = 0; b < 5; b++)
                            tma2d(sb + SM_RING + s * CHUNK + b * 2048, &tmW2, (5 * i + b) * 64, cta * 16, BAR(B_W2 + i));
                        if (++s == NSLOT) { s = 0; par ^= 1; }
                    }
                }
            }
            TS(6);
        }
    } else {
    const int g4 = lane >> 2, j4 = lane & 3, mi = lane >> 3, l8 = lane & 7;
    uint32_t* sc32 = reinterpret_cast<uint32_t*>(smem + SM_SC);
    uint32_t* h32 = reinterpret_cast<uint32_t*>(smem + SM_H);
    uint32_t* x32 = reinterpret_cast<uint32_t*>(smem + SM_X);
    uint32_t* q32 = reinterpret_cast<uint32_t*>(smem + SM_Q);
    float* red = reinterpret_cast<float*>(smem + SM_RED);
    float* stage = reinterpret_cast<float*>(smem + SM_STAGE);
    float* own = reinterpret_cast<float*>(smem + SM_OWN);

    uint32_t tag;
    bool live = true;
    {
    {
        const uint32_t* cg = reinterpret_cast<const uint32_t*>(c_in);
        const uint32_t* xg = reinterpret_cast<const uint32_t*>(x_in);
        uint32_t c0 = cg[tid], x0 = xg[tid], c1 = 0, x1 = 0;
        if (tid < 64) { c1 = cg[256 + tid]; x1 = xg[256 + tid]; }
        unsigned epoch = 0;
        if (tid == 0) asm volatile("ld.relaxed.gpu.global.u32 %0, [%1];" : "=r"(epoch) : "l"(&g_epoch) : "memory");
        sc32[tid] = pack_bf(silu(bf_lo(c0)), silu(bf_hi(c0))); x32[tid] = x0;
        if (tid < 64) { sc32[256 + tid] = pack_bf(silu(bf_lo(c1)), silu(bf_hi(c1))); x32[256 + tid] = x1; }
        if (tid == 0) meta[8] = epoch + 1;
    }
    bar_cons();
    tag = meta[8];
    if (wid == 0) EARLY(3);
    {
        if (cta < 120 && tid >= 128 && tid < 136) st_zero16(reinterpret_cast<uint4*>(&g_mod[cta * 16]) + (tid - 128));
        if (cta < 128 && tid >= 32 && tid < 44) st_zero16(reinterpret_cast<uint4*>(&g_q[cta * 24]) + (tid - 32));
        if (cta < 128) {
            if (tid >= 64 && tid < 66) st_zero16(&g_x2[cta][tid - 64]);
            st_zero16(&g_h1[tid >> 1][cta][tid & 1]);
            if (cta < 96) st_zero16(&g_h3[tid >> 1][cta][tid & 1]);
        }
#pragma unroll 1
        for (int f = tid >> 6; f < NQH; f += 4) {
            const int head = f < GH ? grp * GH + f : NG * GH + (f - GH);
            const int idx = f < GH ? rank : cta;
            st_zero16(&g_dat[head][idx][tid & 63]);
            if ((tid & 63) == 0) st_zero16(&g_hdr[head][idx]);
        }
    }

    float mean_x = 0.f, rden_x = 1.f;
    if (cta < 128) {
        float xv[20];
#pragma unroll
        for (int i = 0; i < 10; i++) { uint32_t v = x32[lane + 32 * i]; xv[2 * i] = bf_lo(v); xv[2 * i + 1] = bf_hi(v); }
        float den;
        ln_stats(xv, mean_x, den);
        rden_x = __fdividef(1.0f, den);
    }

#pragma unroll 1
    for (int step = 0; step < 2; step++) {
    if (wid >= 4 && (step == 0 ? cta < 40 : (cta >= 40 && cta < 120))) {
        const int w4 = wid - 4;
        float acc[2][4] = {};
        const uint32_t base = sb + SM_WMOD + w4 * 10240;
        mbar_wait(BAR(B_MOD + w4), 0);
        EARLY(4 + w4);
#pragma unroll
        for (int hf = 0; hf < 2; hf++) {
            uint32_t a[5][2][4], bb[5][2];
#pragma unroll
            for (int ks = 0; ks < 5; ks++) {
                const int r0 = w4 * 160 + hf * 80 + ks * 16;
                bb[ks][0] = sc32[(r0 >> 1) + j4]; bb[ks][1] = sc32[(r0 >> 1) + 4 + j4];
                const int r = hf * 80 + ks * 16 + l8 + 8 * (mi >> 1);
#pragma unroll
                for (int mt = 0; mt < 2; mt++) ldsm4t(a[ks][mt], base + r * 64 + (((2 * mt + (mi & 1)) ^ ((r >> 1) & 3)) << 4));
            }
#pragma unroll
            for (int ks = 0; ks < 5; ks++) { mma16816(acc[0], a[ks][0], bb[ks][0], bb[ks][1]); mma16816(acc[1], a[ks][1], bb[ks][0], bb[ks][1]); }
        }
        float* red2 = reinterpret_cast<float*>(smem + SM_FIN);
        if (j4 == 0) {
#pragma unroll
            for (int mt = 0; mt < 2; mt++) { red2[w4 * 32 + mt * 16 + g4] = acc[mt][0]; red2[w4 * 32 + mt * 16 + 8 + g4] = acc[mt][2]; }
        }
        asm volatile("bar.sync 3, 128;" ::: "memory");
        if (wid == 4) EARLY(8);
        if (wid == 4) {
            float v = (red2[lane] + red2[32 + lane]) + (red2[64 + lane] + red2[96 + lane]);
            float o = __shfl_down_sync(0xffffffffu, v, 1);
            if (!(lane & 1)) st_pk8(&g_mod[cta * 16 + (lane >> 1)], pack_bf(v, o), tag);
            if (step == 1 && lane == 0) mbar_arrive(BAR(B_PRO));
        }
        TS(1);
    }
    if (step == 1) break;
    if (cta < 128) {
        {
            const int off[4] = {tid, 320 + tid, tid < 64 ? 256 + tid : tid, tid < 64 ? 576 + tid : 320 + tid};
            uint32_t val[4];
            poll8<4>(g_mod, off, val, tag);
#pragma unroll
            for (int rep = 0; rep < 2; rep++) {
                int p = tid + rep * 256;
                if (p < 320) {
                    uint32_t sa = val[2 * rep], ca = val[2 * rep + 1];
                    uint32_t xx = x32[p];
                    float n0 = bfr(bfr(bf_lo(xx) - mean_x) * rden_x), n1 = bfr(bfr(bf_hi(xx) - mean_x) * rden_x);
                    float h0 = bfr(n0 * bfr(1.0f + bf_lo(ca))) + bf_lo(sa);
                    float h1 = bfr(n1 * bfr(1.0f + bf_hi(ca))) + bf_hi(sa);
                    h32[p] = pack_bf(h0, h1);
                }
            }
        }
        bar_cons();
        TS(2);
        float acc[3][4] = {};
        uint32_t a[5][3][4], bb[5][2];
#pragma unroll
        for (int ks = 0; ks < 5; ks++) {
            const int r0 = wid * 80 + ks * 16;
            bb[ks][0] = h32[(r0 >> 1) + j4]; bb[ks][1] = h32[(r0 >> 1) + 4 + j4];
        }
        mbar_wait(BAR(B_WQ + ((wid * 80) >> 7)), 0);
        mbar_wait(BAR(B_WQ + ((wid * 80 + 79) >> 7)), 0);
        if (wid == 0) EARLY(9);
        if (wid == 7) EARLY(10);
#pragma unroll
        for (int ks = 0; ks < 5; ks++) {
            const int r = wid * 80 + ks * 16 + l8 + 8 * (mi >> 1);
#pragma unroll
            for (int mt = 0; mt < 3; mt++) ldsm4t(a[ks][mt], sb + SM_WQ + r * 96 + ((2 * mt + (mi & 1)) << 4));
        }
#pragma unroll
        for (int ks = 0; ks < 5; ks++) {
#pragma unroll
            for (int mt = 0; mt < 3; mt++) mma16816(acc[mt], a[ks][mt], bb[ks][0], bb[ks][1]);
        }
        if (j4 == 0) {
#pragma unroll
            for (int mt = 0; mt < 3; mt++) { red[wid * 64 + mt * 16 + g4] = acc[mt][0]; red[wid * 64 + mt * 16 + 8 + g4] = acc[mt][2]; }
        }
        bar_cons();
        if (tid < 64) {
            float v = 0.f;
            if (tid < 48) {
#pragma unroll
                for (int w = 0; w < 8; w++) v += red[w * 64 + tid];
            }
            float o = __shfl_down_sync(0xffffffffu, v, 1);
            if (tid < 48 && !(tid & 1)) st_pk8(&g_q[cta * 24 + (tid >> 1)], pack_bf(v, o), tag);
        }
        TS(3);
    }
    {
        int off[5];
#pragma unroll
        for (int j = 0; j < 5; j++) {
            int p = tid + 256 * j;
            if (p >= NQH * 96) p = tid;
            off[j] = p < GH * 96 ? grp * GH * 96 + p : NG * GH * 96 + (p - GH * 96);
        }
        uint32_t val[5];
        poll8<5>(g_q, off, val, tag);
#pragma unroll
        for (int j = 0; j < 5; j++)
            if (tid + 256 * j < NQH * 96) q32[tid + 256 * j] = val[j];
    }
    bar_cons();
    if (tid == 0 && !(cta >= 40 && cta < 120)) mbar_arrive(BAR(B_PRO));
    TS(4);
    }

    if (wid < 4) {
        const int pair = wid >> 1, half = wid & 1;
        uint32_t offK[3], offV[3];
        {
            const int rowK = half * 16 + l8 + 8 * (mi & 1), hiK = mi >> 1;
            const int rowV = half * 16 + l8 + 8 * (mi >> 1), hiV = mi & 1;
#pragma unroll
            for (int t = 0; t < 3; t++) {
                offK[t] = (rowK * 3 + t) * 128 + ((hiK ^ ((rowK * 3 + t) & 7)) << 4);
                offV[t] = (rowV * 3 + t) * 128 + ((hiV ^ ((rowV * 3 + t) & 7)) << 4);
                asm volatile("" : "+r"(offK[t]), "+r"(offV[t]));
            }
        }
        float acc[12][4];
#pragma unroll
        for (int i = 0; i < 12; i++) { acc[i][0] = acc[i][1] = acc[i][2] = acc[i][3] = 0.f; }
        float m_run = NEG_BIG, l_run = 0.f;
        uint32_t qf[12][2];
#pragma unroll
        for (int i = 0; i < 12; i++) { qf[i][0] = qf[i][1] = 0; }
        int cur = -1, flushed = 0, cnt = 0;
        int s = 2 * pair; uint32_t par = 0;
        int fb = 0; uint32_t fpar = 1;
        uint32_t ready = 0;
#pragma unroll 1
        while (true) {
            if (!ready) mbar_wait(BAR(B_FULL + s), par);
            const uint32_t mt_ = meta[s];
            const int run = mt_ & 0xff;
            if (mt_ & META_END) CLK(20);
            if ((mt_ & META_END) && half == 0) DBG(4 + pair);
            if (run != cur) {
#pragma unroll 1
                while (flushed < run) {
                    const uint32_t fle = mbar_try(BAR(B_FLE + fb), fpar);
                    float* mb = reinterpret_cast<float*>(smem + SM_MERGE) + (fb * 4 + wid) * 200;
                    if (flushed != cur) {
#pragma unroll
                        for (int i = 0; i < 12; i++) { acc[i][0] = acc[i][2] = 0.f; }
                        m_run = NEG_BIG; l_run = 0.f; cnt = 0;
                    }
                    float l = l_run;
                    l += __shfl_xor_sync(0xffffffffu, l, 4);
                    l += __shfl_xor_sync(0xffffffffu, l, 8);
                    l += __shfl_xor_sync(0xffffffffu, l, 16);
                    if (!fle) mbar_wait(BAR(B_FLE + fb), fpar);
                    if (j4 == 0) {
#pragma unroll
                        for (int i = 0; i < 12; i++) { mb[4 + 16 * i + g4] = acc[i][0]; mb[4 + 16 * i + 8 + g4] = acc[i][2]; }
                    }
                    if (lane == 0) { mb[0] = m_run; mb[1] = l; mb[2] = __int_as_float(cnt); }
                    __syncwarp();
                    if (lane == 0) mbar_arrive(BAR(B_FLF + fb));
                    if (++fb == NBUF) { fb = 0; fpar ^= 1; }
                    flushed++;
                    cur = -1;
                }
                if (mt_ & META_END) {
                    CLK(21);
                    if (flushed == 0 && lane == 0) mbar_arrive(BAR(B_FLF));
                    break;
                }
                cur = run;
                const int qi = (mt_ >> 8) & 0xff;
#pragma unroll
                for (int i = 0; i < 12; i++) { acc[i][0] = acc[i][1] = acc[i][2] = acc[i][3] = 0.f; }
                m_run = NEG_BIG; l_run = 0.f; cnt = 0;
#pragma unroll
                for (int ks = 0; ks < 12; ks++) {
                    qf[ks][0] = q32[qi * 96 + ks * 8 + j4];
                    qf[ks][1] = q32[qi * 96 + ks * 8 + 4 + j4];
                }
            }
            cnt++;
            if (half == 0) DBG(pair);
            const uint32_t kb = sb + SM_RING + s * CHUNK;
            int sv = s + 1; uint32_t parv = par;
            if (sv == NSLOT) { sv = 0; parv ^= 1; }
            float sc[6][4] = {};
            uint32_t vready;
            {
                uint32_t a[12][4];
#pragma unroll
                for (int t = 0; t < 3; t++) {
                    const uint32_t bt = kb + offK[t];
#pragma unroll
                    for (int kk = 0; kk < 4; kk++) ldsm4(a[t * 4 + kk], bt ^ (kk << 5));
                }
                vready = mbar_try(BAR(B_FULL + sv), parv);
#pragma unroll
                for (int i = 0; i < 12; i++) mma16816(sc[i % 6], a[i], qf[i][0], qf[i][1]);
            }
            __syncwarp();
            if (lane == 0) mbar_arrive(BAR(B_EMPTY + s));
            const float scale = 0.07216878364870322f;
            float s0 = bfr(bfr(((sc[0][0] + sc[1][0]) + (sc[2][0] + sc[3][0])) + (sc[4][0] + sc[5][0])) * scale);
            float s1 = bfr(bfr(((sc[0][2] + sc[1][2]) + (sc[2][2] + sc[3][2])) + (sc[4][2] + sc[5][2])) * scale);
            float tm = fmaxf(s0, s1);
            tm = fmaxf(tm, __shfl_xor_sync(0xffffffffu, tm, 4));
            tm = fmaxf(tm, __shfl_xor_sync(0xffffffffu, tm, 8));
            tm = fmaxf(tm, __shfl_xor_sync(0xffffffffu, tm, 16));
            if (tm > m_run) {
                float alpha = ex2((m_run - tm) * LOG2E);
                l_run *= alpha;
#pragma unroll
                for (int i = 0; i < 12; i++) { acc[i][0] *= alpha; acc[i][1] *= alpha; acc[i][2] *= alpha; acc[i][3] *= alpha; }
                m_run = tm;
            }
            float p0 = ex2((s0 - m_run) * LOG2E);
            float p1 = ex2((s1 - m_run) * LOG2E);
            l_run += p0 + p1;
            const uint32_t pw = pack_bf(p0, p1);
            const uint32_t pa = __shfl_sync(0xffffffffu, pw, 8 * j4), pb = __shfl_sync(0xffffffffu, pw, 8 * j4 + 4);
            const uint32_t b0 = __byte_perm(pa, pb, 0x5410), b1 = __byte_perm(pa, pb, 0x7632);
            if (!vready) mbar_wait(BAR(B_FULL + sv), parv);
            s += 4;
            if (s >= NSLOT) { s -= NSLOT; par ^= 1; }
            if (half == 0) DBG(2 + pair);
            ready = mbar_try(BAR(B_FULL + s), par);
            const uint32_t vb = sb + SM_RING + sv * CHUNK;
            {
                uint32_t a[12][4];
#pragma unroll
                for (int t = 0; t < 3; t++) {
                    const uint32_t bt = vb + offV[t];
#pragma unroll
                    for (int kk = 0; kk < 4; kk++) ldsm4t(a[t * 4 + kk], bt ^ (kk << 5));
                }
#pragma unroll
                for (int i = 0; i < 12; i++) mma16816(acc[i], a[i], b0, b1);
            }
            __syncwarp();
            if (lane == 0) mbar_arrive(BAR(B_EMPTY + sv));
        }
        TS(7);
        CLK(18);
    } else if (wid == 4) {
        int fb = 0; uint32_t fpar = 0;
#pragma unroll 1
        for (int f = 0;; f++) {
            const float* mb = reinterpret_cast<const float*>(smem + SM_MERGE) + fb * 800;
            mbar_wait(BAR(B_FLF + fb), fpar);
            const int head = (int)meta[16 + f];
            if (head == 0xFF) break;
            float m0 = mb[0], m1 = mb[200], m2 = mb[400], m3 = mb[600];
            float M = fmaxf(fmaxf(m0, m1), fmaxf(m2, m3));
            float w0 = ex2((m0 - M) * LOG2E), w1 = ex2((m1 - M) * LOG2E);
            float w2 = ex2((m2 - M) * LOG2E), w3 = ex2((m3 - M) * LOG2E);
            const int idx = head < NG * GH ? rank : cta;
            uint4* dst = &g_dat[head][idx][0];
            float o[6];
#pragma unroll
            for (int i = 0; i < 6; i++) {
                int d = 4 + (i < 3 ? 3 * lane + i : 96 + 3 * lane + (i - 3));
                o[i] = w0 * mb[d] + w1 * mb[200 + d] + w2 * mb[400 + d] + w3 * mb[600 + d];
            }
            float L = w0 * mb[1] + w1 * mb[201] + w2 * mb[401] + w3 * mb[601];
            const uint32_t tiles = __float_as_int(mb[2]) + __float_as_int(mb[402]);
            st_pk16(dst + lane, __float_as_uint(o[0]), __float_as_uint(o[1]), __float_as_uint(o[2]), tag);
            st_pk16(dst + 32 + lane, __float_as_uint(o[3]), __float_as_uint(o[4]), __float_as_uint(o[5]), tag);
            if (lane == 0) st_pk16(&g_hdr[head][idx], __float_as_uint(M), __float_as_uint(L), tiles, tag);
            __syncwarp();
            if (lane == 0) mbar_arrive(BAR(B_FLE + fb));
            if (++fb == NBUF) { fb = 0; fpar ^= 1; }
            if (meta[16 + f + 1] == 0xFFu) break;
        }
        TS(8);
        CLK(18);
    } else if (wid >= 6) {
        if (cta < 128) {
            const int t = tid - 192;
            uint32_t* cb32 = reinterpret_cast<uint32_t*>(smem + SM_CB);
            uint32_t* sb32 = reinterpret_cast<uint32_t*>(smem + SM_SB);
            const int col = cta * 5 + t;
            int off[12];
            uint32_t val[12];
#pragma unroll
            for (int rep = 0; rep < 5; rep++) { off[2 * rep] = 960 + t + 64 * rep; off[2 * rep + 1] = 1280 + t + 64 * rep; }
            off[10] = t < 5 ? (1280 + col) >> 1 : 960;
            off[11] = t < 5 ? (3200 + col) >> 1 : 960;
            poll8<12>(g_mod, off, val, tag);
#pragma unroll
            for (int rep = 0; rep < 5; rep++) {
                sb32[t + 64 * rep] = val[2 * rep];
                cb32[t + 64 * rep] = pack_bf(1.0f + bf_lo(val[2 * rep + 1]), 1.0f + bf_hi(val[2 * rep + 1]));
            }
            if (t < 5) {
                own[t] = (col & 1) ? bf_hi(val[10]) : bf_lo(val[10]);
                own[8 + t] = (col & 1) ? bf_hi(val[11]) : bf_lo(val[11]);
                uint32_t xx = x32[col >> 1];
                own[16 + t] = (col & 1) ? bf_hi(xx) : bf_lo(xx);
            }
        }
        live = false;
    }
    }
    const uint32_t sb0 = sb;
    const int tid0 = tid;
#pragma unroll 1
    while (cta < 128) {
        uint32_t sb = sb0; int tid = tid0;
        asm volatile("" : "+r"(sb), "+r"(tid));
        const int wid = tid >> 5, lane = tid & 31;
        const int g4 = lane >> 2, j4 = lane & 3, mi = lane >> 3, l8 = lane & 7;
        CLK(19);
        if (wid >= 5) {
            const int h = cta >> 2, js = cta & 3;
            const bool gl = h >= NG * GH;
            const int ncand = gl ? G : (G - h / GH + NG - 1) / NG;
            const int k = lane & 15, rr = (wid - 5) * 2 + (lane >> 4);
            if (live) {
                const unsigned* cp = &g_ctr[(tag - 1) & 1][(gl ? NG : h / GH) * 32];
                const unsigned thr = ((gl ? h - NG * GH : h % GH) + 1) * TPH;
                uint32_t it = 0;
                while (true) {
                    unsigned v;
                    asm volatile("ld.relaxed.gpu.global.u32 %0, [%1];" : "=r"(v) : "l"(cp) : "memory");
                    if (v >= thr) break;
                    __nanosleep(300);
                    if (++it > SPIN_LIMIT) __trap();
                }
            }
            const uint4* hdr = &g_hdr[h][lane];
            const uint4* dat = &g_dat[h][rr][16 * js + k];
            float* part = stage;
            float L, a0, a1, a2;
            uint32_t it = 0;
            uint4 hd[5], dv[MAXG / 6];
#pragma unroll
            for (int i = 0; i < 5; i++) hd[i] = make_uint4(0, 0, 0, 0);
#pragma unroll
            for (int i = 0; i < MAXG / 6; i++) dv[i] = make_uint4(0, 0, 0, 0);
#pragma unroll 1
            while (true) {
                FreshN<5, 32>::run(hd, hdr, tag, live, lane, 32, ncand);
                FreshN<MAXG / 6, 6 * 64>::run(dv, dat, tag, live, rr, 6, ncand);
                float w[5], M = NEG_BIG;
                int c = 0;
#pragma unroll
                for (int i = 0; i < 5; i++) {
                    const bool v = hd[i].w == tag;
                    w[i] = v ? __uint_as_float(hd[i].x) : NEG_BIG;
                    M = fmaxf(M, w[i]);
                    c += v ? (int)hd[i].z : 0;
                }
                c = __reduce_add_sync(0xffffffffu, c);
                if (++it > SPIN_LIMIT) __trap();
                if (live && c != TPH) continue;
                CLK(1);
#pragma unroll
                for (int o = 16; o > 0; o >>= 1) M = fmaxf(M, __shfl_xor_sync(0xffffffffu, M, o));
                float ls = 0.f;
#pragma unroll
                for (int i = 0; i < 5; i++) {
                    const bool v = w[i] != NEG_BIG;
                    const float e = ex2((w[i] - M) * LOG2E);
                    w[i] = v ? e : -0.0f;
                    ls = fmaf(w[i], __uint_as_float(hd[i].y), ls);
                }
                float* wsm = reinterpret_cast<float*>(smem + SM_X2) + (wid - 5) * 160;
                if (live) {
#pragma unroll
                    for (int i = 0; i < 5; i++) wsm[lane + 32 * i] = w[i];
                }
                __syncwarp();
                uint32_t badm = 0;
                a0 = a1 = a2 = 0.f;
#pragma unroll
                for (int i = 0; i < MAXG / 6; i++) {
                    const float wi = wsm[rr + 6 * i];
                    badm |= (dv[i].w ^ tag) & ~(uint32_t)(__float_as_int(wi) >> 31);
                    a0 = fmaf(wi, __uint_as_float(dv[i].x), a0);
                    a1 = fmaf(wi, __uint_as_float(dv[i].y), a1);
                    a2 = fmaf(wi, __uint_as_float(dv[i].z), a2);
                }
                const bool bad = badm != 0;
                __syncwarp();
                L = warp_sum(ls);
                if (!__any_sync(0xffffffffu, bad) || !live) break;
            }
            a0 += __shfl_xor_sync(0xffffffffu, a0, 16);
            a1 += __shfl_xor_sync(0xffffffffu, a1, 16);
            a2 += __shfl_xor_sync(0xffffffffu, a2, 16);
            CLK(2);
            if (live && lane < 16) { float* pp = part + (wid - 5) * 48 + 3 * k; pp[0] = a0; pp[1] = a1; pp[2] = a2; }
            if (live) asm volatile("bar.sync 2, 96;" ::: "memory");
            if (wid == 5 || !live) {
                uint16_t* osw = reinterpret_cast<uint16_t*>(smem + SM_SC);
                const float inv = __fdividef(1.0f, L);
                const float o0 = (part[lane] + part[48 + lane]) + part[96 + lane];
                const float o1 = (part[32 + (lane & 15)] + part[80 + (lane & 15)]) + part[128 + (lane & 15)];
                if (live) { osw[lane] = (uint16_t)(__float_as_uint(bfr(o0 * inv)) >> 16); if (lane < 16) osw[32 + lane] = (uint16_t)(__float_as_uint(bfr(o1 * inv)) >> 16); }
            }
            if (live) TS(10);
        }
        if (wid < 5 || !live) {
            const int w5 = wid < 5 ? wid : wid - 5;
            uint32_t wa[8][3][4];
            if (live) mbar_wait(BAR(B_WO + w5), 0);
#pragma unroll
            for (int i = 0; i < 8; i++) {
                const int cc = 2 * (i & 3) + (mi & 1);
#pragma unroll
                for (int ks = 0; ks < 3; ks++) {
                    const int r = ks * 16 + l8 + 8 * (mi >> 1);
                    ldsm4t(wa[i][ks], sb + SM_WO + (2 * w5 + (i >> 2)) * 6144 + r * 128 + ((cc ^ (r & 7)) << 4));
                }
            }
            if (live) bar_cons();
            if (live) TS(9);
            CLK(3);
            const uint32_t* os32 = reinterpret_cast<const uint32_t*>(smem + SM_SC);
            float acc[8][4] = {};
#pragma unroll
            for (int ks = 0; ks < 3; ks++) {
                const uint32_t b0 = os32[ks * 8 + j4], b1 = os32[ks * 8 + 4 + j4];
#pragma unroll
                for (int i = 0; i < 8; i++) mma16816(acc[i], wa[i][ks], b0, b1);
            }
            if (live && j4 == 0) {
#pragma unroll
                for (int i = 0; i < 8; i++) { stage[(w5 * 8 + i) * 16 + g4] = acc[i][0]; stage[(w5 * 8 + i) * 16 + 8 + g4] = acc[i][2]; }
            }
        } else {
            bar_cons();
        }
        CLK(4);
        if (live) bar_cons();
        {
            const int o = tid >> 1, kk = tid & 1;
            const float* sp = stage + o * 5 + kk * 3;
            float v0 = sp[0], v1 = sp[1], v2 = kk ? 0.f : sp[2];
            if (live) st_pk16(&g_h1[o][cta][kk], __float_as_uint(v0), __float_as_uint(v1), __float_as_uint(v2), tag);
        }
        if (live) TS(11);
        CLK(5);
        if (wid == 0 || !live) {
            const uint4* p = &g_h1[cta][0][0] + lane;
            uint4 v[8];
            uint32_t it = 0;
            while (true) {
                bool ok = true;
                LoadN<8, 32>::run(v, p, live, 0, 0, 1);
#pragma unroll
                for (int j = 0; j < 8; j++) ok = ok && v[j].w == tag;
                if (__all_sync(0xffffffffu, ok) || !live) break;
                if (++it > SPIN_LIMIT) __trap();
            }
            CLK(6);
            float a0 = 0.f, a1 = 0.f, a2 = 0.f;
#pragma unroll
            for (int j = 0; j < 8; j++) { a0 += __uint_as_float(v[j].x); a1 += __uint_as_float(v[j].y); a2 += __uint_as_float(v[j].z); }
#pragma unroll
            for (int o = 2; o <= 16; o <<= 1) {
                a0 += __shfl_xor_sync(0xffffffffu, a0, o);
                a1 += __shfl_xor_sync(0xffffffffu, a1, o);
                a2 += __shfl_xor_sync(0xffffffffu, a2, o);
            }
            const float gx = own[lane & 7], xx = own[16 + (lane & 7)];
            const float t0 = __shfl_sync(0xffffffffu, a0, lane >= 3), t1 = __shfl_sync(0xffffffffu, a1, lane >= 3);
            const float sum = (lane == 0 || lane == 3) ? t0 : (lane == 2 ? a2 : t1);
            const float x2 = bfr(xx + bfr(gx * bfr(sum)));
            if (live && lane < 5) own[24 + lane] = x2;
            const float y1 = __shfl_sync(0xffffffffu, x2, 1), y2 = __shfl_sync(0xffffffffu, x2, 2);
            const float y3 = __shfl_sync(0xffffffffu, x2, 3), y4 = __shfl_sync(0xffffffffu, x2, 4);
            if (live && lane == 0) st_pk16(&g_x2[cta][0], pack_bf(x2, y1), pack_bf(y2, y3), pack_bf(y4, 0.f), tag);
            if (live) TS(13);
        }
        CLK(8);
        if (cta < 96) {
            uint32_t a1[5][4], a3[5][4], a2[5][4];
            if (live) mbar_wait3(BAR(B_W1 + (wid >> 2)), BAR(B_W3 + (wid >> 2)), BAR(B_W2 + (wid >> 2)));
            const uint32_t w2b = sb + SM_RING + meta[10 + (wid >> 2)] % NSLOT * CHUNK;
#pragma unroll
            for (int ks = 0; ks < 5; ks++) {
                const int r = wid * 80 + ks * 16 + l8 + 8 * (mi >> 1);
                const uint32_t off = r * 32 + (((mi & 1) ^ ((r >> 2) & 1)) << 4);
                ldsm4t(a1[ks], sb + SM_W1 + off);
                ldsm4t(a3[ks], sb + SM_W3 + off);
            }
#pragma unroll
            for (int i = 0; i < 5; i++) {
                const int mt = (wid & 3) * 5 + i;
                const int cc = 2 * (mt & 3) + (mi & 1);
                const int r = l8 + 8 * (mi >> 1);
                ldsm4t(a2[i], w2b + (mt >> 2) * 2048 + r * 128 + ((cc ^ (r & 7)) << 4));
            }
            CLK(9);
            float* x2s = reinterpret_cast<float*>(smem + SM_X2);
            float* st8 = red + 256;
            if (wid >= 4) {
                uint4 v = poll16(&g_x2[tid - 128][0], tag, live);
                const float e0 = bf_lo(v.x), e1 = bf_hi(v.x), e2 = bf_lo(v.y), e3 = bf_hi(v.y), e4 = bf_lo(v.z);
                float* d = x2s + (tid - 128) * 5;
                if (live) { d[0] = e0; d[1] = e1; d[2] = e2; d[3] = e3; d[4] = e4; }
                const float pv = __shfl_sync(0xffffffffu, e0, 0);
                const float d0 = e0 - pv, d1 = e1 - pv, d2 = e2 - pv, d3 = e3 - pv, d4 = e4 - pv;
                float s1 = ((d0 + d1) + (d2 + d3)) + d4;
                float s2 = fmaf(d0, d0, fmaf(d1, d1, fmaf(d2, d2, fmaf(d3, d3, d4 * d4))));
#pragma unroll
                for (int o = 16; o > 0; o >>= 1) { s1 += __shfl_xor_sync(0xffffffffu, s1, o); s2 += __shfl_xor_sync(0xffffffffu, s2, o); }
                if (live && lane == 0) { st8[2 * (wid - 4)] = pv + s1 * (1.0f / 160.0f); st8[2 * (wid - 4) + 1] = s2 - s1 * s1 * (1.0f / 160.0f); }
            }
            if (live) bar_cons();
            if (live) TS(14);
            CLK(10);
            const float4 sA = *reinterpret_cast<const float4*>(st8), sB = *reinterpret_cast<const float4*>(st8 + 4);
            const float mean = ((sA.x + sA.z) + (sB.x + sB.z)) * 0.25f;
            const float u0 = sA.x - mean, u1 = sA.z - mean, u2 = sB.x - mean, u3 = sB.z - mean;
            const float m2 = ((sA.y + sA.w) + (sB.y + sB.w)) + 160.0f * ((u0 * u0 + u1 * u1) + (u2 * u2 + u3 * u3));
            const float mean_b = bfr(mean);
            const float rden = __fdividef(1.0f, bfr(fsqrt(bfr(bfr(m2 * (1.0f / 640.0f)) + 1e-5f))));
            const uint32_t* cb32 = reinterpret_cast<const uint32_t*>(smem + SM_CB);
            const uint32_t* sb32 = reinterpret_cast<const uint32_t*>(smem + SM_SB);
#pragma unroll
            for (int rep = 0; rep < 2; rep++) {
                const int p = lane + 32 * rep;
                if (p < 40) {
                    int pp = wid * 40 + p;
                    const float2 xv = *reinterpret_cast<const float2*>(x2s + 2 * pp);
                    uint32_t cv = cb32[pp], sv = sb32[pp];
                    float n0 = bfr(bfr(xv.x - mean_b) * rden), n1 = bfr(bfr(xv.y - mean_b) * rden);
                    uint32_t hv = pack_bf(bfr(n0 * bf_lo(cv)) + bf_lo(sv), bfr(n1 * bf_hi(cv)) + bf_hi(sv));
                    if (live) h32[pp] = hv;
                }
            }
            __syncwarp();
            CLK(11);
            float ag[2][4] = {}, au[2][4] = {};
#pragma unroll
            for (int ks = 0; ks < 5; ks++) {
                const int r0 = wid * 80 + ks * 16;
                const uint32_t b0 = h32[(r0 >> 1) + j4], b1 = h32[(r0 >> 1) + 4 + j4];
                mma16816(ag[ks & 1], a1[ks], b0, b1);
                mma16816(au[ks & 1], a3[ks], b0, b1);
            }
            if (live && j4 == 0) {
                red[wid * 32 + g4] = ag[0][0] + ag[1][0]; red[wid * 32 + 8 + g4] = ag[0][2] + ag[1][2];
                red[wid * 32 + 16 + g4] = au[0][0] + au[1][0]; red[wid * 32 + 24 + g4] = au[0][2] + au[1][2];
            }
            CLK(12);
            if (live) bar_cons();
            if (live) TS(15);
            CLK(13);
            float v = 0.f;
#pragma unroll
            for (int w = 0; w < 8; w++) v += red[w * 32 + lane];
            v = bfr(v);
            float up = __shfl_down_sync(0xffffffffu, v, 16);
            float hact = bfr(bfr(silu(v)) * up);
            float e0 = __shfl_sync(0xffffffffu, hact, 2 * j4), e1 = __shfl_sync(0xffffffffu, hact, 2 * j4 + 1);
            float e2 = __shfl_sync(0xffffffffu, hact, 2 * j4 + 8), e3 = __shfl_sync(0xffffffffu, hact, 2 * j4 + 9);
            const uint32_t b0 = pack_bf(e0, e1), b1 = pack_bf(e2, e3);
            float acc[5][4] = {};
#pragma unroll
            for (int i = 0; i < 5; i++) mma16816(acc[i], a2[i], b0, b1);
            if (live && j4 == 0) {
#pragma unroll
                for (int i = 0; i < 5; i++) { stage[(wid * 5 + i) * 16 + g4] = acc[i][0]; stage[(wid * 5 + i) * 16 + 8 + g4] = acc[i][2]; }
            }
            CLK(14);
            if (live) bar_cons();
            const int o = tid >> 1, k = tid & 1;
            const float* sp = stage + o * 5 + k * 3;
            float v0 = sp[0], v1 = sp[1], v2 = k ? 0.f : sp[2];
            if (live) st_pk16(&g_h3[o][cta][k], __float_as_uint(v0), __float_as_uint(v1), __float_as_uint(v2), tag);
        }
        if (live) TS(16);
        CLK(15);
        if (wid == 0 || !live) {
            const uint4* p = &g_h3[cta][0][0] + lane;
            uint4 v[6];
            uint32_t it = 0;
            if (live && cta < 96) spin(P_DLY);
            while (true) {
                bool ok = true;
                LoadN<6, 32>::run(v, p, live, 0, 0, 1);
#pragma unroll
                for (int j = 0; j < 6; j++) ok = ok && v[j].w == tag;
                if (__all_sync(0xffffffffu, ok) || !live) break;
                if (++it > SPIN_LIMIT) __trap();
            }
            CLK(16);
            float a0 = 0.f, a1 = 0.f, a2 = 0.f;
#pragma unroll
            for (int j = 0; j < 6; j++) { a0 += __uint_as_float(v[j].x); a1 += __uint_as_float(v[j].y); a2 += __uint_as_float(v[j].z); }
#pragma unroll
            for (int o = 2; o <= 16; o <<= 1) {
                a0 += __shfl_xor_sync(0xffffffffu, a0, o);
                a1 += __shfl_xor_sync(0xffffffffu, a1, o);
                a2 += __shfl_xor_sync(0xffffffffu, a2, o);
            }
            const float gx = own[8 + (lane & 7)], xx = own[24 + (lane & 7)];
            const float t0 = __shfl_sync(0xffffffffu, a0, lane >= 3), t1 = __shfl_sync(0xffffffffu, a1, lane >= 3);
            const float sum = (lane == 0 || lane == 3) ? t0 : (lane == 2 ? a2 : t1);
            const float y = xx + bfr(gx * bfr(sum));
            if (live && lane < 5) reinterpret_cast<uint16_t*>(out)[cta * 5 + lane] = (uint16_t)(__float_as_uint(bfr(y)) >> 16);
            if (live && cta == 0 && lane == 0) g_epoch = tag;
        }
        CLK(17);
        if (live) { TS(18); break; }
        live = true;
    }
    }
}

typedef CUresult (*EncodeFn)(CUtensorMap*, CUtensorMapDataType, cuuint32_t, void*, const cuuint64_t*, const cuuint64_t*,
                             const cuuint32_t*, const cuuint32_t*, CUtensorMapInterleave, CUtensorMapSwizzle,
                             CUtensorMapL2promotion, CUtensorMapFloatOOBfill);

void make_map(EncodeFn enc, CUtensorMap* tm, const void* ptr, uint64_t cols, uint64_t rows, uint32_t box_c, uint32_t box_r,
              CUtensorMapSwizzle sw, CUtensorMapL2promotion prom) {
    cuuint64_t dims[2] = {cols, rows};
    cuuint64_t strides[1] = {cols * 2};
    cuuint32_t box[2] = {box_c, box_r};
    cuuint32_t es[2] = {1, 1};
    enc(tm, CU_TENSOR_MAP_DATA_TYPE_BFLOAT16, 2, const_cast<void*>(ptr), dims, strides, box, es,
        CU_TENSOR_MAP_INTERLEAVE_NONE, sw, prom, CU_TENSOR_MAP_FLOAT_OOB_FILL_NONE);
}

}

extern "C" void kernel_launch(void* const* d_in, const int* in_sizes, int n_in, void* d_out, int out_size) {
    (void)in_sizes; (void)n_in; (void)out_size;
    static EncodeFn enc = nullptr;
    static int num_sms = 0;
    if (!enc) {
        void* fn = nullptr;
        cudaDriverEntryPointQueryResult qr;
        cudaGetDriverEntryPoint("cuTensorMapEncodeTiled", &fn, cudaEnableDefault, &qr);
        enc = (EncodeFn)fn;
        cudaDeviceGetAttribute(&num_sms, cudaDevAttrMultiProcessorCount, 0);
        cudaFuncSetAttribute(fused_decode_kernel, cudaFuncAttributeMaxDynamicSharedMemorySize, SM_TOTAL);
    }
    CUtensorMap tmK, tmV, tmMod, tmWq, tmWo, tmW1, tmW3, tmW2;
    const uint64_t kv_lines = (uint64_t)NH * SK * 3;
    make_map(enc, &tmK, d_in[1], 64, kv_lines, 64, 96, CU_TENSOR_MAP_SWIZZLE_128B, CU_TENSOR_MAP_L2_PROMOTION_L2_128B);
    make_map(enc, &tmV, d_in[2], 64, kv_lines, 64, 96, CU_TENSOR_MAP_SWIZZLE_128B, CU_TENSOR_MAP_L2_PROMOTION_L2_128B);
    make_map(enc, &tmWq, d_in[3], NH * DH, D, 48, 128, CU_TENSOR_MAP_SWIZZLE_NONE, CU_TENSOR_MAP_L2_PROMOTION_L2_128B);
    make_map(enc, &tmWo, d_in[4], D, NH * DH, 64, 48, CU_TENSOR_MAP_SWIZZLE_128B, CU_TENSOR_MAP_L2_PROMOTION_L2_128B);
    make_map(enc, &tmW1, d_in[6], FF, D, 16, 160, CU_TENSOR_MAP_SWIZZLE_32B, CU_TENSOR_MAP_L2_PROMOTION_L2_128B);
    make_map(enc, &tmW3, d_in[7], FF, D, 16, 160, CU_TENSOR_MAP_SWIZZLE_32B, CU_TENSOR_MAP_L2_PROMOTION_L2_128B);
    make_map(enc, &tmW2, d_in[8], D, FF, 64, 16, CU_TENSOR_MAP_SWIZZLE_128B, CU_TENSOR_MAP_L2_PROMOTION_L2_128B);
    make_map(enc, &tmMod, d_in[10], 6 * D, D, 32, 160, CU_TENSOR_MAP_SWIZZLE_64B, CU_TENSOR_MAP_L2_PROMOTION_L2_128B);
    int grid = num_sms < MAXG ? num_sms : MAXG;
    fused_decode_kernel<<<grid, NTHREADS, SM_TOTAL, cudaStreamPerThread>>>(
        tmK, tmV, tmMod, tmWq, tmWo, tmW1, tmW3, tmW2, (const __nv_bfloat16*)d_in[0], (const __nv_bfloat16*)d_in[9],
        (__nv_bfloat16*)d_out);
}
```

```cpp
#include <cuda_runtime.h>
#include <cuda_bf16.h>
#include <cuda.h>
#include <stdint.h>

namespace {

constexpr int D = 640, NH = 32, SK = 8192, DH = 192, FF = 1536;
constexpr int NG = 4;
constexpr int GH = 7;
constexpr int NGLOB = NH - NG * GH;
constexpr int NQH = GH + NGLOB;
constexpr int TILE = 32;
constexpr int TPH = SK / TILE;
constexpr int GT = GH * TPH;
constexpr int PT = NGLOB * TPH;
constexpr int CHUNK = TILE * DH * 2;
#define P_NSLOT 8
#define P_WIN 3
#define P_URG 0
#define P_HOLD 3
#define P_TWIN P_WIN
#define P_DLY 450
constexpr int NSLOT = P_NSLOT;
constexpr int WIN = P_WIN;
#define P_NBUF 3
constexpr int NBUF = P_NBUF;
constexpr int MAXG = 132;
constexpr int NTHREADS = 288;
constexpr float NEG_BIG = -3.402823466e38f;

constexpr int SM_WMOD = 0;
constexpr int SM_WQ = 40960;
constexpr int SM_WO = 0;
constexpr int SM_W1 = 61440;
constexpr int SM_W3 = 81920;
constexpr int SM_RING = 102400;
constexpr int SM_MISC = SM_RING + NSLOT * CHUNK;
constexpr int SM_BARS = SM_MISC;
constexpr int SM_META = SM_BARS + 512;
constexpr int SM_Q = SM_META + 256;
constexpr int SM_SC = SM_Q + NQH * DH * 2;
constexpr int SM_H = SM_SC + 1280;
constexpr int SM_X = SM_H + 1280;
constexpr int SM_CB = SM_X + 1280;
constexpr int SM_SB = SM_CB + 1280;
constexpr int SM_OWN = SM_SB + 1280;
constexpr int SM_RED = SM_OWN + 128;
constexpr int SM_MERGE = SM_RED + 2048;
constexpr int SM_STAGE = SM_MERGE + NBUF * 3200;
constexpr int SM_X2 = SM_STAGE + 2560;
constexpr int SM_FIN = SM_X2 + 2560;
constexpr int SM_TOTAL = SM_FIN + 512;
static_assert(SM_TOTAL <= 232448, "shared memory budget");

constexpr int B_FULL = 0;
constexpr int B_EMPTY = 8;
constexpr int B_MOD = 16;
constexpr int B_WQ = 20;
constexpr int B_WO = 25;
constexpr int B_W1 = 30;
constexpr int B_W3 = 32;
constexpr int B_W2 = 34;
constexpr int B_PRO = 36, B_DUMMY = 37;
constexpr int B_FLF = 40, B_FLE = 44;
constexpr int B_LAST = 48;
static_assert(NSLOT <= 8 && NSLOT >= 6 && WIN <= 4 && WIN <= NSLOT - 3, "barrier map / end markers vs window");
constexpr uint32_t META_END = 0x10000u;

__device__ unsigned g_epoch;
__device__ unsigned g_ctr[2][(NG + 1) * 32];
__device__ __align__(128) unsigned long long g_mod[1920];
__device__ __align__(128) unsigned long long g_q[3072];
__device__ __align__(128) uint4 g_hdr[NH][MAXG];
__device__ __align__(128) uint4 g_dat[NH][MAXG][64];
__device__ __align__(128) uint4 g_h1[128][128][2];
__device__ __align__(128) uint4 g_x2[128][2];
__device__ __align__(128) uint4 g_h3[128][96][2];

#define TS(k) do {} while (0)
#define DBG(k) do {} while (0)
#define EARLY(k) do {} while (0)
#define CLK(k) do {} while (0)

__device__ __forceinline__ uint32_t smem_u32(const void* p) { return (uint32_t)__cvta_generic_to_shared(p); }
__device__ __forceinline__ void mbar_init(uint32_t bar, uint32_t cnt) {
    asm volatile("mbarrier.init.shared::cta.b64 [%0], %1;" ::"r"(bar), "r"(cnt) : "memory");
}
__device__ __forceinline__ void mbar_expect_tx(uint32_t bar, uint32_t bytes) {
    asm volatile("mbarrier.arrive.expect_tx.shared::cta.b64 _, [%0], %1;" ::"r"(bar), "r"(bytes) : "memory");
}
__device__ __forceinline__ void mbar_arrive(uint32_t bar) {
    asm volatile("mbarrier.arrive.shared::cta.b64 _, [%0];" ::"r"(bar) : "memory");
}
constexpr uint32_t SPIN_LIMIT = 1u << 22;
__device__ __forceinline__ void mbar_wait(uint32_t bar, uint32_t parity) {
    asm volatile(
        "{\n.reg .pred p;\n.reg .u32 c;\nmov.u32 c, 0;\n"
        "LW:\nmbarrier.try_wait.parity.shared::cta.b64 p, [%0], %1;\n@p bra LD;\n"
        "add.u32 c, c, 1;\nsetp.lt.u32 p, c, 0x400000;\n@p bra LW;\ntrap;\nLD:\n}" ::"r"(bar), "r"(parity)
        : "memory");
}
__device__ __forceinline__ uint32_t mbar_try(uint32_t bar, uint32_t parity) {
    uint32_t ok;
    asm volatile("{\n.reg .pred p;\nmbarrier.try_wait.parity.shared::cta.b64 p, [%1], %2;\nselp.u32 %0, 1, 0, p;\n}"
                 : "=r"(ok) : "r"(bar), "r"(parity) : "memory");
    return ok;
}
__device__ __forceinline__ void mbar_wait3(uint32_t b0, uint32_t b1, uint32_t b2) {
    asm volatile(
        "{\n.reg .pred p, q, r;\n.reg .u32 c;\nmov.u32 c, 0;\n"
        "LW:\nmbarrier.try_wait.parity.shared::cta.b64 p, [%0], 0;\n"
        "mbarrier.try_wait.parity.shared::cta.b64 q, [%1], 0;\n"
        "mbarrier.try_wait.parity.shared::cta.b64 r, [%2], 0;\n"
        "and.pred p, p, q;\nand.pred p, p, r;\n@p bra LD;\n"
        "add.u32 c, c, 1;\nsetp.lt.u32 p, c, 0x400000;\n@p bra LW;\ntrap;\nLD:\n}" ::"r"(b0), "r"(b1), "r"(b2)
        : "memory");
}
__device__ __forceinline__ void tma2d(uint32_t dst, const CUtensorMap* tm, int c0, int c1, uint32_t bar) {
    asm volatile(
        "cp.async.bulk.tensor.2d.shared::cluster.global.mbarrier::complete_tx::bytes [%0], [%1, {%3, %4}], [%2];" ::"r"(dst),
        "l"(tm), "r"(bar), "r"(c0), "r"(c1)
        : "memory");
}
__device__ __forceinline__ void tma2d_hint(uint32_t dst, const CUtensorMap* tm, int c0, int c1, uint32_t bar, uint64_t pol) {
    asm volatile(
        "cp.async.bulk.tensor.2d.shared::cluster.global.mbarrier::complete_tx::bytes.L2::cache_hint [%0], [%1, {%3, %4}], [%2], %5;" ::"r"(dst),
        "l"(tm), "r"(bar), "r"(c0), "r"(c1), "l"(pol)
        : "memory");
}
__device__ __forceinline__ void prefetch_tm(const CUtensorMap* tm) {
    asm volatile("prefetch.tensormap [%0];" ::"l"(tm) : "memory");
}
__device__ __forceinline__ void ldsm4(uint32_t (&r)[4], uint32_t addr) {
    asm volatile("ldmatrix.sync.aligned.m8n8.x4.shared.b16 {%0,%1,%2,%3}, [%4];"
                 : "=r"(r[0]), "=r"(r[1]), "=r"(r[2]), "=r"(r[3])
                 : "r"(addr));
}
__device__ __forceinline__ void ldsm4t(uint32_t (&r)[4], uint32_t addr) {
    asm volatile("ldmatrix.sync.aligned.m8n8.x4.trans.shared.b16 {%0,%1,%2,%3}, [%4];"
                 : "=r"(r[0]), "=r"(r[1]), "=r"(r[2]), "=r"(r[3])
                 : "r"(addr));
}
__device__ __forceinline__ void mma16816(float (&d)[4], const uint32_t (&a)[4], uint32_t b0, uint32_t b1) {
    asm volatile(
        "mma.sync.aligned.m16n8k16.row.col.f32.bf16.bf16.f32 {%0,%1,%2,%3}, {%4,%5,%6,%7}, {%8,%9}, {%0,%1,%2,%3};"
        : "+f"(d[0]), "+f"(d[1]), "+f"(d[2]), "+f"(d[3])
        : "r"(a[0]), "r"(a[1]), "r"(a[2]), "r"(a[3]), "r"(b0), "r"(b1));
}
__device__ __forceinline__ void bar_cons() { asm volatile("bar.sync 1, 256;" ::: "memory"); }
__device__ __forceinline__ void spin(int cycles) {
    long long t0 = clock64();
    while (clock64() - t0 < cycles) {}
}

__device__ __forceinline__ float bfr(float x) {
    uint32_t r;
    asm("cvt.rn.bf16x2.f32 %0, %1, %2;" : "=r"(r) : "f"(x), "f"(0.0f));
    return __uint_as_float(r);
}
__device__ __forceinline__ uint32_t pack_bf(float lo, float hi) {
    __nv_bfloat162 t = __floats2bfloat162_rn(lo, hi);
    return *reinterpret_cast<uint32_t*>(&t);
}
__device__ __forceinline__ float bf_lo(uint32_t v) { return __uint_as_float(v << 16); }
__device__ __forceinline__ float bf_hi(uint32_t v) { return __uint_as_float(v & 0xffff0000u); }

__device__ __forceinline__ void st_pk8(unsigned long long* p, uint32_t v, uint32_t tag) {
    unsigned long long w = ((unsigned long long)tag << 32) | v;
    asm volatile("st.relaxed.gpu.global.b64 [%0], %1;" ::"l"(p), "l"(w) : "memory");
}
__device__ __forceinline__ unsigned long long ld_raw8(const unsigned long long* p) {
    unsigned long long w;
    asm volatile("ld.relaxed.gpu.global.b64 %0, [%1];" : "=l"(w) : "l"(p) : "memory");
    return w;
}
template <int N>
__device__ __forceinline__ void poll8(const unsigned long long* base, const int (&off)[N], uint32_t (&val)[N], uint32_t tag) {
    uint32_t it = 0;
    while (true) {
        unsigned long long w[N];
#pragma unroll
        for (int i = 0; i < N; i++) w[i] = ld_raw8(base + off[i]);
        bool ok = true;
#pragma unroll
        for (int i = 0; i < N; i++) { ok = ok && ((uint32_t)(w[i] >> 32) == tag); val[i] = (uint32_t)w[i]; }
        if (__all_sync(0xffffffffu, ok)) break;
        if (++it > SPIN_LIMIT) __trap();
    }
}
__device__ __forceinline__ void st_pk16(uint4* p, uint32_t a, uint32_t b, uint32_t c, uint32_t tag) {
    asm volatile(
        "{\n.reg .b128 t;\n.reg .b64 lo, hi;\nmov.b64 lo, {%1, %2};\nmov.b64 hi, {%3, %4};\nmov.b128 t, {lo, hi};\n"
        "st.relaxed.gpu.global.b128 [%0], t;\n}" ::"l"(p), "r"(a), "r"(b), "r"(c), "r"(tag)
        : "memory");
}
template <int OFF = 0>
__device__ __forceinline__ uint4 ld_raw16p(const uint4* p, uint32_t on) {
    uint4 v;
    asm volatile(
        "{\n.reg .b128 t;\n.reg .b64 lo, hi;\n.reg .pred q;\nsetp.ne.u32 q, %5, 0;\n"
        "mov.b64 lo, 0;\nmov.b128 t, {lo, lo};\n"
        "@q ld.relaxed.gpu.global.b128 t, [%4 + %6];\nmov.b128 {lo, hi}, t;\n"
        "mov.b64 {%0, %1}, lo;\nmov.b64 {%2, %3}, hi;\n}"
        : "=r"(v.x), "=r"(v.y), "=r"(v.z), "=r"(v.w)
        : "l"(p), "r"(on), "n"(OFF * 16)
        : "memory");
    return v;
}
template <int OFF>
__device__ __forceinline__ void ld_fresh16(uint4& v, const uint4* p, uint32_t tag, uint32_t on) {
    asm volatile(
        "{\n.reg .b128 t;\n.reg .b64 lo, hi;\n.reg .pred q;\nsetp.ne.u32 q, %3, %5;\nsetp.ne.and.u32 q, %6, 0, q;\n"
        "mov.b64 lo, {%0, %1};\nmov.b64 hi, {%2, %3};\nmov.b128 t, {lo, hi};\n"
        "@q ld.relaxed.gpu.global.b128 t, [%4 + %7];\nmov.b128 {lo, hi}, t;\n"
        "mov.b64 {%0, %1}, lo;\nmov.b64 {%2, %3}, hi;\n}"
        : "+r"(v.x), "+r"(v.y), "+r"(v.z), "+r"(v.w)
        : "l"(p), "r"(tag), "r"(on), "n"(OFF * 16)
        : "memory");
}
template <int N, int STRIDE, int I = 0>
struct FreshN {
    static __device__ __forceinline__ void run(uint4* v, const uint4* p, uint32_t tag, bool live, int base, int step, int lim) {
        ld_fresh16<I * STRIDE>(v[I], p, tag, live && base + step * I < lim);
        FreshN<N, STRIDE, I + 1>::run(v, p, tag, live, base, step, lim);
    }
};
template <int N, int STRIDE>
struct FreshN<N, STRIDE, N> {
    static __device__ __forceinline__ void run(uint4*, const uint4*, uint32_t, bool, int, int, int) {}
};
template <int N, int STRIDE, int I = 0>
struct LoadN {
    static __device__ __forceinline__ void run(uint4* v, const uint4* p, bool live, int base, int step, int lim) {
        v[I] = ld_raw16p<I * STRIDE>(p, live && base + step * I < lim);
        LoadN<N, STRIDE, I + 1>::run(v, p, live, base, step, lim);
    }
};
template <int N, int STRIDE>
struct LoadN<N, STRIDE, N> {
    static __device__ __forceinline__ void run(uint4*, const uint4*, bool, int, int, int) {}
};
__device__ __forceinline__ uint4 poll16(const uint4* p, uint32_t tag, bool live) {
    uint32_t it = 0;
    uint4 v;
    while (true) {
        v = ld_raw16p(p, live);
        if (__all_sync(0xffffffffu, v.w == tag) || !live) break;
        if (++it > SPIN_LIMIT) __trap();
    }
    return v;
}
__device__ __forceinline__ void st_zero16(void* p) {
    asm volatile("st.relaxed.gpu.global.v4.u32 [%0], {%1, %1, %1, %1};" ::"l"(p), "r"(0u) : "memory");
}
__device__ __forceinline__ float ex2(float x) {
    float y;
    asm("ex2.approx.ftz.f32 %0, %1;" : "=f"(y) : "f"(x));
    return y;
}
__device__ __forceinline__ float fsqrt(float x) {
    float y;
    asm("sqrt.approx.f32 %0, %1;" : "=f"(y) : "f"(x));
    return y;
}
constexpr float LOG2E = 1.4426950408889634f;
__device__ __forceinline__ float silu(float a) { return __fdividef(a, 1.0f + ex2(-a * LOG2E)); }
__device__ __forceinline__ float warp_sum(float v) {
#pragma unroll
    for (int o = 16; o > 0; o >>= 1) v += __shfl_xor_sync(0xffffffffu, v, o);
    return v;
}

__device__ __forceinline__ void ln_stats(const float (&v)[20], float& mean_b, float& den_b) {
    float s = 0.f;
#pragma unroll
    for (int i = 0; i < 20; i++) s += v[i];
    s = warp_sum(s);
    float mean = s * (1.0f / 640.0f);
    float q = 0.f;
#pragma unroll
    for (int i = 0; i < 20; i++) { float d = v[i] - mean; q += d * d; }
    q = warp_sum(q);
    float var_b = bfr(q * (1.0f / 640.0f));
    mean_b = bfr(mean);
    den_b = bfr(fsqrt(bfr(var_b + 1e-5f)));
}

struct Window {
    uint32_t bar[WIN];
    uint32_t par[WIN];
    __device__ __forceinline__ void init(uint32_t dummy) {
#pragma unroll
        for (int i = 0; i < WIN; i++) { bar[i] = dummy; par[i] = 1; }
    }
    __device__ __forceinline__ void push_tail(uint32_t b, uint32_t p) {
#pragma unroll
        for (int i = 1; i <= WIN - P_TWIN; i++) mbar_wait(bar[i], par[i]);
        push(b, p);
    }
    __device__ __forceinline__ void push(uint32_t b, uint32_t p, bool wait = true) {
        if (wait) mbar_wait(bar[0], par[0]);
#pragma unroll
        for (int i = 0; i + 1 < WIN; i++) { bar[i] = bar[i + 1]; par[i] = par[i + 1]; }
        bar[WIN - 1] = b; par[WIN - 1] = p;
    }
};

__global__ void __launch_bounds__(NTHREADS, 1)
fused_decode_kernel(const __grid_constant__ CUtensorMap tmK, const __grid_constant__ CUtensorMap tmV,
                    const __grid_constant__ CUtensorMap tmMod, const __grid_constant__ CUtensorMap tmWq,
                    const __grid_constant__ CUtensorMap tmWo, const __grid_constant__ CUtensorMap tmW1,
                    const __grid_constant__ CUtensorMap tmW3, const __grid_constant__ CUtensorMap tmW2,
                    const __nv_bfloat16* __restrict__ x_in, const __nv_bfloat16* __restrict__ c_in,
                    __nv_bfloat16* __restrict__ out) {
    extern __shared__ __align__(1024) uint8_t smem[];
    const uint32_t sb = smem_u32(smem);
    const int tid = threadIdx.x, wid = tid >> 5, lane = tid & 31;
    const int cta = blockIdx.x, G = gridDim.x;
    const int grp = cta % NG, rank = cta / NG;
    const uint32_t bars = sb + SM_BARS;
    auto BAR = [&](int i) { return bars + 8u * i; };
    volatile uint32_t* meta = reinterpret_cast<volatile uint32_t*>(smem + SM_META);

    {
        const bool mf = cta < 40;
        const int b0 = mf ? B_MOD : B_WQ;
        if (tid == 256) {
#pragma unroll 1
            for (int i = 0; i < 4; i++) mbar_init(BAR(b0 + i), 1);
            asm volatile("fence.mbarrier_init.release.cluster;" ::: "memory");
            asm volatile("fence.proxy.async.shared::cta;" ::: "memory");
            if (cta < 128) {
                const CUtensorMap* tm = mf ? &tmMod : &tmWq;
#pragma unroll 1
                for (int i = 0; i < 4; i++) {
                    const uint32_t bar = BAR(b0 + i);
                    mbar_expect_tx(bar, mf ? 10240 : 12288);
                    tma2d(sb + (mf ? SM_WMOD + i * 10240 : SM_WQ + i * 12288), tm, cta * (mf ? 32 : 48), i * (mf ? 160 : 128), bar);
                }
            }
        } else if (wid < 8 && lane == 0) {
#pragma unroll 1
            for (int i = wid; i < B_LAST; i += 8) {
                if (i >= b0 && i < b0 + 4) continue;
                mbar_init(BAR(i), (i >= B_EMPTY && i < B_MOD) ? 2 : ((i >= B_FLF && i < B_FLE) ? 4 : 1));
            }
            asm volatile("fence.mbarrier_init.release.cluster;" ::: "memory");
            asm volatile("fence.proxy.async.shared::cta;" ::: "memory");
        }
    }
    __syncwarp();
    __syncthreads();
    if (sb & 1023u) __trap();

    if (wid == 8) {
        if (tid == 256) {
            Window win;
            unsigned epoch;
            asm volatile("ld.relaxed.gpu.global.u32 %0, [%1];" : "=r"(epoch) : "l"(&g_epoch) : "memory");
            prefetch_tm(&tmWq); prefetch_tm(&tmMod); prefetch_tm(&tmK); prefetch_tm(&tmV);
            const int nmod = cta < 120 ? 4 : 0, nwq = cta < 128 ? 5 : 0;
            win.init(BAR(B_DUMMY));
            auto pro_issue = [&](int i, bool issue) {
                const bool is_mod = cta < 40 ? i < nmod : i >= nwq;
                const int j = cta < 40 ? (is_mod ? i : i - nmod) : (is_mod ? i - nwq : i);
                const uint32_t bar = BAR((is_mod ? B_MOD : B_WQ) + j);
                win.push(bar, 0, issue);
                if (issue) {
                    mbar_expect_tx(bar, is_mod ? 10240 : 12288);
                    if (is_mod) tma2d(sb + SM_WMOD + j * 10240, &tmMod, cta * 32, j * 160, bar);
                    else tma2d(sb + SM_WQ + j * 12288, &tmWq, cta * 48, j * 128, bar);
                }
            };
            prefetch_tm(&tmWo); prefetch_tm(&tmW1); prefetch_tm(&tmW3); prefetch_tm(&tmW2);
            unsigned* ctr = &g_ctr[epoch & 1][grp * 32];
            unsigned* gctr = &g_ctr[epoch & 1][NG * 32];
            if (cta == 0) {
                for (int g = 0; g <= NG; g++) g_ctr[(epoch + 1) & 1][g * 32] = 0;
            }
            unsigned pend = atomicAdd(ctr, 1);
#pragma unroll 1
            for (int i = 0; i < nmod + nwq; i++) pro_issue(i, i >= 4);
            uint64_t pol;
            asm volatile("createpolicy.fractional.L2::evict_first.b64 %0, 1.0;" : "=l"(pol));
            int s = 0; uint32_t par = 0;
            int ntiles = 0, run = -1, last_head = -1;
            bool glob = false;
#pragma unroll 1
            while (true) {
                unsigned t = pend;
                DBG(8);
                if (!glob && t >= (unsigned)GT) { glob = true; t = atomicAdd(gctr, 1); }
                if (glob && t >= (unsigned)PT) break;
                pend = atomicAdd(glob ? gctr : ctr, 1);
                ntiles++;
                const int hl = t / TPH, tile = t % TPH;
                const int head = glob ? NG * GH + hl : grp * GH + hl;
                const int qidx = glob ? GH + hl : hl;
                if (head != last_head) { last_head = head; run++; meta[16 + run] = head; }
                const int line0 = (head * SK + tile * TILE) * 3;
                const bool urgent = glob && t >= (unsigned)(PT - P_URG);
#pragma unroll 1
                for (int kv = 0; kv < 2; kv++) {
                    win.push(BAR(B_FULL + s), par, !urgent);
                    mbar_wait(BAR(B_EMPTY + s), par ^ 1);
                    meta[s] = run | (qidx << 8);
                    mbar_expect_tx(BAR(B_FULL + s), CHUNK);
                    tma2d_hint(sb + SM_RING + s * CHUNK, kv ? &tmV : &tmK, 0, line0, BAR(B_FULL + s), pol);
                    DBG(6 + kv);
                    if (++s == NSLOT) { s = 0; par ^= 1; }
                }
            }
            TS(5);
            meta[16 + run + 1] = 0xFFu;
#pragma unroll 1
            for (int e = 0; e < 2; e++) {
                mbar_wait(BAR(B_EMPTY + s), par ^ 1);
                meta[s] = (run + 1) | META_END;
                mbar_arrive(BAR(B_FULL + s));
                if (++s == NSLOT) { s = 0; par ^= 1; }
                if (++s == NSLOT) { s = 0; par ^= 1; }
            }
#pragma unroll
            for (int i = 0; i < WIN - P_HOLD; i++) mbar_wait(win.bar[i], win.par[i]);
            TS(12);
            if (cta < 128) {
                mbar_wait(BAR(B_PRO), 0);
#pragma unroll 1
                for (int i = 0; i < 5; i++) {
                    win.push_tail(BAR(B_WO + i), 0);
                    mbar_expect_tx(BAR(B_WO + i), 12288);
                    tma2d(sb + SM_WO + (2 * i) * 6144, &tmWo, (2 * i) * 64, cta * 48, BAR(B_WO + i));
                    tma2d(sb + SM_WO + (2 * i + 1) * 6144, &tmWo, (2 * i + 1) * 64, cta * 48, BAR(B_WO + i));
                }
                if (cta < 96) {
#pragma unroll 1
                    for (int i = 0; i < 4; i++) {
                        const int m = i & 1, hf = i >> 1;
                        const uint32_t bar = BAR((m ? B_W3 : B_W1) + hf);
                        const uint32_t dst = sb + (m ? SM_W3 : SM_W1) + hf * 10240;
                        const CUtensorMap* tm = m ? &tmW3 : &tmW1;
                        win.push_tail(bar, 0);
                        mbar_expect_tx(bar, 10240);
                        tma2d(dst, tm, cta * 16, hf * 320, bar);
                        tma2d(dst + 5120, tm, cta * 16, hf * 320 + 160, bar);
                    }
#pragma unroll 1
                    for (int i = 0; i < 2; i++) {
                        win.push_tail(BAR(B_W2 + i), 0);
                        mbar_wait(BAR(B_EMPTY + s), par ^ 1);
                        meta[10 + i] = s;
                        mbar_expect_tx(BAR(B_W2 + i), 10240);
#pragma unroll 1
                        for (int b = 0; b < 5; b++)
                            tma2d(sb + SM_RING + s * CHUNK + b * 2048, &tmW2, (5 * i + b) * 64, cta * 16, BAR(B_W2 + i));
                        if (++s == NSLOT) { s = 0; par ^= 1; }
                    }
                }
            }
            TS(6);
        }
    } else {
    const int g4 = lane >> 2, j4 = lane & 3, mi = lane >> 3, l8 = lane & 7;
    uint32_t* sc32 = reinterpret_cast<uint32_t*>(smem + SM_SC);
    uint32_t* h32 = reinterpret_cast<uint32_t*>(smem + SM_H);
    uint32_t* x32 = reinterpret_cast<uint32_t*>(smem + SM_X);
    uint32_t* q32 = reinterpret_cast<uint32_t*>(smem + SM_Q);
    float* red = reinterpret_cast<float*>(smem + SM_RED);
    float* stage = reinterpret_cast<float*>(smem + SM_STAGE);
    float* own = reinterpret_cast<float*>(smem + SM_OWN);

    uint32_t tag;
    bool live = true;
    {
    {
        const uint32_t* cg = reinterpret_cast<const uint32_t*>(c_in);
        const uint32_t* xg = reinterpret_cast<const uint32_t*>(x_in);
        uint32_t c0 = cg[tid], x0 = xg[tid], c1 = 0, x1 = 0;
        if (tid < 64) { c1 = cg[256 + tid]; x1 = xg[256 + tid]; }
        unsigned epoch = 0;
        if (tid == 0) asm volatile("ld.relaxed.gpu.global.u32 %0, [%1];" : "=r"(epoch) : "l"(&g_epoch) : "memory");
        sc32[tid] = pack_bf(silu(bf_lo(c0)), silu(bf_hi(c0))); x32[tid] = x0;
        if (tid < 64) { sc32[256 + tid] = pack_bf(silu(bf_lo(c1)), silu(bf_hi(c1))); x32[256 + tid] = x1; }
        if (tid == 0) meta[8] = epoch + 1;
    }
    bar_cons();
    tag = meta[8];
    if (wid == 0) EARLY(3);
    {
        if (cta < 120 && tid >= 128 && tid < 136) st_zero16(reinterpret_cast<uint4*>(&g_mod[cta * 16]) + (tid - 128));
        if (cta < 128 && tid >= 32 && tid < 44) st_zero16(reinterpret_cast<uint4*>(&g_q[cta * 24]) + (tid - 32));
        if (cta < 128) {
            if (tid >= 64 && tid < 66) st_zero16(&g_x2[cta][tid - 64]);
            st_zero16(&g_h1[tid >> 1][cta][tid & 1]);
            if (cta < 96) st_zero16(&g_h3[tid >> 1][cta][tid & 1]);
        }
#pragma unroll 1
        for (int f = tid >> 6; f < NQH; f += 4) {
            const int head = f < GH ? grp * GH + f : NG * GH + (f - GH);
            const int idx = f < GH ? rank : cta;
            st_zero16(&g_dat[head][idx][tid & 63]);
            if ((tid & 63) == 0) st_zero16(&g_hdr[head][idx]);
        }
    }

    float mean_x = 0.f, rden_x = 1.f;
    if (cta < 128) {
        float xv[20];
#pragma unroll
        for (int i = 0; i < 10; i++) { uint32_t v = x32[lane + 32 * i]; xv[2 * i] = bf_lo(v); xv[2 * i + 1] = bf_hi(v); }
        float den;
        ln_stats(xv, mean_x, den);
        rden_x = __fdividef(1.0f, den);
    }

#pragma unroll 1
    for (int step = 0; step < 2; step++) {
    if (wid >= 4 && (step == 0 ? cta < 40 : (cta >= 40 && cta < 120))) {
        const int w4 = wid - 4;
        float acc[2][4] = {};
        const uint32_t base = sb + SM_WMOD + w4 * 10240;
        mbar_wait(BAR(B_MOD + w4), 0);
        EARLY(4 + w4);
#pragma unroll
        for (int hf = 0; hf < 2; hf++) {
            uint32_t a[5][2][4], bb[5][2];
#pragma unroll
            for (int ks = 0; ks < 5; ks++) {
                const int r0 = w4 * 160 + hf * 80 + ks * 16;
                bb[ks][0] = sc32[(r0 >> 1) + j4]; bb[ks][1] = sc32[(r0 >> 1) + 4 + j4];
                const int r = hf * 80 + ks * 16 + l8 + 8 * (mi >> 1);
#pragma unroll
                for (int mt = 0; mt < 2; mt++) ldsm4t(a[ks][mt], base + r * 64 + (((2 * mt + (mi & 1)) ^ ((r >> 1) & 3)) << 4));
            }
#pragma unroll
            for (int ks = 0; ks < 5; ks++) { mma16816(acc[0], a[ks][0], bb[ks][0], bb[ks][1]); mma16816(acc[1], a[ks][1], bb[ks][0], bb[ks][1]); }
        }
        float* red2 = reinterpret_cast<float*>(smem + SM_FIN);
        if (j4 == 0) {
#pragma unroll
            for (int mt = 0; mt < 2; mt++) { red2[w4 * 32 + mt * 16 + g4] = acc[mt][0]; red2[w4 * 32 + mt * 16 + 8 + g4] = acc[mt][2]; }
        }
        asm volatile("bar.sync 3, 128;" ::: "memory");
        if (wid == 4) EARLY(8);
        if (wid == 4) {
            float v = (red2[lane] + red2[32 + lane]) + (red2[64 + lane] + red2[96 + lane]);
            float o = __shfl_down_sync(0xffffffffu, v, 1);
            if (!(lane & 1)) st_pk8(&g_mod[cta * 16 + (lane >> 1)], pack_bf(v, o), tag);
            if (step == 1 && lane == 0) mbar_arrive(BAR(B_PRO));
        }
        TS(1);
    }
    if (step == 1) break;
    if (cta < 128) {
        {
            const int off[4] = {tid, 320 + tid, tid < 64 ? 256 + tid : tid, tid < 64 ? 576 + tid : 320 + tid};
            uint32_t val[4];
            poll8<4>(g_mod, off, val, tag);
#pragma unroll
            for (int rep = 0; rep < 2; rep++) {
                int p = tid + rep * 256;
                if (p < 320) {
                    uint32_t sa = val[2 * rep], ca = val[2 * rep + 1];
                    uint32_t xx = x32[p];
                    float n0 = bfr(bfr(bf_lo(xx) - mean_x) * rden_x), n1 = bfr(bfr(bf_hi(xx) - mean_x) * rden_x);
                    float h0 = bfr(n0 * bfr(1.0f + bf_lo(ca))) + bf_lo(sa);
                    float h1 = bfr(n1 * bfr(1.0f + bf_hi(ca))) + bf_hi(sa);
                    h32[p] = pack_bf(h0, h1);
                }
            }
        }
        bar_cons();
        TS(2);
        float acc[3][4] = {};
        uint32_t a[5][3][4], bb[5][2];
#pragma unroll
        for (int ks = 0; ks < 5; ks++) {
            const int r0 = wid * 80 + ks * 16;
            bb[ks][0] = h32[(r0 >> 1) + j4]; bb[ks][1] = h32[(r0 >> 1) + 4 + j4];
        }
        mbar_wait(BAR(B_WQ + ((wid * 80) >> 7)), 0);
        mbar_wait(BAR(B_WQ + ((wid * 80 + 79) >> 7)), 0);
        if (wid == 0) EARLY(9);
        if (wid == 7) EARLY(10);
#pragma unroll
        for (int ks = 0; ks < 5; ks++) {
            const int r = wid * 80 + ks * 16 + l8 + 8 * (mi >> 1);
#pragma unroll
            for (int mt = 0; mt < 3; mt++) ldsm4t(a[ks][mt], sb + SM_WQ + r * 96 + ((2 * mt + (mi & 1)) << 4));
        }
#pragma unroll
        for (int ks = 0; ks < 5; ks++) {
#pragma unroll
            for (int mt = 0; mt < 3; mt++) mma16816(acc[mt], a[ks][mt], bb[ks][0], bb[ks][1]);
        }
        if (j4 == 0) {
#pragma unroll
            for (int mt = 0; mt < 3; mt++) { red[wid * 64 + mt * 16 + g4] = acc[mt][0]; red[wid * 64 + mt * 16 + 8 + g4] = acc[mt][2]; }
        }
        bar_cons();
        if (tid < 64) {
            float v = 0.f;
            if (tid < 48) {
#pragma unroll
                for (int w = 0; w < 8; w++) v += red[w * 64 + tid];
            }
            float o = __shfl_down_sync(0xffffffffu, v, 1);
            if (tid < 48 && !(tid & 1)) st_pk8(&g_q[cta * 24 + (tid >> 1)], pack_bf(v, o), tag);
        }
        TS(3);
    }
    {
        int off[5];
#pragma unroll
        for (int j = 0; j < 5; j++) {
            int p = tid + 256 * j;
            if (p >= NQH * 96) p = tid;
            off[j] = p < GH * 96 ? grp * GH * 96 + p : NG * GH * 96 + (p - GH * 96);
        }
        uint32_t val[5];
        poll8<5>(g_q, off, val, tag);
#pragma unroll
        for (int j = 0; j < 5; j++)
            if (tid + 256 * j < NQH * 96) q32[tid + 256 * j] = val[j];
    }
    bar_cons();
    if (tid == 0 && !(cta >= 40 && cta < 120)) mbar_arrive(BAR(B_PRO));
    TS(4);
    }

    if (wid < 4) {
        const int pair = wid >> 1, half = wid & 1;
        uint32_t offK[3], offV[3];
        {
            const int rowK = half * 16 + l8 + 8 * (mi & 1), hiK = mi >> 1;
            const int rowV = half * 16 + l8 + 8 * (mi >> 1), hiV = mi & 1;
#pragma unroll
            for (int t = 0; t < 3; t++) {
                offK[t] = (rowK * 3 + t) * 128 + ((hiK ^ ((rowK * 3 + t) & 7)) << 4);
                offV[t] = (rowV * 3 + t) * 128 + ((hiV ^ ((rowV * 3 + t) & 7)) << 4);
                asm volatile("" : "+r"(offK[t]), "+r"(offV[t]));
            }
        }
        float acc[12][4];
#pragma unroll
        for (int i = 0; i < 12; i++) { acc[i][0] = acc[i][1] = acc[i][2] = acc[i][3] = 0.f; }
        float m_run = NEG_BIG, l_run = 0.f;
        uint32_t qf[12][2];
#pragma unroll
        for (int i = 0; i < 12; i++) { qf[i][0] = qf[i][1] = 0; }
        int cur = -1, flushed = 0, cnt = 0;
        int s = 2 * pair; uint32_t par = 0;
        int fb = 0; uint32_t fpar = 1;
        uint32_t ready = 0;
#pragma unroll 1
        while (true) {
            if (!ready) mbar_wait(BAR(B_FULL + s), par);
            const uint32_t mt_ = meta[s];
            const int run = mt_ & 0xff;
            if (mt_ & META_END) CLK(20);
            if ((mt_ & META_END) && half == 0) DBG(4 + pair);
            if (run != cur) {
#pragma unroll 1
                while (flushed < run) {
                    const uint32_t fle = mbar_try(BAR(B_FLE + fb), fpar);
                    float* mb = reinterpret_cast<float*>(smem + SM_MERGE) + (fb * 4 + wid) * 200;
                    if (flushed != cur) {
#pragma unroll
                        for (int i = 0; i < 12; i++) { acc[i][0] = acc[i][2] = 0.f; }
                        m_run = NEG_BIG; l_run = 0.f; cnt = 0;
                    }
                    float l = l_run;
                    l += __shfl_xor_sync(0xffffffffu, l, 4);
                    l += __shfl_xor_sync(0xffffffffu, l, 8);
                    l += __shfl_xor_sync(0xffffffffu, l, 16);
                    if (!fle) mbar_wait(BAR(B_FLE + fb), fpar);
                    if (j4 == 0) {
#pragma unroll
                        for (int i = 0; i < 12; i++) { mb[4 + 16 * i + g4] = acc[i][0]; mb[4 + 16 * i + 8 + g4] = acc[i][2]; }
                    }
                    if (lane == 0) { mb[0] = m_run; mb[1] = l; mb[2] = __int_as_float(cnt); }
                    __syncwarp();
                    if (lane == 0) mbar_arrive(BAR(B_FLF + fb));
                    if (++fb == NBUF) { fb = 0; fpar ^= 1; }
                    flushed++;
                    cur = -1;
                }
                if (mt_ & META_END) {
                    CLK(21);
                    if (flushed == 0 && lane == 0) mbar_arrive(BAR(B_FLF));
                    break;
                }
                cur = run;
                const int qi = (mt_ >> 8) & 0xff;
#pragma unroll
                for (int i = 0; i < 12; i++) { acc[i][0] = acc[i][1] = acc[i][2] = acc[i][3] = 0.f; }
                m_run = NEG_BIG; l_run = 0.f; cnt = 0;
#pragma unroll
                for (int ks = 0; ks < 12; ks++) {
                    qf[ks][0] = q32[qi * 96 + ks * 8 + j4];
                    qf[ks][1] = q32[qi * 96 + ks * 8 + 4 + j4];
                }
            }
            cnt++;
            if (half == 0) DBG(pair);
            const uint32_t kb = sb + SM_RING + s * CHUNK;
            int sv = s + 1; uint32_t parv = par;
            if (sv == NSLOT) { sv = 0; parv ^= 1; }
            float sc[6][4] = {};
            uint32_t vready;
            {
                uint32_t a[12][4];
#pragma unroll
                for (int t = 0; t < 3; t++) {
                    const uint32_t bt = kb + offK[t];
#pragma unroll
                    for (int kk = 0; kk < 4; kk++) ldsm4(a[t * 4 + kk], bt ^ (kk << 5));
                }
                vready = mbar_try(BAR(B_FULL + sv), parv);
#pragma unroll
                for (int i = 0; i < 12; i++) mma16816(sc[i % 6], a[i], qf[i][0], qf[i][1]);
            }
            __syncwarp();
            if (lane == 0) mbar_arrive(BAR(B_EMPTY + s));
            const float scale = 0.07216878364870322f;
            float s0 = bfr(bfr(((sc[0][0] + sc[1][0]) + (sc[2][0] + sc[3][0])) + (sc[4][0] + sc[5][0])) * scale);
            float s1 = bfr(bfr(((sc[0][2] + sc[1][2]) + (sc[2][2] + sc[3][2])) + (sc[4][2] + sc[5][2])) * scale);
            float tm = fmaxf(s0, s1);
            tm = fmaxf(tm, __shfl_xor_sync(0xffffffffu, tm, 4));
            tm = fmaxf(tm, __shfl_xor_sync(0xffffffffu, tm, 8));
            tm = fmaxf(tm, __shfl_xor_sync(0xffffffffu, tm, 16));
            if (tm > m_run) {
                float alpha = ex2((m_run - tm) * LOG2E);
                l_run *= alpha;
#pragma unroll
                for (int i = 0; i < 12; i++) { acc[i][0] *= alpha; acc[i][1] *= alpha; acc[i][2] *= alpha; acc[i][3] *= alpha; }
                m_run = tm;
            }
            float p0 = ex2((s0 - m_run) * LOG2E);
            float p1 = ex2((s1 - m_run) * LOG2E);
            l_run += p0 + p1;
            const uint32_t pw = pack_bf(p0, p1);
            const uint32_t pa = __shfl_sync(0xffffffffu, pw, 8 * j4), pb = __shfl_sync(0xffffffffu, pw, 8 * j4 + 4);
            const uint32_t b0 = __byte_perm(pa, pb, 0x5410), b1 = __byte_perm(pa, pb, 0x7632);
            if (!vready) mbar_wait(BAR(B_FULL + sv), parv);
            s += 4;
            if (s >= NSLOT) { s -= NSLOT; par ^= 1; }
            if (half == 0) DBG(2 + pair);
            ready = mbar_try(BAR(B_FULL + s), par);
            const uint32_t vb = sb + SM_RING + sv * CHUNK;
            {
                uint32_t a[12][4];
#pragma unroll
                for (int t = 0; t < 3; t++) {
                    const uint32_t bt = vb + offV[t];
#pragma unroll
                    for (int kk = 0; kk < 4; kk++) ldsm4t(a[t * 4 + kk], bt ^ (kk << 5));
                }
#pragma unroll
                for (int i = 0; i < 12; i++) mma16816(acc[i], a[i], b0, b1);
            }
            __syncwarp();
            if (lane == 0) mbar_arrive(BAR(B_EMPTY + sv));
        }
        TS(7);
        CLK(18);
    } else if (wid == 4) {
        int fb = 0; uint32_t fpar = 0;
#pragma unroll 1
        for (int f = 0;; f++) {
            const float* mb = reinterpret_cast<const float*>(smem + SM_MERGE) + fb * 800;
            mbar_wait(BAR(B_FLF + fb), fpar);
            const int head = (int)meta[16 + f];
            if (head == 0xFF) break;
            float m0 = mb[0], m1 = mb[200], m2 = mb[400], m3 = mb[600];
            float M = fmaxf(fmaxf(m0, m1), fmaxf(m2, m3));
            float w0 = ex2((m0 - M) * LOG2E), w1 = ex2((m1 - M) * LOG2E);
            float w2 = ex2((m2 - M) * LOG2E), w3 = ex2((m3 - M) * LOG2E);
            const int idx = head < NG * GH ? rank : cta;
            uint4* dst = &g_dat[head][idx][0];
            float o[6];
#pragma unroll
            for (int i = 0; i < 6; i++) {
                int d = 4 + (i < 3 ? 3 * lane + i : 96 + 3 * lane + (i - 3));
                o[i] = w0 * mb[d] + w1 * mb[200 + d] + w2 * mb[400 + d] + w3 * mb[600 + d];
            }
            float L = w0 * mb[1] + w1 * mb[201] + w2 * mb[401] + w3 * mb[601];
            const uint32_t tiles = __float_as_int(mb[2]) + __float_as_int(mb[402]);
            st_pk16(dst + lane, __float_as_uint(o[0]), __float_as_uint(o[1]), __float_as_uint(o[2]), tag);
            st_pk16(dst + 32 + lane, __float_as_uint(o[3]), __float_as_uint(o[4]), __float_as_uint(o[5]), tag);
            if (lane == 0) st_pk16(&g_hdr[head][idx], __float_as_uint(M), __float_as_uint(L), tiles, tag);
            __syncwarp();
            if (lane == 0) mbar_arrive(BAR(B_FLE + fb));
            if (++fb == NBUF) { fb = 0; fpar ^= 1; }
            if (meta[16 + f + 1] == 0xFFu) break;
        }
        TS(8);
        CLK(18);
    } else if (wid >= 6) {
        if (cta < 128) {
            const int t = tid - 192;
            uint32_t* cb32 = reinterpret_cast<uint32_t*>(smem + SM_CB);
            uint32_t* sb32 = reinterpret_cast<uint32_t*>(smem + SM_SB);
            const int col = cta * 5 + t;
            int off[12];
            uint32_t val[12];
#pragma unroll
            for (int rep = 0; rep < 5; rep++) { off[2 * rep] = 960 + t + 64 * rep; off[2 * rep + 1] = 1280 + t + 64 * rep; }
            off[10] = t < 5 ? (1280 + col) >> 1 : 960;
            off[11] = t < 5 ? (3200 + col) >> 1 : 960;
            poll8<12>(g_mod, off, val, tag);
#pragma unroll
            for (int rep = 0; rep < 5; rep++) {
                sb32[t + 64 * rep] = val[2 * rep];
                cb32[t + 64 * rep] = pack_bf(1.0f + bf_lo(val[2 * rep + 1]), 1.0f + bf_hi(val[2 * rep + 1]));
            }
            if (t < 5) {
                own[t] = (col & 1) ? bf_hi(val[10]) : bf_lo(val[10]);
                own[8 + t] = (col & 1) ? bf_hi(val[11]) : bf_lo(val[11]);
                uint32_t xx = x32[col >> 1];
                own[16 + t] = (col & 1) ? bf_hi(xx) : bf_lo(xx);
            }
        }
        live = false;
    }
    }
    const uint32_t sb0 = sb;
    const int tid0 = tid;
#pragma unroll 1
    while (cta < 128) {
        uint32_t sb = sb0; int tid = tid0;
        asm volatile("" : "+r"(sb), "+r"(tid));
        const int wid = tid >> 5, lane = tid & 31;
        const int g4 = lane >> 2, j4 = lane & 3, mi = lane >> 3, l8 = lane & 7;
        CLK(19);
        if (wid >= 5) {
            const int h = cta >> 2, js = cta & 3;
            const bool gl = h >= NG * GH;
            const int ncand = gl ? G : (G - h / GH + NG - 1) / NG;
            const int k = lane & 15, rr = (wid - 5) * 2 + (lane >> 4);
            if (live) {
                const unsigned* cp = &g_ctr[(tag - 1) & 1][(gl ? NG : h / GH) * 32];
                const unsigned thr = ((gl ? h - NG * GH : h % GH) + 1) * TPH;
                uint32_t it = 0;
                while (true) {
                    unsigned v;
                    asm volatile("ld.relaxed.gpu.global.u32 %0, [%1];" : "=r"(v) : "l"(cp) : "memory");
                    if (v >= thr) break;
                    __nanosleep(300);
                    if (++it > SPIN_LIMIT) __trap();
                }
            }
            const uint4* hdr = &g_hdr[h][lane];
            const uint4* dat = &g_dat[h][rr][16 * js + k];
            float* part = stage;
            float L, a0, a1, a2;
            uint32_t it = 0;
            uint4 hd[5], dv[MAXG / 6];
#pragma unroll
            for (int i = 0; i < 5; i++) hd[i] = make_uint4(0, 0, 0, 0);
#pragma unroll
            for (int i = 0; i < MAXG / 6; i++) dv[i] = make_uint4(0, 0, 0, 0);
#pragma unroll 1
            while (true) {
                FreshN<5, 32>::run(hd, hdr, tag, live, lane, 32, ncand);
                FreshN<MAXG / 6, 6 * 64>::run(dv, dat, tag, live, rr, 6, ncand);
                float w[5], M = NEG_BIG;
                int c = 0;
#pragma unroll
                for (int i = 0; i < 5; i++) {
                    const bool v = hd[i].w == tag;
                    w[i] = v ? __uint_as_float(hd[i].x) : NEG_BIG;
                    M = fmaxf(M, w[i]);
                    c += v ? (int)hd[i].z : 0;
                }
                c = __reduce_add_sync(0xffffffffu, c);
                if (++it > SPIN_LIMIT) __trap();
                if (live && c != TPH) continue;
                CLK(1);
#pragma unroll
                for (int o = 16; o > 0; o >>= 1) M = fmaxf(M, __shfl_xor_sync(0xffffffffu, M, o));
                float ls = 0.f;
#pragma unroll
                for (int i = 0; i < 5; i++) {
                    const bool v = w[i] != NEG_BIG;
                    const float e = ex2((w[i] - M) * LOG2E);
                    w[i] = v ? e : -0.0f;
                    ls = fmaf(w[i], __uint_as_float(hd[i].y), ls);
                }
                float* wsm = reinterpret_cast<float*>(smem + SM_X2) + (wid - 5) * 160;
                if (live) {
#pragma unroll
                    for (int i = 0; i < 5; i++) wsm[lane + 32 * i] = w[i];
                }
                __syncwarp();
                uint32_t badm = 0;
                a0 = a1 = a2 = 0.f;
#pragma unroll
                for (int i = 0; i < MAXG / 6; i++) {
                    const float wi = wsm[rr + 6 * i];
                    badm |= (dv[i].w ^ tag) & ~(uint32_t)(__float_as_int(wi) >> 31);
                    a0 = fmaf(wi, __uint_as_float(dv[i].x), a0);
                    a1 = fmaf(wi, __uint_as_float(dv[i].y), a1);
                    a2 = fmaf(wi, __uint_as_float(dv[i].z), a2);
                }
                const bool bad = badm != 0;
                __syncwarp();
                L = warp_sum(ls);
                if (!__any_sync(0xffffffffu, bad) || !live) break;
            }
            a0 += __shfl_xor_sync(0xffffffffu, a0, 16);
            a1 += __shfl_xor_sync(0xffffffffu, a1, 16);
            a2 += __shfl_xor_sync(0xffffffffu, a2, 16);
            CLK(2);
            if (live && lane < 16) { float* pp = part + (wid - 5) * 48 + 3 * k; pp[0] = a0; pp[1] = a1; pp[2] = a2; }
            if (live) asm volatile("bar.sync 2, 96;" ::: "memory");
            if (wid == 5 || !live) {
                uint16_t* osw = reinterpret_cast<uint16_t*>(smem + SM_SC);
                const float inv = __fdividef(1.0f, L);
                const float o0 = (part[lane] + part[48 + lane]) + part[96 + lane];
                const float o1 = (part[32 + (lane & 15)] + part[80 + (lane & 15)]) + part[128 + (lane & 15)];
                if (live) { osw[lane] = (uint16_t)(__float_as_uint(bfr(o0 * inv)) >> 16); if (lane < 16) osw[32 + lane] = (uint16_t)(__float_as_uint(bfr(o1 * inv)) >> 16); }
            }
            if (live) TS(10);
        }
        if (wid < 5 || !live) {
            const int w5 = wid < 5 ? wid : wid - 5;
            uint32_t wa[8][3][4];
            if (live) mbar_wait(BAR(B_WO + w5), 0);
#pragma unroll
            for (int i = 0; i < 8; i++) {
                const int cc = 2 * (i & 3) + (mi & 1);
#pragma unroll
                for (int ks = 0; ks < 3; ks++) {
                    const int r = ks * 16 + l8 + 8 * (mi >> 1);
                    ldsm4t(wa[i][ks], sb + SM_WO + (2 * w5 + (i >> 2)) * 6144 + r * 128 + ((cc ^ (r & 7)) << 4));
                }
            }
            if (live) bar_cons();
            if (live) TS(9);
            CLK(3);
            const uint32_t* os32 = reinterpret_cast<const uint32_t*>(smem + SM_SC);
            float acc[8][4] = {};
#pragma unroll
            for (int ks = 0; ks < 3; ks++) {
                const uint32_t b0 = os32[ks * 8 + j4], b1 = os32[ks * 8 + 4 + j4];
#pragma unroll
                for (int i = 0; i < 8; i++) mma16816(acc[i], wa[i][ks], b0, b1);
            }
            if (live && j4 == 0) {
#pragma unroll
                for (int i = 0; i < 8; i++) { stage[(w5 * 8 + i) * 16 + g4] = acc[i][0]; stage[(w5 * 8 + i) * 16 + 8 + g4] = acc[i][2]; }
            }
        } else {
            bar_cons();
        }
        CLK(4);
        if (live) bar_cons();
        {
            const int o = tid >> 1, kk = tid & 1;
            const float* sp = stage + o * 5 + kk * 3;
            float v0 = sp[0], v1 = sp[1], v2 = kk ? 0.f : sp[2];
            if (live) st_pk16(&g_h1[o][cta][kk], __float_as_uint(v0), __float_as_uint(v1), __float_as_uint(v2), tag);
        }
        if (live) TS(11);
        CLK(5);
        if (wid == 0 || !live) {
            const uint4* p = &g_h1[cta][0][0] + lane;
            uint4 v[8];
            uint32_t it = 0;
            while (true) {
                bool ok = true;
                LoadN<8, 32>::run(v, p, live, 0, 0, 1);
#pragma unroll
                for (int j = 0; j < 8; j++) ok = ok && v[j].w == tag;
                if (__all_sync(0xffffffffu, ok) || !live) break;
                if (++it > SPIN_LIMIT) __trap();
            }
            CLK(6);
            float a0 = 0.f, a1 = 0.f, a2 = 0.f;
#pragma unroll
            for (int j = 0; j < 8; j++) { a0 += __uint_as_float(v[j].x); a1 += __uint_as_float(v[j].y); a2 += __uint_as_float(v[j].z); }
#pragma unroll
            for (int o = 2; o <= 16; o <<= 1) {
                a0 += __shfl_xor_sync(0xffffffffu, a0, o);
                a1 += __shfl_xor_sync(0xffffffffu, a1, o);
                a2 += __shfl_xor_sync(0xffffffffu, a2, o);
            }
            const float gx = own[lane & 7], xx = own[16 + (lane & 7)];
            const float t0 = __shfl_sync(0xffffffffu, a0, lane >= 3), t1 = __shfl_sync(0xffffffffu, a1, lane >= 3);
            const float sum = (lane == 0 || lane == 3) ? t0 : (lane == 2 ? a2 : t1);
            const float x2 = bfr(xx + bfr(gx * bfr(sum)));
            if (live && lane < 5) own[24 + lane] = x2;
            const float y1 = __shfl_sync(0xffffffffu, x2, 1), y2 = __shfl_sync(0xffffffffu, x2, 2);
            const float y3 = __shfl_sync(0xffffffffu, x2, 3), y4 = __shfl_sync(0xffffffffu, x2, 4);
            if (live && lane == 0) st_pk16(&g_x2[cta][0], pack_bf(x2, y1), pack_bf(y2, y3), pack_bf(y4, 0.f), tag);
            if (live) TS(13);
        }
        CLK(8);
        if (cta < 96) {
            uint32_t a1[5][4], a3[5][4], a2[5][4];
            if (live) mbar_wait3(BAR(B_W1 + (wid >> 2)), BAR(B_W3 + (wid >> 2)), BAR(B_W2 + (wid >> 2)));
            const uint32_t w2b = sb + SM_RING + meta[10 + (wid >> 2)] % NSLOT * CHUNK;
#pragma unroll
            for (int ks = 0; ks < 5; ks++) {
                const int r = wid * 80 + ks * 16 + l8 + 8 * (mi >> 1);
                const uint32_t off = r * 32 + (((mi & 1) ^ ((r >> 2) & 1)) << 4);
                ldsm4t(a1[ks], sb + SM_W1 + off);
                ldsm4t(a3[ks], sb + SM_W3 + off);
            }
#pragma unroll
            for (int i = 0; i < 5; i++) {
                const int mt = (wid & 3) * 5 + i;
                const int cc = 2 * (mt & 3) + (mi & 1);
                const int r = l8 + 8 * (mi >> 1);
                ldsm4t(a2[i], w2b + (mt >> 2) * 2048 + r * 128 + ((cc ^ (r & 7)) << 4));
            }
            CLK(9);
            float* x2s = reinterpret_cast<float*>(smem + SM_X2);
            float* st8 = red + 256;
            if (wid >= 4) {
                uint4 v = poll16(&g_x2[tid - 128][0], tag, live);
                const float e0 = bf_lo(v.x), e1 = bf_hi(v.x), e2 = bf_lo(v.y), e3 = bf_hi(v.y), e4 = bf_lo(v.z);
                float* d = x2s + (tid - 128) * 5;
                if (live) { d[0] = e0; d[1] = e1; d[2] = e2; d[3] = e3; d[4] = e4; }
                const float pv = __shfl_sync(0xffffffffu, e0, 0);
                const float d0 = e0 - pv, d1 = e1 - pv, d2 = e2 - pv, d3 = e3 - pv, d4 = e4 - pv;
                float s1 = ((d0 + d1) + (d2 + d3)) + d4;
                float s2 = fmaf(d0, d0, fmaf(d1, d1, fmaf(d2, d2, fmaf(d3, d3, d4 * d4))));
#pragma unroll
                for (int o = 16; o > 0; o >>= 1) { s1 += __shfl_xor_sync(0xffffffffu, s1, o); s2 += __shfl_xor_sync(0xffffffffu, s2, o); }
                if (live && lane == 0) { st8[2 * (wid - 4)] = pv + s1 * (1.0f / 160.0f); st8[2 * (wid - 4) + 1] = s2 - s1 * s1 * (1.0f / 160.0f); }
            }
            if (live) bar_cons();
            if (live) TS(14);
            CLK(10);
            const float4 sA = *reinterpret_cast<const float4*>(st8), sB = *reinterpret_cast<const float4*>(st8 + 4);
            const float mean = ((sA.x + sA.z) + (sB.x + sB.z)) * 0.25f;
            const float u0 = sA.x - mean, u1 = sA.z - mean, u2 = sB.x - mean, u3 = sB.z - mean;
            const float m2 = ((sA.y + sA.w) + (sB.y + sB.w)) + 160.0f * ((u0 * u0 + u1 * u1) + (u2 * u2 + u3 * u3));
            const float mean_b = bfr(mean);
            const float rden = __fdividef(1.0f, bfr(fsqrt(bfr(bfr(m2 * (1.0f / 640.0f)) + 1e-5f))));
            const uint32_t* cb32 = reinterpret_cast<const uint32_t*>(smem + SM_CB);
            const uint32_t* sb32 = reinterpret_cast<const uint32_t*>(smem + SM_SB);
#pragma unroll
            for (int rep = 0; rep < 2; rep++) {
                const int p = lane + 32 * rep;
                if (p < 40) {
                    int pp = wid * 40 + p;
                    const float2 xv = *reinterpret_cast<const float2*>(x2s + 2 * pp);
                    uint32_t cv = cb32[pp], sv = sb32[pp];
                    float n0 = bfr(bfr(xv.x - mean_b) * rden), n1 = bfr(bfr(xv.y - mean_b) * rden);
                    uint32_t hv = pack_bf(bfr(n0 * bf_lo(cv)) + bf_lo(sv), bfr(n1 * bf_hi(cv)) + bf_hi(sv));
                    if (live) h32[pp] = hv;
                }
            }
            __syncwarp();
            CLK(11);
            float ag[2][4] = {}, au[2][4] = {};
#pragma unroll
            for (int ks = 0; ks < 5; ks++) {
                const int r0 = wid * 80 + ks * 16;
                const uint32_t b0 = h32[(r0 >> 1) + j4], b1 = h32[(r0 >> 1) + 4 + j4];
                mma16816(ag[ks & 1], a1[ks], b0, b1);
                mma16816(au[ks & 1], a3[ks], b0, b1);
            }
            if (live && j4 == 0) {
                red[wid * 32 + g4] = ag[0][0] + ag[1][0]; red[wid * 32 + 8 + g4] = ag[0][2] + ag[1][2];
                red[wid * 32 + 16 + g4] = au[0][0] + au[1][0]; red[wid * 32 + 24 + g4] = au[0][2] + au[1][2];
            }
            CLK(12);
            if (live) bar_cons();
            if (live) TS(15);
            CLK(13);
            float v = 0.f;
#pragma unroll
            for (int w = 0; w < 8; w++) v += red[w * 32 + lane];
            v = bfr(v);
            float up = __shfl_down_sync(0xffffffffu, v, 16);
            float hact = bfr(bfr(silu(v)) * up);
            float e0 = __shfl_sync(0xffffffffu, hact, 2 * j4), e1 = __shfl_sync(0xffffffffu, hact, 2 * j4 + 1);
            float e2 = __shfl_sync(0xffffffffu, hact, 2 * j4 + 8), e3 = __shfl_sync(0xffffffffu, hact, 2 * j4 + 9);
            const uint32_t b0 = pack_bf(e0, e1), b1 = pack_bf(e2, e3);
            float acc[5][4] = {};
#pragma unroll
            for (int i = 0; i < 5; i++) mma16816(acc[i], a2[i], b0, b1);
            if (live && j4 == 0) {
#pragma unroll
                for (int i = 0; i < 5; i++) { stage[(wid * 5 + i) * 16 + g4] = acc[i][0]; stage[(wid * 5 + i) * 16 + 8 + g4] = acc[i][2]; }
            }
            CLK(14);
            if (live) bar_cons();
            const int o = tid >> 1, k = tid & 1;
            const float* sp = stage + o * 5 + k * 3;
            float v0 = sp[0], v1 = sp[1], v2 = k ? 0.f : sp[2];
            if (live) st_pk16(&g_h3[o][cta][k], __float_as_uint(v0), __float_as_uint(v1), __float_as_uint(v2), tag);
        }
        if (live) TS(16);
        CLK(15);
        if (wid == 0 || !live) {
            const uint4* p = &g_h3[cta][0][0] + lane;
            uint4 v[6];
            uint32_t it = 0;
            if (live && cta < 96) spin(P_DLY);
            while (true) {
                bool ok = true;
                LoadN<6, 32>::run(v, p, live, 0, 0, 1);
#pragma unroll
                for (int j = 0; j < 6; j++) ok = ok && v[j].w == tag;
                if (__all_sync(0xffffffffu, ok) || !live) break;
                if (++it > SPIN_LIMIT) __trap();
            }
            CLK(16);
            float a0 = 0.f, a1 = 0.f, a2 = 0.f;
#pragma unroll
            for (int j = 0; j < 6; j++) { a0 += __uint_as_float(v[j].x); a1 += __uint_as_float(v[j].y); a2 += __uint_as_float(v[j].z); }
#pragma unroll
            for (int o = 2; o <= 16; o <<= 1) {
                a0 += __shfl_xor_sync(0xffffffffu, a0, o);
                a1 += __shfl_xor_sync(0xffffffffu, a1, o);
                a2 += __shfl_xor_sync(0xffffffffu, a2, o);
            }
            const float gx = own[8 + (lane & 7)], xx = own[24 + (lane & 7)];
            const float t0 = __shfl_sync(0xffffffffu, a0, lane >= 3), t1 = __shfl_sync(0xffffffffu, a1, lane >= 3);
            const float sum = (lane == 0 || lane == 3) ? t0 : (lane == 2 ? a2 : t1);
            const float y = xx + bfr(gx * bfr(sum));
            if (live && lane < 5) reinterpret_cast<uint16_t*>(out)[cta * 5 + lane] = (uint16_t)(__float_as_uint(bfr(y)) >> 16);
            if (live && cta == 0 && lane == 0) g_epoch = tag;
        }
        CLK(17);
        if (live) { TS(18); break; }
        live = true;
    }
    }
}

typedef CUresult (*EncodeFn)(CUtensorMap*, CUtensorMapDataType, cuuint32_t, void*, const cuuint64_t*, const cuuint64_t*,
                             const cuuint32_t*, const cuuint32_t*, CUtensorMapInterleave, CUtensorMapSwizzle,
                             CUtensorMapL2promotion, CUtensorMapFloatOOBfill);

void make_map(EncodeFn enc, CUtensorMap* tm, const void* ptr, uint64_t cols, uint64_t rows, uint32_t box_c, uint32_t box_r,
              CUtensorMapSwizzle sw, CUtensorMapL2promotion prom) {
    cuuint64_t dims[2] = {cols, rows};
    cuuint64_t strides[1] = {cols * 2};
    cuuint32_t box[2] = {box_c, box_r};
    cuuint32_t es[2] = {1, 1};
    enc(tm, CU_TENSOR_MAP_DATA_TYPE_BFLOAT16, 2, const_cast<void*>(ptr), dims, strides, box, es,
        CU_TENSOR_MAP_INTERLEAVE_NONE, sw, prom, CU_TENSOR_MAP_FLOAT_OOB_FILL_NONE);
}

}

extern "C" void kernel_launch(void* const* d_in, const int* in_sizes, int n_in, void* d_out, int out_size) {
    (void)in_sizes; (void)n_in; (void)out_size;
    static EncodeFn enc = nullptr;
    static int num_sms = 0;
    if (!enc) {
        void* fn = nullptr;
        cudaDriverEntryPointQueryResult qr;
        cudaGetDriverEntryPoint("cuTensorMapEncodeTiled", &fn, cudaEnableDefault, &qr);
        enc = (EncodeFn)fn;
        cudaDeviceGetAttribute(&num_sms, cudaDevAttrMultiProcessorCount, 0);
        cudaFuncSetAttribute(fused_decode_kernel, cudaFuncAttributeMaxDynamicSharedMemorySize, SM_TOTAL);
    }
    CUtensorMap tmK, tmV, tmMod, tmWq, tmWo, tmW1, tmW3, tmW2;
    const uint64_t kv_lines = (uint64_t)NH * SK * 3;
    make_map(enc, &tmK, d_in[1], 64, kv_lines, 64, 96, CU_TENSOR_MAP_SWIZZLE_128B, CU_TENSOR_MAP_L2_PROMOTION_L2_128B);
    make_map(enc, &tmV, d_in[2], 64, kv_lines, 64, 96, CU_TENSOR_MAP_SWIZZLE_128B, CU_TENSOR_MAP_L2_PROMOTION_L2_128B);
    make_map(enc, &tmWq, d_in[3], NH * DH, D, 48, 128, CU_TENSOR_MAP_SWIZZLE_NONE, CU_TENSOR_MAP_L2_PROMOTION_L2_128B);
    make_map(enc, &tmWo, d_in[4], D, NH * DH, 64, 48, CU_TENSOR_MAP_SWIZZLE_128B, CU_TENSOR_MAP_L2_PROMOTION_L2_128B);
    make_map(enc, &tmW1, d_in[6], FF, D, 16, 160, CU_TENSOR_MAP_SWIZZLE_32B, CU_TENSOR_MAP_L2_PROMOTION_L2_128B);
    make_map(enc, &tmW3, d_in[7], FF, D, 16, 160, CU_TENSOR_MAP_SWIZZLE_32B, CU_TENSOR_MAP_L2_PROMOTION_L2_128B);
    make_map(enc, &tmW2, d_in[8], D, FF, 64, 16, CU_TENSOR_MAP_SWIZZLE_128B, CU_TENSOR_MAP_L2_PROMOTION_L2_128B);
    make_map(enc, &tmMod, d_in[10], 6 * D, D, 32, 160, CU_TENSOR_MAP_SWIZZLE_64B, CU_TENSOR_MAP_L2_PROMOTION_L2_128B);
    int grid = num_sms < MAXG ? num_sms : MAXG;
    fused_decode_kernel<<<grid, NTHREADS, SM_TOTAL, cudaStreamPerThread>>>(
        tmK, tmV, tmMod, tmWq, tmWo, tmW1, tmW3, tmW2, (const __nv_bfloat16*)d_in[0], (const __nv_bfloat16*)d_in[9],
        (__nv_bfloat16*)d_out);
}
```

```cpp
#include <cuda_runtime.h>
#include <cuda_bf16.h>
#include <cuda.h>
#include <stdint.h>

namespace {

constexpr int D = 640, NH = 32, SK = 8192, DH = 192, FF = 1536;
constexpr int NG = 4;
constexpr int GH = 7;
constexpr int NGLOB = NH - NG * GH;
constexpr int NQH = GH + NGLOB;
constexpr int TILE = 32;
constexpr int TPH = SK / TILE;
constexpr int GT = GH * TPH;
constexpr int PT = NGLOB * TPH;
constexpr int CHUNK = TILE * DH * 2;
#define P_NSLOT 8
#define P_WIN 3
#define P_URG 0
#define P_HOLD 3
#define P_TWIN P_WIN
#define P_BACKOFF 100
#define P_PRONW 6
#define P_DLY 450
constexpr int NSLOT = P_NSLOT;
constexpr int WIN = P_WIN;
#define P_NBUF 3
constexpr int NBUF = P_NBUF;
constexpr int MAXG = 132;
constexpr int NTHREADS = 288;
constexpr float NEG_BIG = -3.402823466e38f;

constexpr int SM_WMOD = 0;
constexpr int SM_WQ = 40960;
constexpr int SM_WO = 0;
constexpr int SM_W1 = 61440;
constexpr int SM_W3 = 81920;
constexpr int SM_RING = 102400;
constexpr int SM_MISC = SM_RING + NSLOT * CHUNK;
constexpr int SM_BARS = SM_MISC;
constexpr int SM_META = SM_BARS + 512;
constexpr int SM_Q = SM_META + 256;
constexpr int SM_SC = SM_Q + NQH * DH * 2;
constexpr int SM_H = SM_SC + 1280;
constexpr int SM_X = SM_H + 1280;
constexpr int SM_CB = SM_X + 1280;
constexpr int SM_SB = SM_CB + 1280;
constexpr int SM_OWN = SM_SB + 1280;
constexpr int SM_RED = SM_OWN + 128;
constexpr int SM_MERGE = SM_RED + 2048;
constexpr int SM_STAGE = SM_MERGE + NBUF * 3200;
constexpr int SM_X2 = SM_STAGE + 2560;
constexpr int SM_FIN = SM_X2 + 2560;
constexpr int SM_TOTAL = SM_FIN + 512;
static_assert(SM_TOTAL <= 232448, "shared memory budget");

constexpr int B_FULL = 0;
constexpr int B_EMPTY = 8;
constexpr int B_MOD = 16;
constexpr int B_WQ = 20;
constexpr int B_WO = 25;
constexpr int B_W1 = 30;
constexpr int B_W3 = 32;
constexpr int B_W2 = 34;
constexpr int B_PRO = 36, B_DUMMY = 37, B_CLR = 38;
constexpr int B_FLF = 40, B_FLE = 44;
constexpr int B_LAST = 48;
static_assert(NSLOT <= 8 && NSLOT >= 6 && WIN <= 4 && WIN <= NSLOT - 3, "barrier map / end markers vs window");
constexpr uint32_t META_END = 0x10000u;

__device__ unsigned g_epoch;
__device__ unsigned g_ctr[2][(NG + 1) * 32];
__device__ __align__(128) unsigned long long g_mod[1920];
__device__ __align__(128) unsigned long long g_q[3072];
__device__ __align__(128) uint4 g_hdr[NH][MAXG];
__device__ __align__(128) uint4 g_dat[NH][MAXG][64];
__device__ __align__(128) uint4 g_h1[128][128][2];
__device__ __align__(128) uint4 g_x2[128][2];
__device__ __align__(128) uint4 g_h3[128][96][2];

#define TS(k) do {} while (0)
#define DBG(k) do {} while (0)
#define EARLY(k) do {} while (0)
#define CLK(k) do {} while (0)

__device__ __forceinline__ uint32_t smem_u32(const void* p) { return (uint32_t)__cvta_generic_to_shared(p); }
__device__ __forceinline__ void mbar_init(uint32_t bar, uint32_t cnt) {
    asm volatile("mbarrier.init.shared::cta.b64 [%0], %1;" ::"r"(bar), "r"(cnt) : "memory");
}
__device__ __forceinline__ void mbar_expect_tx(uint32_t bar, uint32_t bytes) {
    asm volatile("mbarrier.arrive.expect_tx.shared::cta.b64 _, [%0], %1;" ::"r"(bar), "r"(bytes) : "memory");
}
__device__ __forceinline__ void mbar_arrive(uint32_t bar) {
    asm volatile("mbarrier.arrive.shared::cta.b64 _, [%0];" ::"r"(bar) : "memory");
}
constexpr uint32_t SPIN_LIMIT = 1u << 22;
__device__ __forceinline__ void mbar_wait(uint32_t bar, uint32_t parity) {
    asm volatile(
        "{\n.reg .pred p;\n.reg .u32 c;\nmov.u32 c, 0;\n"
        "LW:\nmbarrier.try_wait.parity.shared::cta.b64 p, [%0], %1;\n@p bra LD;\n"
        "add.u32 c, c, 1;\nsetp.lt.u32 p, c, 0x400000;\n@p bra LW;\ntrap;\nLD:\n}" ::"r"(bar), "r"(parity)
        : "memory");
}
__device__ __forceinline__ uint32_t mbar_try(uint32_t bar, uint32_t parity) {
    uint32_t ok;
    asm volatile("{\n.reg .pred p;\nmbarrier.try_wait.parity.shared::cta.b64 p, [%1], %2;\nselp.u32 %0, 1, 0, p;\n}"
                 : "=r"(ok) : "r"(bar), "r"(parity) : "memory");
    return ok;
}
__device__ __forceinline__ void mbar_wait3(uint32_t b0, uint32_t b1, uint32_t b2) {
    asm volatile(
        "{\n.reg .pred p, q, r;\n.reg .u32 c;\nmov.u32 c, 0;\n"
        "LW:\nmbarrier.try_wait.parity.shared::cta.b64 p, [%0], 0;\n"
        "mbarrier.try_wait.parity.shared::cta.b64 q, [%1], 0;\n"
        "mbarrier.try_wait.parity.shared::cta.b64 r, [%2], 0;\n"
        "and.pred p, p, q;\nand.pred p, p, r;\n@p bra LD;\n"
        "add.u32 c, c, 1;\nsetp.lt.u32 p, c, 0x400000;\n@p bra LW;\ntrap;\nLD:\n}" ::"r"(b0), "r"(b1), "r"(b2)
        : "memory");
}
__device__ __forceinline__ void tma2d(uint32_t dst, const CUtensorMap* tm, int c0, int c1, uint32_t bar) {
    asm volatile(
        "cp.async.bulk.tensor.2d.shared::cluster.global.mbarrier::complete_tx::bytes [%0], [%1, {%3, %4}], [%2];" ::"r"(dst),
        "l"(tm), "r"(bar), "r"(c0), "r"(c1)
        : "memory");
}
__device__ __forceinline__ void tma2d_hint(uint32_t dst, const CUtensorMap* tm, int c0, int c1, uint32_t bar, uint64_t pol) {
    asm volatile(
        "cp.async.bulk.tensor.2d.shared::cluster.global.mbarrier::complete_tx::bytes.L2::cache_hint [%0], [%1, {%3, %4}], [%2], %5;" ::"r"(dst),
        "l"(tm), "r"(bar), "r"(c0), "r"(c1), "l"(pol)
        : "memory");
}
__device__ __forceinline__ void prefetch_tm(const CUtensorMap* tm) {
    asm volatile("prefetch.tensormap [%0];" ::"l"(tm) : "memory");
}
__device__ __forceinline__ void ldsm4(uint32_t (&r)[4], uint32_t addr) {
    asm volatile("ldmatrix.sync.aligned.m8n8.x4.shared.b16 {%0,%1,%2,%3}, [%4];"
                 : "=r"(r[0]), "=r"(r[1]), "=r"(r[2]), "=r"(r[3])
                 : "r"(addr));
}
__device__ __forceinline__ void ldsm4t(uint32_t (&r)[4], uint32_t addr) {
    asm volatile("ldmatrix.sync.aligned.m8n8.x4.trans.shared.b16 {%0,%1,%2,%3}, [%4];"
                 : "=r"(r[0]), "=r"(r[1]), "=r"(r[2]), "=r"(r[3])
                 : "r"(addr));
}
__device__ __forceinline__ void mma16816(float (&d)[4], const uint32_t (&a)[4], uint32_t b0, uint32_t b1) {
    asm volatile(
        "mma.sync.aligned.m16n8k16.row.col.f32.bf16.bf16.f32 {%0,%1,%2,%3}, {%4,%5,%6,%7}, {%8,%9}, {%0,%1,%2,%3};"
        : "+f"(d[0]), "+f"(d[1]), "+f"(d[2]), "+f"(d[3])
        : "r"(a[0]), "r"(a[1]), "r"(a[2]), "r"(a[3]), "r"(b0), "r"(b1));
}
__device__ __forceinline__ void bar_cons() { asm volatile("bar.sync 1, 256;" ::: "memory"); }
__device__ __forceinline__ void spin(int cycles) {
    long long t0 = clock64();
    while (clock64() - t0 < cycles) {}
}

__device__ __forceinline__ float bfr(float x) {
    uint32_t r;
    asm("cvt.rn.bf16x2.f32 %0, %1, %2;" : "=r"(r) : "f"(x), "f"(0.0f));
    return __uint_as_float(r);
}
__device__ __forceinline__ uint32_t pack_bf(float lo, float hi) {
    __nv_bfloat162 t = __floats2bfloat162_rn(lo, hi);
    return *reinterpret_cast<uint32_t*>(&t);
}
__device__ __forceinline__ float bf_lo(uint32_t v) { return __uint_as_float(v << 16); }
__device__ __forceinline__ float bf_hi(uint32_t v) { return __uint_as_float(v & 0xffff0000u); }

__device__ __forceinline__ void st_pk8(unsigned long long* p, uint32_t v, uint32_t tag) {
    unsigned long long w = ((unsigned long long)tag << 32) | v;
    asm volatile("st.relaxed.gpu.global.b64 [%0], %1;" ::"l"(p), "l"(w) : "memory");
}
template <int N>
__device__ __forceinline__ void poll8(const unsigned long long* base, const int (&off)[N], uint32_t (&val)[N], uint32_t tag) {
    uint32_t tg[N];
#pragma unroll
    for (int i = 0; i < N; i++) { val[i] = 0; tg[i] = 0; }
    uint32_t it = 0;
    while (true) {
#pragma unroll
        for (int i = 0; i < N; i++)
            asm volatile("{\n.reg .pred q;\n.reg .b64 t;\nsetp.ne.u32 q, %1, %3;\nmov.b64 t, {%0, %1};\n"
                         "@q ld.relaxed.gpu.global.b64 t, [%2];\nmov.b64 {%0, %1}, t;\n}"
                         : "+r"(val[i]), "+r"(tg[i]) : "l"(base + off[i]), "r"(tag) : "memory");
        bool ok = true;
#pragma unroll
        for (int i = 0; i < N; i++) ok = ok && tg[i] == tag;
        if (__all_sync(0xffffffffu, ok)) break;
        if (++it > SPIN_LIMIT) __trap();
        __nanosleep(P_BACKOFF);
    }
}
__device__ __forceinline__ void st_pk16(uint4* p, uint32_t a, uint32_t b, uint32_t c, uint32_t tag) {
    asm volatile(
        "{\n.reg .b128 t;\n.reg .b64 lo, hi;\nmov.b64 lo, {%1, %2};\nmov.b64 hi, {%3, %4};\nmov.b128 t, {lo, hi};\n"
        "st.relaxed.gpu.global.b128 [%0], t;\n}" ::"l"(p), "r"(a), "r"(b), "r"(c), "r"(tag)
        : "memory");
}
template <int OFF = 0>
__device__ __forceinline__ uint4 ld_raw16p(const uint4* p, uint32_t on) {
    uint4 v;
    asm volatile(
        "{\n.reg .b128 t;\n.reg .b64 lo, hi;\n.reg .pred q;\nsetp.ne.u32 q, %5, 0;\n"
        "mov.b64 lo, 0;\nmov.b128 t, {lo, lo};\n"
        "@q ld.relaxed.gpu.global.b128 t, [%4 + %6];\nmov.b128 {lo, hi}, t;\n"
        "mov.b64 {%0, %1}, lo;\nmov.b64 {%2, %3}, hi;\n}"
        : "=r"(v.x), "=r"(v.y), "=r"(v.z), "=r"(v.w)
        : "l"(p), "r"(on), "n"(OFF * 16)
        : "memory");
    return v;
}
template <int OFF>
__device__ __forceinline__ void ld_fresh16(uint4& v, const uint4* p, uint32_t tag, uint32_t on) {
    asm volatile(
        "{\n.reg .b128 t;\n.reg .b64 lo, hi;\n.reg .pred q;\nsetp.ne.u32 q, %3, %5;\nsetp.ne.and.u32 q, %6, 0, q;\n"
        "mov.b64 lo, {%0, %1};\nmov.b64 hi, {%2, %3};\nmov.b128 t, {lo, hi};\n"
        "@q ld.relaxed.gpu.global.b128 t, [%4 + %7];\nmov.b128 {lo, hi}, t;\n"
        "mov.b64 {%0, %1}, lo;\nmov.b64 {%2, %3}, hi;\n}"
        : "+r"(v.x), "+r"(v.y), "+r"(v.z), "+r"(v.w)
        : "l"(p), "r"(tag), "r"(on), "n"(OFF * 16)
        : "memory");
}
template <int N, int STRIDE, int I = 0>
struct FreshN {
    static __device__ __forceinline__ void run(uint4* v, const uint4* p, uint32_t tag, bool live, int base, int step, int lim) {
        ld_fresh16<I * STRIDE>(v[I], p, tag, live && base + step * I < lim);
        FreshN<N, STRIDE, I + 1>::run(v, p, tag, live, base, step, lim);
    }
};
template <int N, int STRIDE>
struct FreshN<N, STRIDE, N> {
    static __device__ __forceinline__ void run(uint4*, const uint4*, uint32_t, bool, int, int, int) {}
};
template <int N, int STRIDE, int I = 0>
struct LoadN {
    static __device__ __forceinline__ void run(uint4* v, const uint4* p, bool live, int base, int step, int lim) {
        v[I] = ld_raw16p<I * STRIDE>(p, live && base + step * I < lim);
        LoadN<N, STRIDE, I + 1>::run(v, p, live, base, step, lim);
    }
};
template <int N, int STRIDE>
struct LoadN<N, STRIDE, N> {
    static __device__ __forceinline__ void run(uint4*, const uint4*, bool, int, int, int) {}
};
__device__ __forceinline__ uint4 poll16(const uint4* p, uint32_t tag, bool live) {
    uint32_t it = 0;
    uint4 v;
    while (true) {
        v = ld_raw16p(p, live);
        if (__all_sync(0xffffffffu, v.w == tag) || !live) break;
        if (++it > SPIN_LIMIT) __trap();
    }
    return v;
}
__device__ __forceinline__ void st_zero16(void* p) {
    asm volatile("st.relaxed.gpu.global.v4.u32 [%0], {%1, %1, %1, %1};" ::"l"(p), "r"(0u) : "memory");
}
__device__ __forceinline__ float ex2(float x) {
    float y;
    asm("ex2.approx.ftz.f32 %0, %1;" : "=f"(y) : "f"(x));
    return y;
}
__device__ __forceinline__ float fsqrt(float x) {
    float y;
    asm("sqrt.approx.f32 %0, %1;" : "=f"(y) : "f"(x));
    return y;
}
constexpr float LOG2E = 1.4426950408889634f;
__device__ __forceinline__ float silu(float a) { return __fdividef(a, 1.0f + ex2(-a * LOG2E)); }
__device__ __forceinline__ float warp_sum(float v) {
#pragma unroll
    for (int o = 16; o > 0; o >>= 1) v += __shfl_xor_sync(0xffffffffu, v, o);
    return v;
}

__device__ __forceinline__ void ln_stats(const float (&v)[20], float& mean_b, float& den_b) {
    float s = 0.f;
#pragma unroll
    for (int i = 0; i < 20; i++) s += v[i];
    s = warp_sum(s);
    float mean = s * (1.0f / 640.0f);
    float q = 0.f;
#pragma unroll
    for (int i = 0; i < 20; i++) { float d = v[i] - mean; q += d * d; }
    q = warp_sum(q);
    float var_b = bfr(q * (1.0f / 640.0f));
    mean_b = bfr(mean);
    den_b = bfr(fsqrt(bfr(var_b + 1e-5f)));
}

struct Window {
    uint32_t bar[WIN];
    uint32_t par[WIN];
    __device__ __forceinline__ void init(uint32_t dummy) {
#pragma unroll
        for (int i = 0; i < WIN; i++) { bar[i] = dummy; par[i] = 1; }
    }
    __device__ __forceinline__ void push_tail(uint32_t b, uint32_t p) {
#pragma unroll
        for (int i = 1; i <= WIN - P_TWIN; i++) mbar_wait(bar[i], par[i]);
        push(b, p);
    }
    __device__ __forceinline__ void push(uint32_t b, uint32_t p, bool wait = true) {
        if (wait) mbar_wait(bar[0], par[0]);
#pragma unroll
        for (int i = 0; i + 1 < WIN; i++) { bar[i] = bar[i + 1]; par[i] = par[i + 1]; }
        bar[WIN - 1] = b; par[WIN - 1] = p;
    }
};

__global__ void __launch_bounds__(NTHREADS, 1)
fused_decode_kernel(const __grid_constant__ CUtensorMap tmK, const __grid_constant__ CUtensorMap tmV,
                    const __grid_constant__ CUtensorMap tmMod, const __grid_constant__ CUtensorMap tmWq,
                    const __grid_constant__ CUtensorMap tmWo, const __grid_constant__ CUtensorMap tmW1,
                    const __grid_constant__ CUtensorMap tmW3, const __grid_constant__ CUtensorMap tmW2,
                    const __nv_bfloat16* __restrict__ x_in, const __nv_bfloat16* __restrict__ c_in,
                    __nv_bfloat16* __restrict__ out) {
    extern __shared__ __align__(1024) uint8_t smem[];
    const uint32_t sb = smem_u32(smem);
    const int tid = threadIdx.x, wid = tid >> 5, lane = tid & 31;
    const int cta = blockIdx.x, G = gridDim.x;
    const int grp = cta % NG, rank = cta / NG;
    const uint32_t bars = sb + SM_BARS;
    auto BAR = [&](int i) { return bars + 8u * i; };
    volatile uint32_t* meta = reinterpret_cast<volatile uint32_t*>(smem + SM_META);

    uint32_t in_c0 = 0, in_x0 = 0, in_c1 = 0, in_x1 = 0, in_epoch = 0;
    {
        const bool mf = cta < 40;
        const int b0 = mf ? B_MOD : B_WQ;
        if (wid == 8) {
            if (lane == 0) {
#pragma unroll 1
                for (int i = 0; i < 4; i++) mbar_init(BAR(b0 + i), 1);
                asm volatile("fence.mbarrier_init.release.cluster;" ::: "memory");
                asm volatile("fence.proxy.async.shared::cta;" ::: "memory");
                if (cta < 128) {
                    const CUtensorMap* tm = mf ? &tmMod : &tmWq;
#pragma unroll 1
                    for (int i = 0; i < 4; i++) {
                        const uint32_t bar = BAR(b0 + i);
                        mbar_expect_tx(bar, mf ? 10240 : 12288);
                        tma2d(sb + (mf ? SM_WMOD + i * 10240 : SM_WQ + i * 12288), tm, cta * (mf ? 32 : 48), i * (mf ? 160 : 128), bar);
                    }
                }
                asm volatile("ld.relaxed.gpu.global.u32 %0, [%1];" : "=r"(in_epoch) : "l"(&g_epoch) : "memory");
            }
        } else {
            const uint32_t* cg = reinterpret_cast<const uint32_t*>(c_in);
            const uint32_t* xg = reinterpret_cast<const uint32_t*>(x_in);
            in_c0 = __ldg(cg + tid); in_x0 = __ldg(xg + tid);
            if (tid < 64) { in_c1 = __ldg(cg + 256 + tid); in_x1 = __ldg(xg + 256 + tid); }
            if (tid == 0) asm volatile("ld.relaxed.gpu.global.u32 %0, [%1];" : "=r"(in_epoch) : "l"(&g_epoch) : "memory");
            if (lane == 0) {
#pragma unroll 1
                for (int i = wid; i < B_LAST; i += 8) {
                    if (i >= b0 && i < b0 + 4) continue;
                    mbar_init(BAR(i), (i >= B_EMPTY && i < B_MOD) ? 2 : ((i >= B_FLF && i < B_FLE) ? 4 : 1));
                }
                asm volatile("fence.mbarrier_init.release.cluster;" ::: "memory");
                asm volatile("fence.proxy.async.shared::cta;" ::: "memory");
            }
        }
    }
    __syncwarp();
    __syncthreads();
    if (sb & 1023u) __trap();

    if (wid == 8) {
        if (tid == 256) {
            Window win;
            const unsigned epoch = in_epoch;
            prefetch_tm(&tmWq); prefetch_tm(&tmMod); prefetch_tm(&tmK); prefetch_tm(&tmV);
            const int nmod = cta < 120 ? 4 : 0, nwq = cta < 128 ? 5 : 0;
            win.init(BAR(B_DUMMY));
            auto pro_issue = [&](int i, bool issue, bool wait) {
                const bool is_mod = cta < 40 ? i < nmod : i >= nwq;
                const int j = cta < 40 ? (is_mod ? i : i - nmod) : (is_mod ? i - nwq : i);
                const uint32_t bar = BAR((is_mod ? B_MOD : B_WQ) + j);
                win.push(bar, 0, wait);
                if (issue) {
                    mbar_expect_tx(bar, is_mod ? 10240 : 12288);
                    if (is_mod) tma2d(sb + SM_WMOD + j * 10240, &tmMod, cta * 32, j * 160, bar);
                    else tma2d(sb + SM_WQ + j * 12288, &tmWq, cta * 48, j * 128, bar);
                }
            };
            prefetch_tm(&tmWo); prefetch_tm(&tmW1); prefetch_tm(&tmW3); prefetch_tm(&tmW2);
            unsigned* ctr = &g_ctr[epoch & 1][grp * 32];
            unsigned* gctr = &g_ctr[epoch & 1][NG * 32];
            if (cta == 0) {
                for (int g = 0; g <= NG; g++) g_ctr[(epoch + 1) & 1][g * 32] = 0;
            }
            unsigned pend = atomicAdd(ctr, 1);
#pragma unroll 1
            for (int i = 0; i < nmod + nwq; i++) pro_issue(i, i >= 4, i >= P_PRONW);
            uint64_t pol;
            asm volatile("createpolicy.fractional.L2::evict_first.b64 %0, 1.0;" : "=l"(pol));
            int s = 0; uint32_t par = 0;
            int ntiles = 0, run = -1, last_head = -1;
            bool glob = false;
#pragma unroll 1
            while (true) {
                unsigned t = pend;
                DBG(8);
                if (!glob && t >= (unsigned)GT) { glob = true; t = atomicAdd(gctr, 1); }
                if (glob && t >= (unsigned)PT) break;
                pend = atomicAdd(glob ? gctr : ctr, 1);
                ntiles++;
                const int hl = t / TPH, tile = t % TPH;
                const int head = glob ? NG * GH + hl : grp * GH + hl;
                const int qidx = glob ? GH + hl : hl;
                if (head != last_head) { last_head = head; run++; meta[16 + run] = head; }
                const int line0 = (head * SK + tile * TILE) * 3;
                const bool urgent = glob && t >= (unsigned)(PT - P_URG);
#pragma unroll 1
                for (int kv = 0; kv < 2; kv++) {
                    win.push(BAR(B_FULL + s), par, !urgent);
                    mbar_wait(BAR(B_EMPTY + s), par ^ 1);
                    meta[s] = run | (qidx << 8);
                    mbar_expect_tx(BAR(B_FULL + s), CHUNK);
                    tma2d_hint(sb + SM_RING + s * CHUNK, kv ? &tmV : &tmK, 0, line0, BAR(B_FULL + s), pol);
                    DBG(6 + kv);
                    if (++s == NSLOT) { s = 0; par ^= 1; }
                }
            }
            TS(5);
            meta[16 + run + 1] = 0xFFu;
#pragma unroll 1
            for (int e = 0; e < 2; e++) {
                mbar_wait(BAR(B_EMPTY + s), par ^ 1);
                meta[s] = (run + 1) | META_END;
                mbar_arrive(BAR(B_FULL + s));
                if (++s == NSLOT) { s = 0; par ^= 1; }
                if (++s == NSLOT) { s = 0; par ^= 1; }
            }
#pragma unroll
            for (int i = 0; i < WIN - P_HOLD; i++) mbar_wait(win.bar[i], win.par[i]);
            TS(12);
            if (cta < 128) {
                mbar_wait(BAR(B_PRO), 0);
#pragma unroll 1
                for (int i = 0; i < 5; i++) {
                    win.push_tail(BAR(B_WO + i), 0);
                    mbar_expect_tx(BAR(B_WO + i), 12288);
                    tma2d(sb + SM_WO + (2 * i) * 6144, &tmWo, (2 * i) * 64, cta * 48, BAR(B_WO + i));
                    tma2d(sb + SM_WO + (2 * i + 1) * 6144, &tmWo, (2 * i + 1) * 64, cta * 48, BAR(B_WO + i));
                }
                if (cta < 96) {
#pragma unroll 1
                    for (int i = 0; i < 4; i++) {
                        const int m = i & 1, hf = i >> 1;
                        const uint32_t bar = BAR((m ? B_W3 : B_W1) + hf);
                        const uint32_t dst = sb + (m ? SM_W3 : SM_W1) + hf * 10240;
                        const CUtensorMap* tm = m ? &tmW3 : &tmW1;
                        win.push_tail(bar, 0);
                        mbar_expect_tx(bar, 10240);
                        tma2d(dst, tm, cta * 16, hf * 320, bar);
                        tma2d(dst + 5120, tm, cta * 16, hf * 320 + 160, bar);
                    }
#pragma unroll 1
                    for (int i = 0; i < 2; i++) {
                        win.push_tail(BAR(B_W2 + i), 0);
                        mbar_wait(BAR(B_EMPTY + s), par ^ 1);
                        meta[10 + i] = s;
                        mbar_expect_tx(BAR(B_W2 + i), 10240);
#pragma unroll 1
                        for (int b = 0; b < 5; b++)
                            tma2d(sb + SM_RING + s * CHUNK + b * 2048, &tmW2, (5 * i + b) * 64, cta * 16, BAR(B_W2 + i));
                        if (++s == NSLOT) { s = 0; par ^= 1; }
                    }
                }
            }
            TS(6);
        }
    } else {
    const int g4 = lane >> 2, j4 = lane & 3, mi = lane >> 3, l8 = lane & 7;
    uint32_t* sc32 = reinterpret_cast<uint32_t*>(smem + SM_SC);
    uint32_t* h32 = reinterpret_cast<uint32_t*>(smem + SM_H);
    uint32_t* x32 = reinterpret_cast<uint32_t*>(smem + SM_X);
    uint32_t* q32 = reinterpret_cast<uint32_t*>(smem + SM_Q);
    float* red = reinterpret_cast<float*>(smem + SM_RED);
    float* stage = reinterpret_cast<float*>(smem + SM_STAGE);
    float* own = reinterpret_cast<float*>(smem + SM_OWN);

    uint32_t tag;
    bool live = true;
    {
    {
        const uint32_t c0 = in_c0, x0 = in_x0, c1 = in_c1, x1 = in_x1, epoch = in_epoch;
        if (cta < 120 && tid >= 128 && tid < 136) st_zero16(reinterpret_cast<uint4*>(&g_mod[cta * 16]) + (tid - 128));
        if (cta < 128 && tid >= 32 && tid < 44) st_zero16(reinterpret_cast<uint4*>(&g_q[cta * 24]) + (tid - 32));
        sc32[tid] = pack_bf(silu(bf_lo(c0)), silu(bf_hi(c0))); x32[tid] = x0;
        if (tid < 64) { sc32[256 + tid] = pack_bf(silu(bf_lo(c1)), silu(bf_hi(c1))); x32[256 + tid] = x1; }
        if (tid == 0) meta[8] = epoch + 1;
    }
    bar_cons();
    tag = meta[8];
    if (wid == 0) EARLY(3);
    float mean_x = 0.f, rden_x = 1.f;
    if (cta < 128) {
        float xv[20];
#pragma unroll
        for (int i = 0; i < 10; i++) { uint32_t v = x32[lane + 32 * i]; xv[2 * i] = bf_lo(v); xv[2 * i + 1] = bf_hi(v); }
        float den;
        ln_stats(xv, mean_x, den);
        rden_x = __fdividef(1.0f, den);
    }

#pragma unroll 1
    for (int step = 0; step < 2; step++) {
    if (wid >= 4 && (step == 0 ? cta < 40 : (cta >= 40 && cta < 120))) {
        const int w4 = wid - 4;
        float acc[2][4] = {};
        const uint32_t base = sb + SM_WMOD + w4 * 10240;
        mbar_wait(BAR(B_MOD + w4), 0);
        EARLY(4 + w4);
#pragma unroll
        for (int hf = 0; hf < 2; hf++) {
            uint32_t a[5][2][4], bb[5][2];
#pragma unroll
            for (int ks = 0; ks < 5; ks++) {
                const int r0 = w4 * 160 + hf * 80 + ks * 16;
                bb[ks][0] = sc32[(r0 >> 1) + j4]; bb[ks][1] = sc32[(r0 >> 1) + 4 + j4];
                const int r = hf * 80 + ks * 16 + l8 + 8 * (mi >> 1);
#pragma unroll
                for (int mt = 0; mt < 2; mt++) ldsm4t(a[ks][mt], base + r * 64 + (((2 * mt + (mi & 1)) ^ ((r >> 1) & 3)) << 4));
            }
#pragma unroll
            for (int ks = 0; ks < 5; ks++) { mma16816(acc[0], a[ks][0], bb[ks][0], bb[ks][1]); mma16816(acc[1], a[ks][1], bb[ks][0], bb[ks][1]); }
        }
        float* red2 = reinterpret_cast<float*>(smem + SM_FIN);
        if (j4 == 0) {
#pragma unroll
            for (int mt = 0; mt < 2; mt++) { red2[w4 * 32 + mt * 16 + g4] = acc[mt][0]; red2[w4 * 32 + mt * 16 + 8 + g4] = acc[mt][2]; }
        }
        asm volatile("bar.sync 3, 128;" ::: "memory");
        if (wid == 4) EARLY(8);
        if (wid == 4) {
            float v = (red2[lane] + red2[32 + lane]) + (red2[64 + lane] + red2[96 + lane]);
            float o = __shfl_down_sync(0xffffffffu, v, 1);
            if (!(lane & 1)) st_pk8(&g_mod[cta * 16 + (lane >> 1)], pack_bf(v, o), tag);
            if (step == 1 && lane == 0) mbar_arrive(BAR(B_PRO));
        }
        TS(1);
    }
    if (step == 1) break;
    if (cta < 128) {
        {
            const int off[4] = {tid, 320 + tid, tid < 64 ? 256 + tid : tid, tid < 64 ? 576 + tid : 320 + tid};
            uint32_t val[4];
            poll8<4>(g_mod, off, val, tag);
#pragma unroll
            for (int rep = 0; rep < 2; rep++) {
                int p = tid + rep * 256;
                if (p < 320) {
                    uint32_t sa = val[2 * rep], ca = val[2 * rep + 1];
                    uint32_t xx = x32[p];
                    float n0 = bfr(bfr(bf_lo(xx) - mean_x) * rden_x), n1 = bfr(bfr(bf_hi(xx) - mean_x) * rden_x);
                    float h0 = bfr(n0 * bfr(1.0f + bf_lo(ca))) + bf_lo(sa);
                    float h1 = bfr(n1 * bfr(1.0f + bf_hi(ca))) + bf_hi(sa);
                    h32[p] = pack_bf(h0, h1);
                }
            }
        }
        bar_cons();
        TS(2);
        float acc[3][4] = {};
        uint32_t a[5][3][4], bb[5][2];
#pragma unroll
        for (int ks = 0; ks < 5; ks++) {
            const int r0 = wid * 80 + ks * 16;
            bb[ks][0] = h32[(r0 >> 1) + j4]; bb[ks][1] = h32[(r0 >> 1) + 4 + j4];
        }
        mbar_wait(BAR(B_WQ + ((wid * 80) >> 7)), 0);
        mbar_wait(BAR(B_WQ + ((wid * 80 + 79) >> 7)), 0);
        if (wid == 0) EARLY(9);
        if (wid == 7) EARLY(10);
#pragma unroll
        for (int ks = 0; ks < 5; ks++) {
            const int r = wid * 80 + ks * 16 + l8 + 8 * (mi >> 1);
#pragma unroll
            for (int mt = 0; mt < 3; mt++) ldsm4t(a[ks][mt], sb + SM_WQ + r * 96 + ((2 * mt + (mi & 1)) << 4));
        }
#pragma unroll
        for (int ks = 0; ks < 5; ks++) {
#pragma unroll
            for (int mt = 0; mt < 3; mt++) mma16816(acc[mt], a[ks][mt], bb[ks][0], bb[ks][1]);
        }
        if (j4 == 0) {
#pragma unroll
            for (int mt = 0; mt < 3; mt++) { red[wid * 64 + mt * 16 + g4] = acc[mt][0]; red[wid * 64 + mt * 16 + 8 + g4] = acc[mt][2]; }
        }
        bar_cons();
        if (tid < 64) {
            float v = 0.f;
            if (tid < 48) {
#pragma unroll
                for (int w = 0; w < 8; w++) v += red[w * 64 + tid];
            }
            float o = __shfl_down_sync(0xffffffffu, v, 1);
            if (tid < 48 && !(tid & 1)) st_pk8(&g_q[cta * 24 + (tid >> 1)], pack_bf(v, o), tag);
        }
        TS(3);
    }
    {
        int off[5];
#pragma unroll
        for (int j = 0; j < 5; j++) {
            int p = tid + 256 * j;
            if (p >= NQH * 96) p = tid;
            off[j] = p < GH * 96 ? grp * GH * 96 + p : NG * GH * 96 + (p - GH * 96);
        }
        uint32_t val[5];
        poll8<5>(g_q, off, val, tag);
#pragma unroll
        for (int j = 0; j < 5; j++)
            if (tid + 256 * j < NQH * 96) q32[tid + 256 * j] = val[j];
    }
    bar_cons();
    if (tid == 0 && !(cta >= 40 && cta < 120)) mbar_arrive(BAR(B_PRO));
    TS(4);
    }

    if (wid < 4) {
        const int pair = wid >> 1, half = wid & 1;
        uint32_t offK[3], offV[3];
        {
            const int rowK = half * 16 + l8 + 8 * (mi & 1), hiK = mi >> 1;
            const int rowV = half * 16 + l8 + 8 * (mi >> 1), hiV = mi & 1;
#pragma unroll
            for (int t = 0; t < 3; t++) {
                offK[t] = (rowK * 3 + t) * 128 + ((hiK ^ ((rowK * 3 + t) & 7)) << 4);
                offV[t] = (rowV * 3 + t) * 128 + ((hiV ^ ((rowV * 3 + t) & 7)) << 4);
                asm volatile("" : "+r"(offK[t]), "+r"(offV[t]));
            }
        }
        float acc[12][4];
#pragma unroll
        for (int i = 0; i < 12; i++) { acc[i][0] = acc[i][1] = acc[i][2] = acc[i][3] = 0.f; }
        float m_run = NEG_BIG, l_run = 0.f;
        uint32_t qf[12][2];
#pragma unroll
        for (int i = 0; i < 12; i++) { qf[i][0] = qf[i][1] = 0; }
        int cur = -1, flushed = 0, cnt = 0;
        int s = 2 * pair; uint32_t par = 0;
        int fb = 0; uint32_t fpar = 1;
        uint32_t ready = 0;
#pragma unroll 1
        while (true) {
            if (!ready) mbar_wait(BAR(B_FULL + s), par);
            const uint32_t mt_ = meta[s];
            const int run = mt_ & 0xff;
            if (mt_ & META_END) CLK(20);
            if ((mt_ & META_END) && half == 0) DBG(4 + pair);
            if (run != cur) {
#pragma unroll 1
                while (flushed < run) {
                    const uint32_t fle = mbar_try(BAR(B_FLE + fb), fpar);
                    float* mb = reinterpret_cast<float*>(smem + SM_MERGE) + (fb * 4 + wid) * 200;
                    if (flushed != cur) {
#pragma unroll
                        for (int i = 0; i < 12; i++) { acc[i][0] = acc[i][2] = 0.f; }
                        m_run = NEG_BIG; l_run = 0.f; cnt = 0;
                    }
                    float l = l_run;
                    l += __shfl_xor_sync(0xffffffffu, l, 4);
                    l += __shfl_xor_sync(0xffffffffu, l, 8);
                    l += __shfl_xor_sync(0xffffffffu, l, 16);
                    if (!fle) mbar_wait(BAR(B_FLE + fb), fpar);
                    if (j4 == 0) {
#pragma unroll
                        for (int i = 0; i < 12; i++) { mb[4 + 16 * i + g4] = acc[i][0]; mb[4 + 16 * i + 8 + g4] = acc[i][2]; }
                    }
                    if (lane == 0) { mb[0] = m_run; mb[1] = l; mb[2] = __int_as_float(cnt); }
                    __syncwarp();
                    if (lane == 0) mbar_arrive(BAR(B_FLF + fb));
                    if (++fb == NBUF) { fb = 0; fpar ^= 1; }
                    flushed++;
                    cur = -1;
                }
                if (mt_ & META_END) {
                    CLK(21);
                    if (flushed == 0 && lane == 0) mbar_arrive(BAR(B_FLF));
                    break;
                }
                cur = run;
                const int qi = (mt_ >> 8) & 0xff;
#pragma unroll
                for (int i = 0; i < 12; i++) { acc[i][0] = acc[i][1] = acc[i][2] = acc[i][3] = 0.f; }
                m_run = NEG_BIG; l_run = 0.f; cnt = 0;
#pragma unroll
                for (int ks = 0; ks < 12; ks++) {
                    qf[ks][0] = q32[qi * 96 + ks * 8 + j4];
                    qf[ks][1] = q32[qi * 96 + ks * 8 + 4 + j4];
                }
            }
            cnt++;
            if (half == 0) DBG(pair);
            const uint32_t kb = sb + SM_RING + s * CHUNK;
            int sv = s + 1; uint32_t parv = par;
            if (sv == NSLOT) { sv = 0; parv ^= 1; }
            float sc[6][4] = {};
            uint32_t vready;
            {
                uint32_t a[12][4];
#pragma unroll
                for (int t = 0; t < 3; t++) {
                    const uint32_t bt = kb + offK[t];
#pragma unroll
                    for (int kk = 0; kk < 4; kk++) ldsm4(a[t * 4 + kk], bt ^ (kk << 5));
                }
                vready = mbar_try(BAR(B_FULL + sv), parv);
#pragma unroll
                for (int i = 0; i < 12; i++) mma16816(sc[i % 6], a[i], qf[i][0], qf[i][1]);
            }
            __syncwarp();
            if (lane == 0) mbar_arrive(BAR(B_EMPTY + s));
            const float scale = 0.07216878364870322f;
            float s0 = bfr(bfr(((sc[0][0] + sc[1][0]) + (sc[2][0] + sc[3][0])) + (sc[4][0] + sc[5][0])) * scale);
            float s1 = bfr(bfr(((sc[0][2] + sc[1][2]) + (sc[2][2] + sc[3][2])) + (sc[4][2] + sc[5][2])) * scale);
            float tm = fmaxf(s0, s1);
            tm = fmaxf(tm, __shfl_xor_sync(0xffffffffu, tm, 4));
            tm = fmaxf(tm, __shfl_xor_sync(0xffffffffu, tm, 8));
            tm = fmaxf(tm, __shfl_xor_sync(0xffffffffu, tm, 16));
            if (tm > m_run) {
                float alpha = ex2((m_run - tm) * LOG2E);
                l_run *= alpha;
#pragma unroll
                for (int i = 0; i < 12; i++) { acc[i][0] *= alpha; acc[i][1] *= alpha; acc[i][2] *= alpha; acc[i][3] *= alpha; }
                m_run = tm;
            }
            float p0 = ex2((s0 - m_run) * LOG2E);
            float p1 = ex2((s1 - m_run) * LOG2E);
            l_run += p0 + p1;
            const uint32_t pw = pack_bf(p0, p1);
            const uint32_t pa = __shfl_sync(0xffffffffu, pw, 8 * j4), pb = __shfl_sync(0xffffffffu, pw, 8 * j4 + 4);
            const uint32_t b0 = __byte_perm(pa, pb, 0x5410), b1 = __byte_perm(pa, pb, 0x7632);
            if (!vready) mbar_wait(BAR(B_FULL + sv), parv);
            s += 4;
            if (s >= NSLOT) { s -= NSLOT; par ^= 1; }
            if (half == 0) DBG(2 + pair);
            ready = mbar_try(BAR(B_FULL + s), par);
            const uint32_t vb = sb + SM_RING + sv * CHUNK;
            {
                uint32_t a[12][4];
#pragma unroll
                for (int t = 0; t < 3; t++) {
                    const uint32_t bt = vb + offV[t];
#pragma unroll
                    for (int kk = 0; kk < 4; kk++) ldsm4t(a[t * 4 + kk], bt ^ (kk << 5));
                }
#pragma unroll
                for (int i = 0; i < 12; i++) mma16816(acc[i], a[i], b0, b1);
            }
            __syncwarp();
            if (lane == 0) mbar_arrive(BAR(B_EMPTY + sv));
        }
        TS(7);
        CLK(18);
    } else if (wid == 4) {
        int fb = 0; uint32_t fpar = 0;
        mbar_wait(BAR(B_CLR), 0);
#pragma unroll 1
        for (int f = 0;; f++) {
            const float* mb = reinterpret_cast<const float*>(smem + SM_MERGE) + fb * 800;
            mbar_wait(BAR(B_FLF + fb), fpar);
            const int head = (int)meta[16 + f];
            if (head == 0xFF) break;
            float m0 = mb[0], m1 = mb[200], m2 = mb[400], m3 = mb[600];
            float M = fmaxf(fmaxf(m0, m1), fmaxf(m2, m3));
            float w0 = ex2((m0 - M) * LOG2E), w1 = ex2((m1 - M) * LOG2E);
            float w2 = ex2((m2 - M) * LOG2E), w3 = ex2((m3 - M) * LOG2E);
            const int idx = head < NG * GH ? rank : cta;
            uint4* dst = &g_dat[head][idx][0];
            float o[6];
#pragma unroll
            for (int i = 0; i < 6; i++) {
                int d = 4 + (i < 3 ? 3 * lane + i : 96 + 3 * lane + (i - 3));
                o[i] = w0 * mb[d] + w1 * mb[200 + d] + w2 * mb[400 + d] + w3 * mb[600 + d];
            }
            float L = w0 * mb[1] + w1 * mb[201] + w2 * mb[401] + w3 * mb[601];
            const uint32_t tiles = __float_as_int(mb[2]) + __float_as_int(mb[402]);
            st_pk16(dst + lane, __float_as_uint(o[0]), __float_as_uint(o[1]), __float_as_uint(o[2]), tag);
            st_pk16(dst + 32 + lane, __float_as_uint(o[3]), __float_as_uint(o[4]), __float_as_uint(o[5]), tag);
            if (lane == 0) st_pk16(&g_hdr[head][idx], __float_as_uint(M), __float_as_uint(L), tiles, tag);
            __syncwarp();
            if (lane == 0) mbar_arrive(BAR(B_FLE + fb));
            if (++fb == NBUF) { fb = 0; fpar ^= 1; }
            if (meta[16 + f + 1] == 0xFFu) break;
        }
        TS(8);
        CLK(18);
    } else if (wid == 5) {
        if (cta < 128) {
            if (lane < 2) st_zero16(&g_x2[cta][lane]);
#pragma unroll 1
            for (int i = lane; i < 256; i += 32) {
                st_zero16(&g_h1[i >> 1][cta][i & 1]);
                if (cta < 96) st_zero16(&g_h3[i >> 1][cta][i & 1]);
            }
        }
#pragma unroll 1
        for (int f = 0; f < NQH; f++) {
            const int head = f < GH ? grp * GH + f : NG * GH + (f - GH);
            const int idx = f < GH ? rank : cta;
            st_zero16(&g_dat[head][idx][lane]);
            st_zero16(&g_dat[head][idx][32 + lane]);
            if (lane == 0) st_zero16(&g_hdr[head][idx]);
        }
        __syncwarp();
        if (lane == 0) mbar_arrive(BAR(B_CLR));
    } else {
        if (cta < 128) {
            const int t = tid - 192;
            uint32_t* cb32 = reinterpret_cast<uint32_t*>(smem + SM_CB);
            uint32_t* sb32 = reinterpret_cast<uint32_t*>(smem + SM_SB);
            const int col = cta * 5 + t;
            int off[12];
            uint32_t val[12];
#pragma unroll
            for (int rep = 0; rep < 5; rep++) { off[2 * rep] = 960 + t + 64 * rep; off[2 * rep + 1] = 1280 + t + 64 * rep; }
            off[10] = t < 5 ? (1280 + col) >> 1 : 960;
            off[11] = t < 5 ? (3200 + col) >> 1 : 960;
            poll8<12>(g_mod, off, val, tag);
#pragma unroll
            for (int rep = 0; rep < 5; rep++) {
                sb32[t + 64 * rep] = val[2 * rep];
                cb32[t + 64 * rep] = pack_bf(1.0f + bf_lo(val[2 * rep + 1]), 1.0f + bf_hi(val[2 * rep + 1]));
            }
            if (t < 5) {
                own[t] = (col & 1) ? bf_hi(val[10]) : bf_lo(val[10]);
                own[8 + t] = (col & 1) ? bf_hi(val[11]) : bf_lo(val[11]);
                uint32_t xx = x32[col >> 1];
                own[16 + t] = (col & 1) ? bf_hi(xx) : bf_lo(xx);
            }
        }
        live = false;
    }
    }
    const uint32_t sb0 = sb;
    const int tid0 = tid;
#pragma unroll 1
    while (cta < 128) {
        uint32_t sb = sb0; int tid = tid0;
        asm volatile("" : "+r"(sb), "+r"(tid));
        const int wid = tid >> 5, lane = tid & 31;
        const int g4 = lane >> 2, j4 = lane & 3, mi = lane >> 3, l8 = lane & 7;
        CLK(19);
        if (wid >= 5) {
            const int h = cta >> 2, js = cta & 3;
            const bool gl = h >= NG * GH;
            const int ncand = gl ? G : (G - h / GH + NG - 1) / NG;
            const int k = lane & 15, rr = (wid - 5) * 2 + (lane >> 4);
            if (live) {
                const unsigned* cp = &g_ctr[(tag - 1) & 1][(gl ? NG : h / GH) * 32];
                const unsigned thr = ((gl ? h - NG * GH : h % GH) + 1) * TPH;
                uint32_t it = 0;
                while (true) {
                    unsigned v;
                    asm volatile("ld.relaxed.gpu.global.u32 %0, [%1];" : "=r"(v) : "l"(cp) : "memory");
                    if (v >= thr) break;
                    __nanosleep(300);
                    if (++it > SPIN_LIMIT) __trap();
                }
            }
            const uint4* hdr = &g_hdr[h][lane];
            const uint4* dat = &g_dat[h][rr][16 * js + k];
            float* part = stage;
            float L, a0, a1, a2;
            uint32_t it = 0;
            uint4 hd[5], dv[MAXG / 6];
#pragma unroll
            for (int i = 0; i < 5; i++) hd[i] = make_uint4(0, 0, 0, 0);
#pragma unroll
            for (int i = 0; i < MAXG / 6; i++) dv[i] = make_uint4(0, 0, 0, 0);
#pragma unroll 1
            while (true) {
                FreshN<5, 32>::run(hd, hdr, tag, live, lane, 32, ncand);
                FreshN<MAXG / 6, 6 * 64>::run(dv, dat, tag, live, rr, 6, ncand);
                float w[5], M = NEG_BIG;
                int c = 0;
#pragma unroll
                for (int i = 0; i < 5; i++) {
                    const bool v = hd[i].w == tag;
                    w[i] = v ? __uint_as_float(hd[i].x) : NEG_BIG;
                    M = fmaxf(M, w[i]);
                    c += v ? (int)hd[i].z : 0;
                }
                c = __reduce_add_sync(0xffffffffu, c);
                if (++it > SPIN_LIMIT) __trap();
                if (live && c != TPH) continue;
                CLK(1);
#pragma unroll
                for (int o = 16; o > 0; o >>= 1) M = fmaxf(M, __shfl_xor_sync(0xffffffffu, M, o));
                float ls = 0.f;
#pragma unroll
                for (int i = 0; i < 5; i++) {
                    const bool v = w[i] != NEG_BIG;
                    const float e = ex2((w[i] - M) * LOG2E);
                    w[i] = v ? e : -0.0f;
                    ls = fmaf(w[i], __uint_as_float(hd[i].y), ls);
                }
                float* wsm = reinterpret_cast<float*>(smem + SM_X2) + (wid - 5) * 160;
                if (live) {
#pragma unroll
                    for (int i = 0; i < 5; i++) wsm[lane + 32 * i] = w[i];
                }
                __syncwarp();
                uint32_t badm = 0;
                a0 = a1 = a2 = 0.f;
#pragma unroll
                for (int i = 0; i < MAXG / 6; i++) {
                    const float wi = wsm[rr + 6 * i];
                    badm |= (dv[i].w ^ tag) & ~(uint32_t)(__float_as_int(wi) >> 31);
                    a0 = fmaf(wi, __uint_as_float(dv[i].x), a0);
                    a1 = fmaf(wi, __uint_as_float(dv[i].y), a1);
                    a2 = fmaf(wi, __uint_as_float(dv[i].z), a2);
                }
                const bool bad = badm != 0;
                __syncwarp();
                L = warp_sum(ls);
                if (!__any_sync(0xffffffffu, bad) || !live) break;
            }
            a0 += __shfl_xor_sync(0xffffffffu, a0, 16);
            a1 += __shfl_xor_sync(0xffffffffu, a1, 16);
            a2 += __shfl_xor_sync(0xffffffffu, a2, 16);
            CLK(2);
            if (live && lane < 16) { float* pp = part + (wid - 5) * 48 + 3 * k; pp[0] = a0; pp[1] = a1; pp[2] = a2; }
            if (live) asm volatile("bar.sync 2, 96;" ::: "memory");
            if (wid == 5 || !live) {
                uint16_t* osw = reinterpret_cast<uint16_t*>(smem + SM_SC);
                const float inv = __fdividef(1.0f, L);
                const float o0 = (part[lane] + part[48 + lane]) + part[96 + lane];
                const float o1 = (part[32 + (lane & 15)] + part[80 + (lane & 15)]) + part[128 + (lane & 15)];
                if (live) { osw[lane] = (uint16_t)(__float_as_uint(bfr(o0 * inv)) >> 16); if (lane < 16) osw[32 + lane] = (uint16_t)(__float_as_uint(bfr(o1 * inv)) >> 16); }
            }
            if (live) TS(10);
        }
        if (wid < 5 || !live) {
            const int w5 = wid < 5 ? wid : wid - 5;
            uint32_t wa[8][3][4];
            if (live) mbar_wait(BAR(B_WO + w5), 0);
#pragma unroll
            for (int i = 0; i < 8; i++) {
                const int cc = 2 * (i & 3) + (mi & 1);
#pragma unroll
                for (int ks = 0; ks < 3; ks++) {
                    const int r = ks * 16 + l8 + 8 * (mi >> 1);
                    ldsm4t(wa[i][ks], sb + SM_WO + (2 * w5 + (i >> 2)) * 6144 + r * 128 + ((cc ^ (r & 7)) << 4));
                }
            }
            if (live) bar_cons();
            if (live) TS(9);
            CLK(3);
            const uint32_t* os32 = reinterpret_cast<const uint32_t*>(smem + SM_SC);
            float acc[8][4] = {};
#pragma unroll
            for (int ks = 0; ks < 3; ks++) {
                const uint32_t b0 = os32[ks * 8 + j4], b1 = os32[ks * 8 + 4 + j4];
#pragma unroll
                for (int i = 0; i < 8; i++) mma16816(acc[i], wa[i][ks], b0, b1);
            }
            if (live && j4 == 0) {
#pragma unroll
                for (int i = 0; i < 8; i++) { stage[(w5 * 8 + i) * 16 + g4] = acc[i][0]; stage[(w5 * 8 + i) * 16 + 8 + g4] = acc[i][2]; }
            }
        } else {
            bar_cons();
        }
        CLK(4);
        if (live) bar_cons();
        {
            const int o = tid >> 1, kk = tid & 1;
            const float* sp = stage + o * 5 + kk * 3;
            float v0 = sp[0], v1 = sp[1], v2 = kk ? 0.f : sp[2];
            if (live) st_pk16(&g_h1[o][cta][kk], __float_as_uint(v0), __float_as_uint(v1), __float_as_uint(v2), tag);
        }
        if (live) TS(11);
        CLK(5);
        if (wid == 0 || !live) {
            const uint4* p = &g_h1[cta][0][0] + lane;
            uint4 v[8];
            uint32_t it = 0;
            while (true) {
                bool ok = true;
                LoadN<8, 32>::run(v, p, live, 0, 0, 1);
#pragma unroll
                for (int j = 0; j < 8; j++) ok = ok && v[j].w == tag;
                if (__all_sync(0xffffffffu, ok) || !live) break;
                if (++it > SPIN_LIMIT) __trap();
            }
            CLK(6);
            float a0 = 0.f, a1 = 0.f, a2 = 0.f;
#pragma unroll
            for (int j = 0; j < 8; j++) { a0 += __uint_as_float(v[j].x); a1 += __uint_as_float(v[j].y); a2 += __uint_as_float(v[j].z); }
#pragma unroll
            for (int o = 2; o <= 16; o <<= 1) {
                a0 += __shfl_xor_sync(0xffffffffu, a0, o);
                a1 += __shfl_xor_sync(0xffffffffu, a1, o);
                a2 += __shfl_xor_sync(0xffffffffu, a2, o);
            }
            const float gx = own[lane & 7], xx = own[16 + (lane & 7)];
            const float t0 = __shfl_sync(0xffffffffu, a0, lane >= 3), t1 = __shfl_sync(0xffffffffu, a1, lane >= 3);
            const float sum = (lane == 0 || lane == 3) ? t0 : (lane == 2 ? a2 : t1);
            const float x2 = bfr(xx + bfr(gx * bfr(sum)));
            if (live && lane < 5) own[24 + lane] = x2;
            const float y1 = __shfl_sync(0xffffffffu, x2, 1), y2 = __shfl_sync(0xffffffffu, x2, 2);
            const float y3 = __shfl_sync(0xffffffffu, x2, 3), y4 = __shfl_sync(0xffffffffu, x2, 4);
            if (live && lane == 0) st_pk16(&g_x2[cta][0], pack_bf(x2, y1), pack_bf(y2, y3), pack_bf(y4, 0.f), tag);
            if (live) TS(13);
        }
        CLK(8);
        if (cta < 96) {
            uint32_t a1[5][4], a3[5][4], a2[5][4];
            if (live) mbar_wait3(BAR(B_W1 + (wid >> 2)), BAR(B_W3 + (wid >> 2)), BAR(B_W2 + (wid >> 2)));
            const uint32_t w2b = sb + SM_RING + meta[10 + (wid >> 2)] % NSLOT * CHUNK;
#pragma unroll
            for (int ks = 0; ks < 5; ks++) {
                const int r = wid * 80 + ks * 16 + l8 + 8 * (mi >> 1);
                const uint32_t off = r * 32 + (((mi & 1) ^ ((r >> 2) & 1)) << 4);
                ldsm4t(a1[ks], sb + SM_W1 + off);
                ldsm4t(a3[ks], sb + SM_W3 + off);
            }
#pragma unroll
            for (int i = 0; i < 5; i++) {
                const int mt = (wid & 3) * 5 + i;
                const int cc = 2 * (mt & 3) + (mi & 1);
                const int r = l8 + 8 * (mi >> 1);
                ldsm4t(a2[i], w2b + (mt >> 2) * 2048 + r * 128 + ((cc ^ (r & 7)) << 4));
            }
            CLK(9);
            float* x2s = reinterpret_cast<float*>(smem + SM_X2);
            float* st8 = red + 256;
            if (wid >= 4) {
                uint4 v = poll16(&g_x2[tid - 128][0], tag, live);
                const float e0 = bf_lo(v.x), e1 = bf_hi(v.x), e2 = bf_lo(v.y), e3 = bf_hi(v.y), e4 = bf_lo(v.z);
                float* d = x2s + (tid - 128) * 5;
                if (live) { d[0] = e0; d[1] = e1; d[2] = e2; d[3] = e3; d[4] = e4; }
                const float pv = __shfl_sync(0xffffffffu, e0, 0);
                const float d0 = e0 - pv, d1 = e1 - pv, d2 = e2 - pv, d3 = e3 - pv, d4 = e4 - pv;
                float s1 = ((d0 + d1) + (d2 + d3)) + d4;
                float s2 = fmaf(d0, d0, fmaf(d1, d1, fmaf(d2, d2, fmaf(d3, d3, d4 * d4))));
#pragma unroll
                for (int o = 16; o > 0; o >>= 1) { s1 += __shfl_xor_sync(0xffffffffu, s1, o); s2 += __shfl_xor_sync(0xffffffffu, s2, o); }
                if (live && lane == 0) { st8[2 * (wid - 4)] = pv + s1 * (1.0f / 160.0f); st8[2 * (wid - 4) + 1] = s2 - s1 * s1 * (1.0f / 160.0f); }
            }
            if (live) bar_cons();
            if (live) TS(14);
            CLK(10);
            const float4 sA = *reinterpret_cast<const float4*>(st8), sB = *reinterpret_cast<const float4*>(st8 + 4);
            const float mean = ((sA.x + sA.z) + (sB.x + sB.z)) * 0.25f;
            const float u0 = sA.x - mean, u1 = sA.z - mean, u2 = sB.x - mean, u3 = sB.z - mean;
            const float m2 = ((sA.y + sA.w) + (sB.y + sB.w)) + 160.0f * ((u0 * u0 + u1 * u1) + (u2 * u2 + u3 * u3));
            const float mean_b = bfr(mean);
            const float rden = __fdividef(1.0f, bfr(fsqrt(bfr(bfr(m2 * (1.0f / 640.0f)) + 1e-5f))));
            const uint32_t* cb32 = reinterpret_cast<const uint32_t*>(smem + SM_CB);
            const uint32_t* sb32 = reinterpret_cast<const uint32_t*>(smem + SM_SB);
#pragma unroll
            for (int rep = 0; rep < 2; rep++) {
                const int p = lane + 32 * rep;
                if (p < 40) {
                    int pp = wid * 40 + p;
                    const float2 xv = *reinterpret_cast<const float2*>(x2s + 2 * pp);
                    uint32_t cv = cb32[pp], sv = sb32[pp];
                    float n0 = bfr(bfr(xv.x - mean_b) * rden), n1 = bfr(bfr(xv.y - mean_b) * rden);
                    uint32_t hv = pack_bf(bfr(n0 * bf_lo(cv)) + bf_lo(sv), bfr(n1 * bf_hi(cv)) + bf_hi(sv));
                    if (live) h32[pp] = hv;
                }
            }
            __syncwarp();
            CLK(11);
            float ag[2][4] = {}, au[2][4] = {};
#pragma unroll
            for (int ks = 0; ks < 5; ks++) {
                const int r0 = wid * 80 + ks * 16;
                const uint32_t b0 = h32[(r0 >> 1) + j4], b1 = h32[(r0 >> 1) + 4 + j4];
                mma16816(ag[ks & 1], a1[ks], b0, b1);
                mma16816(au[ks & 1], a3[ks], b0, b1);
            }
            if (live && j4 == 0) {
                red[wid * 32 + g4] = ag[0][0] + ag[1][0]; red[wid * 32 + 8 + g4] = ag[0][2] + ag[1][2];
                red[wid * 32 + 16 + g4] = au[0][0] + au[1][0]; red[wid * 32 + 24 + g4] = au[0][2] + au[1][2];
            }
            CLK(12);
            if (live) bar_cons();
            if (live) TS(15);
            CLK(13);
            float v = 0.f;
#pragma unroll
            for (int w = 0; w < 8; w++) v += red[w * 32 + lane];
            v = bfr(v);
            float up = __shfl_down_sync(0xffffffffu, v, 16);
            float hact = bfr(bfr(silu(v)) * up);
            float e0 = __shfl_sync(0xffffffffu, hact, 2 * j4), e1 = __shfl_sync(0xffffffffu, hact, 2 * j4 + 1);
            float e2 = __shfl_sync(0xffffffffu, hact, 2 * j4 + 8), e3 = __shfl_sync(0xffffffffu, hact, 2 * j4 + 9);
            const uint32_t b0 = pack_bf(e0, e1), b1 = pack_bf(e2, e3);
            float acc[5][4] = {};
#pragma unroll
            for (int i = 0; i < 5; i++) mma16816(acc[i], a2[i], b0, b1);
            if (live && j4 == 0) {
#pragma unroll
                for (int i = 0; i < 5; i++) { stage[(wid * 5 + i) * 16 + g4] = acc[i][0]; stage[(wid * 5 + i) * 16 + 8 + g4] = acc[i][2]; }
            }
            CLK(14);
            if (live) bar_cons();
            const int o = tid >> 1, k = tid & 1;
            const float* sp = stage + o * 5 + k * 3;
            float v0 = sp[0], v1 = sp[1], v2 = k ? 0.f : sp[2];
            if (live) st_pk16(&g_h3[o][cta][k], __float_as_uint(v0), __float_as_uint(v1), __float_as_uint(v2), tag);
        }
        if (live) TS(16);
        CLK(15);
        if (wid == 0 || !live) {
            const uint4* p = &g_h3[cta][0][0] + lane;
            uint4 v[6];
            uint32_t it = 0;
            if (live && cta < 96) spin(P_DLY);
            while (true) {
                bool ok = true;
                LoadN<6, 32>::run(v, p, live, 0, 0, 1);
#pragma unroll
                for (int j = 0; j < 6; j++) ok = ok && v[j].w == tag;
                if (__all_sync(0xffffffffu, ok) || !live) break;
                if (++it > SPIN_LIMIT) __trap();
            }
            CLK(16);
            float a0 = 0.f, a1 = 0.f, a2 = 0.f;
#pragma unroll
            for (int j = 0; j < 6; j++) { a0 += __uint_as_float(v[j].x); a1 += __uint_as_float(v[j].y); a2 += __uint_as_float(v[j].z); }
#pragma unroll
            for (int o = 2; o <= 16; o <<= 1) {
                a0 += __shfl_xor_sync(0xffffffffu, a0, o);
                a1 += __shfl_xor_sync(0xffffffffu, a1, o);
                a2 += __shfl_xor_sync(0xffffffffu, a2, o);
            }
            const float gx = own[8 + (lane & 7)], xx = own[24 + (lane & 7)];
            const float t0 = __shfl_sync(0xffffffffu, a0, lane >= 3), t1 = __shfl_sync(0xffffffffu, a1, lane >= 3);
            const float sum = (lane == 0 || lane == 3) ? t0 : (lane == 2 ? a2 : t1);
            const float y = xx + bfr(gx * bfr(sum));
            if (live && lane < 5) reinterpret_cast<uint16_t*>(out)[cta * 5 + lane] = (uint16_t)(__float_as_uint(bfr(y)) >> 16);
            if (live && cta == 0 && lane == 0) g_epoch = tag;
        }
        CLK(17);
        if (live) { TS(18); break; }
        live = true;
    }
    }
}

typedef CUresult (*EncodeFn)(CUtensorMap*, CUtensorMapDataType, cuuint32_t, void*, const cuuint64_t*, const cuuint64_t*,
                             const cuuint32_t*, const cuuint32_t*, CUtensorMapInterleave, CUtensorMapSwizzle,
                             CUtensorMapL2promotion, CUtensorMapFloatOOBfill);

void make_map(EncodeFn enc, CUtensorMap* tm, const void* ptr, uint64_t cols, uint64_t rows, uint32_t box_c, uint32_t box_r,
              CUtensorMapSwizzle sw, CUtensorMapL2promotion prom) {
    cuuint64_t dims[2] = {cols, rows};
    cuuint64_t strides[1] = {cols * 2};
    cuuint32_t box[2] = {box_c, box_r};
    cuuint32_t es[2] = {1, 1};
    enc(tm, CU_TENSOR_MAP_DATA_TYPE_BFLOAT16, 2, const_cast<void*>(ptr), dims, strides, box, es,
        CU_TENSOR_MAP_INTERLEAVE_NONE, sw, prom, CU_TENSOR_MAP_FLOAT_OOB_FILL_NONE);
}

}

extern "C" void kernel_launch(void* const* d_in, const int* in_sizes, int n_in, void* d_out, int out_size) {
    (void)in_sizes; (void)n_in; (void)out_size;
    static EncodeFn enc = nullptr;
    static int num_sms = 0;
    if (!enc) {
        void* fn = nullptr;
        cudaDriverEntryPointQueryResult qr;
        cudaGetDriverEntryPoint("cuTensorMapEncodeTiled", &fn, cudaEnableDefault, &qr);
        enc = (EncodeFn)fn;
        cudaDeviceGetAttribute(&num_sms, cudaDevAttrMultiProcessorCount, 0);
        cudaFuncSetAttribute(fused_decode_kernel, cudaFuncAttributeMaxDynamicSharedMemorySize, SM_TOTAL);
    }
    CUtensorMap tmK, tmV, tmMod, tmWq, tmWo, tmW1, tmW3, tmW2;
    const uint64_t kv_lines = (uint64_t)NH * SK * 3;
    make_map(enc, &tmK, d_in[1], 64, kv_lines, 64, 96, CU_TENSOR_MAP_SWIZZLE_128B, CU_TENSOR_MAP_L2_PROMOTION_L2_128B);
    make_map(enc, &tmV, d_in[2], 64, kv_lines, 64, 96, CU_TENSOR_MAP_SWIZZLE_128B, CU_TENSOR_MAP_L2_PROMOTION_L2_128B);
    make_map(enc, &tmWq, d_in[3], NH * DH, D, 48, 128, CU_TENSOR_MAP_SWIZZLE_NONE, CU_TENSOR_MAP_L2_PROMOTION_L2_128B);
    make_map(enc, &tmWo, d_in[4], D, NH * DH, 64, 48, CU_TENSOR_MAP_SWIZZLE_128B, CU_TENSOR_MAP_L2_PROMOTION_L2_128B);
    make_map(enc, &tmW1, d_in[6], FF, D, 16, 160, CU_TENSOR_MAP_SWIZZLE_32B, CU_TENSOR_MAP_L2_PROMOTION_L2_128B);
    make_map(enc, &tmW3, d_in[7], FF, D, 16, 160, CU_TENSOR_MAP_SWIZZLE_32B, CU_TENSOR_MAP_L2_PROMOTION_L2_128B);
    make_map(enc, &tmW2, d_in[8], D, FF, 64, 16, CU_TENSOR_MAP_SWIZZLE_128B, CU_TENSOR_MAP_L2_PROMOTION_L2_128B);
    make_map(enc, &tmMod, d_in[10], 6 * D, D, 32, 160, CU_TENSOR_MAP_SWIZZLE_64B, CU_TENSOR_MAP_L2_PROMOTION_L2_128B);
    int grid = num_sms < MAXG ? num_sms : MAXG;
    fused_decode_kernel<<<grid, NTHREADS, SM_TOTAL, cudaStreamPerThread>>>(
        tmK, tmV, tmMod, tmWq, tmWo, tmW1, tmW3, tmW2, (const __nv_bfloat16*)d_in[0], (const __nv_bfloat16*)d_in[9],
        (__nv_bfloat16*)d_out);
}
```

```cpp
#include <cuda_runtime.h>
#include <cuda_bf16.h>
#include <cuda.h>
#include <stdint.h>

namespace {

constexpr int D = 640, NH = 32, SK = 8192, DH = 192, FF = 1536;
constexpr int NG = 4;
constexpr int GH = 7;
constexpr int NGLOB = NH - NG * GH;
constexpr int NQH = GH + NGLOB;
constexpr int TILE = 32;
constexpr int TPH = SK / TILE;
constexpr int GT = GH * TPH;
constexpr int PT = NGLOB * TPH;
constexpr int CHUNK = TILE * DH * 2;
#define P_NSLOT 8
#define P_WIN 3
#define P_URG 0
#define P_HOLD 3
#define P_FFNWAIT 6
#define P_WOWAIT 5
#define P_BACKOFF 100
#define P_PRONW 6
#define P_W13AT 0
#define P_DLY2 350
#define P_DLY 450
constexpr int NSLOT = P_NSLOT;
constexpr int WIN = P_WIN;
#define P_NBUF 3
constexpr int NBUF = P_NBUF;
constexpr int MAXG = 132;
constexpr int NTHREADS = 288;
constexpr float NEG_BIG = -3.402823466e38f;

constexpr int SM_WMOD = 0;
constexpr int SM_WQ = 40960;
constexpr int SM_WO = 0;
constexpr int SM_W1 = 61440;
constexpr int SM_W3 = 81920;
constexpr int SM_RING = 102400;
constexpr int SM_MISC = SM_RING + NSLOT * CHUNK;
constexpr int SM_BARS = SM_MISC;
constexpr int SM_META = SM_BARS + 512;
constexpr int SM_Q = SM_META + 256;
constexpr int SM_SC = SM_Q + NQH * DH * 2;
constexpr int SM_H = SM_SC + 1280;
constexpr int SM_X = SM_H + 1280;
constexpr int SM_CB = SM_X + 1280;
constexpr int SM_SB = SM_CB + 1280;
constexpr int SM_OWN = SM_SB + 1280;
constexpr int SM_RED = SM_OWN + 128;
constexpr int SM_MERGE = SM_RED + 2048;
constexpr int SM_STAGE = SM_MERGE + NBUF * 3200;
constexpr int SM_X2 = SM_STAGE + 2560;
constexpr int SM_FIN = SM_X2 + 2560;
constexpr int SM_TOTAL = SM_FIN + 512;
static_assert(SM_TOTAL <= 232448, "shared memory budget");

constexpr int B_FULL = 0;
constexpr int B_EMPTY = 8;
constexpr int B_MOD = 16;
constexpr int B_WQ = 20;
constexpr int B_WO = 25;
constexpr int B_W1 = 30;
constexpr int B_W3 = 32;
constexpr int B_W2 = 34;
constexpr int B_PRO = 36, B_DUMMY = 37, B_CLR = 38;
constexpr int B_FLF = 40, B_FLE = 44;
constexpr int B_LAST = 48;
static_assert(NSLOT <= 8 && NSLOT >= 6 && WIN <= 4 && WIN <= NSLOT - 3, "barrier map / end markers vs window");
constexpr uint32_t META_END = 0x10000u;

__device__ unsigned g_epoch;
__device__ unsigned g_ctr[2][(NG + 1) * 32];
__device__ __align__(128) unsigned long long g_mod[1920];
__device__ __align__(128) unsigned long long g_q[3072];
__device__ __align__(128) uint4 g_hdr[NH][MAXG];
__device__ __align__(128) uint4 g_dat[NH][MAXG][64];
__device__ __align__(128) uint4 g_h1[128][128][2];
__device__ __align__(128) uint4 g_x2[128][2];
__device__ __align__(128) uint4 g_h3[128][96][2];

#define TS(k) do {} while (0)
#define DBG(k) do {} while (0)
#define EARLY(k) do {} while (0)
#define CLK(k) do {} while (0)

__device__ __forceinline__ uint32_t smem_u32(const void* p) { return (uint32_t)__cvta_generic_to_shared(p); }
__device__ __forceinline__ void mbar_init(uint32_t bar, uint32_t cnt) {
    asm volatile("mbarrier.init.shared::cta.b64 [%0], %1;" ::"r"(bar), "r"(cnt) : "memory");
}
__device__ __forceinline__ void mbar_expect_tx(uint32_t bar, uint32_t bytes) {
    asm volatile("mbarrier.arrive.expect_tx.shared::cta.b64 _, [%0], %1;" ::"r"(bar), "r"(bytes) : "memory");
}
__device__ __forceinline__ void mbar_arrive(uint32_t bar) {
    asm volatile("mbarrier.arrive.shared::cta.b64 _, [%0];" ::"r"(bar) : "memory");
}
constexpr uint32_t SPIN_LIMIT = 1u << 22;
__device__ __forceinline__ void mbar_wait(uint32_t bar, uint32_t parity) {
    asm volatile(
        "{\n.reg .pred p;\n.reg .u32 c;\nmov.u32 c, 0;\n"
        "LW:\nmbarrier.try_wait.parity.shared::cta.b64 p, [%0], %1;\n@p bra LD;\n"
        "add.u32 c, c, 1;\nsetp.lt.u32 p, c, 0x400000;\n@p bra LW;\ntrap;\nLD:\n}" ::"r"(bar), "r"(parity)
        : "memory");
}
__device__ __forceinline__ uint32_t mbar_try(uint32_t bar, uint32_t parity) {
    uint32_t ok;
    asm volatile("{\n.reg .pred p;\nmbarrier.try_wait.parity.shared::cta.b64 p, [%1], %2;\nselp.u32 %0, 1, 0, p;\n}"
                 : "=r"(ok) : "r"(bar), "r"(parity) : "memory");
    return ok;
}
__device__ __forceinline__ void mbar_wait3(uint32_t b0, uint32_t b1, uint32_t b2) {
    asm volatile(
        "{\n.reg .pred p, q, r;\n.reg .u32 c;\nmov.u32 c, 0;\n"
        "LW:\nmbarrier.try_wait.parity.shared::cta.b64 p, [%0], 0;\n"
        "mbarrier.try_wait.parity.shared::cta.b64 q, [%1], 0;\n"
        "mbarrier.try_wait.parity.shared::cta.b64 r, [%2], 0;\n"
        "and.pred p, p, q;\nand.pred p, p, r;\n@p bra LD;\n"
        "add.u32 c, c, 1;\nsetp.lt.u32 p, c, 0x400000;\n@p bra LW;\ntrap;\nLD:\n}" ::"r"(b0), "r"(b1), "r"(b2)
        : "memory");
}
__device__ __forceinline__ void tma2d(uint32_t dst, const CUtensorMap* tm, int c0, int c1, uint32_t bar) {
    asm volatile(
        "cp.async.bulk.tensor.2d.shared::cluster.global.mbarrier::complete_tx::bytes [%0], [%1, {%3, %4}], [%2];" ::"r"(dst),
        "l"(tm), "r"(bar), "r"(c0), "r"(c1)
        : "memory");
}
__device__ __forceinline__ void tma2d_hint(uint32_t dst, const CUtensorMap* tm, int c0, int c1, uint32_t bar, uint64_t pol) {
    asm volatile(
        "cp.async.bulk.tensor.2d.shared::cluster.global.mbarrier::complete_tx::bytes.L2::cache_hint [%0], [%1, {%3, %4}], [%2], %5;" ::"r"(dst),
        "l"(tm), "r"(bar), "r"(c0), "r"(c1), "l"(pol)
        : "memory");
}
__device__ __forceinline__ void prefetch_tm(const CUtensorMap* tm) {
    asm volatile("prefetch.tensormap [%0];" ::"l"(tm) : "memory");
}
__device__ __forceinline__ void ldsm4(uint32_t (&r)[4], uint32_t addr) {
    asm volatile("ldmatrix.sync.aligned.m8n8.x4.shared.b16 {%0,%1,%2,%3}, [%4];"
                 : "=r"(r[0]), "=r"(r[1]), "=r"(r[2]), "=r"(r[3])
                 : "r"(addr));
}
__device__ __forceinline__ void ldsm4t(uint32_t (&r)[4], uint32_t addr) {
    asm volatile("ldmatrix.sync.aligned.m8n8.x4.trans.shared.b16 {%0,%1,%2,%3}, [%4];"
                 : "=r"(r[0]), "=r"(r[1]), "=r"(r[2]), "=r"(r[3])
                 : "r"(addr));
}
__device__ __forceinline__ void mma16816(float (&d)[4], const uint32_t (&a)[4], uint32_t b0, uint32_t b1) {
    asm volatile(
        "mma.sync.aligned.m16n8k16.row.col.f32.bf16.bf16.f32 {%0,%1,%2,%3}, {%4,%5,%6,%7}, {%8,%9}, {%0,%1,%2,%3};"
        : "+f"(d[0]), "+f"(d[1]), "+f"(d[2]), "+f"(d[3])
        : "r"(a[0]), "r"(a[1]), "r"(a[2]), "r"(a[3]), "r"(b0), "r"(b1));
}
__device__ __forceinline__ void bar_cons() { asm volatile("bar.sync 1, 256;" ::: "memory"); }
__device__ __forceinline__ void spin(int cycles) {
    long long t0 = clock64();
    while (clock64() - t0 < cycles) {}
}

__device__ __forceinline__ float bfr(float x) {
    uint32_t r;
    asm("cvt.rn.bf16x2.f32 %0, %1, %2;" : "=r"(r) : "f"(x), "f"(0.0f));
    return __uint_as_float(r);
}
__device__ __forceinline__ uint32_t pack_bf(float lo, float hi) {
    __nv_bfloat162 t = __floats2bfloat162_rn(lo, hi);
    return *reinterpret_cast<uint32_t*>(&t);
}
__device__ __forceinline__ float bf_lo(uint32_t v) { return __uint_as_float(v << 16); }
__device__ __forceinline__ float bf_hi(uint32_t v) { return __uint_as_float(v & 0xffff0000u); }

__device__ __forceinline__ void st_pk8(unsigned long long* p, uint32_t v, uint32_t tag) {
    unsigned long long w = ((unsigned long long)tag << 32) | v;
    asm volatile("st.relaxed.gpu.global.b64 [%0], %1;" ::"l"(p), "l"(w) : "memory");
}
template <int N>
__device__ __forceinline__ void poll8(const unsigned long long* base, const int (&off)[N], uint32_t (&val)[N], uint32_t tag) {
    uint32_t tg[N];
#pragma unroll
    for (int i = 0; i < N; i++) { val[i] = 0; tg[i] = 0; }
    uint32_t it = 0;
    while (true) {
#pragma unroll
        for (int i = 0; i < N; i++)
            asm volatile("{\n.reg .pred q;\n.reg .b64 t;\nsetp.ne.u32 q, %1, %3;\nmov.b64 t, {%0, %1};\n"
                         "@q ld.relaxed.gpu.global.b64 t, [%2];\nmov.b64 {%0, %1}, t;\n}"
                         : "+r"(val[i]), "+r"(tg[i]) : "l"(base + off[i]), "r"(tag) : "memory");
        bool ok = true;
#pragma unroll
        for (int i = 0; i < N; i++) ok = ok && tg[i] == tag;
        if (__all_sync(0xffffffffu, ok)) break;
        if (++it > SPIN_LIMIT) __trap();
        __nanosleep(P_BACKOFF);
    }
}
__device__ __forceinline__ void st_pk16(uint4* p, uint32_t a, uint32_t b, uint32_t c, uint32_t tag) {
    asm volatile(
        "{\n.reg .b128 t;\n.reg .b64 lo, hi;\nmov.b64 lo, {%1, %2};\nmov.b64 hi, {%3, %4};\nmov.b128 t, {lo, hi};\n"
        "st.relaxed.gpu.global.b128 [%0], t;\n}" ::"l"(p), "r"(a), "r"(b), "r"(c), "r"(tag)
        : "memory");
}
template <int OFF = 0>
__device__ __forceinline__ uint4 ld_raw16p(const uint4* p, uint32_t on) {
    uint4 v;
    asm volatile(
        "{\n.reg .b128 t;\n.reg .b64 lo, hi;\n.reg .pred q;\nsetp.ne.u32 q, %5, 0;\n"
        "mov.b64 lo, 0;\nmov.b128 t, {lo, lo};\n"
        "@q ld.relaxed.gpu.global.b128 t, [%4 + %6];\nmov.b128 {lo, hi}, t;\n"
        "mov.b64 {%0, %1}, lo;\nmov.b64 {%2, %3}, hi;\n}"
        : "=r"(v.x), "=r"(v.y), "=r"(v.z), "=r"(v.w)
        : "l"(p), "r"(on), "n"(OFF * 16)
        : "memory");
    return v;
}
template <int OFF>
__device__ __forceinline__ void ld_fresh16(uint4& v, const uint4* p, uint32_t tag, uint32_t on) {
    asm volatile(
        "{\n.reg .b128 t;\n.reg .b64 lo, hi;\n.reg .pred q;\nsetp.ne.u32 q, %3, %5;\nsetp.ne.and.u32 q, %6, 0, q;\n"
        "mov.b64 lo, {%0, %1};\nmov.b64 hi, {%2, %3};\nmov.b128 t, {lo, hi};\n"
        "@q ld.relaxed.gpu.global.b128 t, [%4 + %7];\nmov.b128 {lo, hi}, t;\n"
        "mov.b64 {%0, %1}, lo;\nmov.b64 {%2, %3}, hi;\n}"
        : "+r"(v.x), "+r"(v.y), "+r"(v.z), "+r"(v.w)
        : "l"(p), "r"(tag), "r"(on), "n"(OFF * 16)
        : "memory");
}
template <int N, int STRIDE, int I = 0>
struct FreshN {
    static __device__ __forceinline__ void run(uint4* v, const uint4* p, uint32_t tag, bool live, int base, int step, int lim) {
        ld_fresh16<I * STRIDE>(v[I], p, tag, live && base + step * I < lim);
        FreshN<N, STRIDE, I + 1>::run(v, p, tag, live, base, step, lim);
    }
};
template <int N, int STRIDE>
struct FreshN<N, STRIDE, N> {
    static __device__ __forceinline__ void run(uint4*, const uint4*, uint32_t, bool, int, int, int) {}
};
template <int N, int STRIDE, int I = 0>
struct LoadN {
    static __device__ __forceinline__ void run(uint4* v, const uint4* p, bool live, int base, int step, int lim) {
        v[I] = ld_raw16p<I * STRIDE>(p, live && base + step * I < lim);
        LoadN<N, STRIDE, I + 1>::run(v, p, live, base, step, lim);
    }
};
template <int N, int STRIDE>
struct LoadN<N, STRIDE, N> {
    static __device__ __forceinline__ void run(uint4*, const uint4*, bool, int, int, int) {}
};
__device__ __forceinline__ uint4 poll16(const uint4* p, uint32_t tag, bool live) {
    uint32_t it = 0;
    uint4 v;
    while (true) {
        v = ld_raw16p(p, live);
        if (__all_sync(0xffffffffu, v.w == tag) || !live) break;
        if (++it > SPIN_LIMIT) __trap();
    }
    return v;
}
__device__ __forceinline__ void st_zero16(void* p) {
    asm volatile("st.relaxed.gpu.global.v4.u32 [%0], {%1, %1, %1, %1};" ::"l"(p), "r"(0u) : "memory");
}
__device__ __forceinline__ float ex2(float x) {
    float y;
    asm("ex2.approx.ftz.f32 %0, %1;" : "=f"(y) : "f"(x));
    return y;
}
__device__ __forceinline__ float fsqrt(float x) {
    float y;
    asm("sqrt.approx.f32 %0, %1;" : "=f"(y) : "f"(x));
    return y;
}
constexpr float LOG2E = 1.4426950408889634f;
__device__ __forceinline__ float silu(float a) { return __fdividef(a, 1.0f + ex2(-a * LOG2E)); }
__device__ __forceinline__ float warp_max(float v) {
    int k = __float_as_int(v);
    k ^= (k >> 31) & 0x7fffffff;
    k = __reduce_max_sync(0xffffffffu, k);
    k ^= (k >> 31) & 0x7fffffff;
    return __int_as_float(k);
}
__device__ __forceinline__ float warp_sum(float v) {
#pragma unroll
    for (int o = 16; o > 0; o >>= 1) v += __shfl_xor_sync(0xffffffffu, v, o);
    return v;
}

__device__ __forceinline__ void ln_stats(const float (&v)[20], float& mean_b, float& den_b) {
    float s = 0.f;
#pragma unroll
    for (int i = 0; i < 20; i++) s += v[i];
    s = warp_sum(s);
    float mean = s * (1.0f / 640.0f);
    float q = 0.f;
#pragma unroll
    for (int i = 0; i < 20; i++) { float d = v[i] - mean; q += d * d; }
    q = warp_sum(q);
    float var_b = bfr(q * (1.0f / 640.0f));
    mean_b = bfr(mean);
    den_b = bfr(fsqrt(bfr(var_b + 1e-5f)));
}

struct Window {
    uint32_t bar[WIN];
    uint32_t par[WIN];
    __device__ __forceinline__ void init(uint32_t dummy) {
#pragma unroll
        for (int i = 0; i < WIN; i++) { bar[i] = dummy; par[i] = 1; }
    }
    __device__ __forceinline__ void push_tail(uint32_t b, uint32_t p, bool wait = true) {
        push(b, p, wait);
    }
    __device__ __forceinline__ void push(uint32_t b, uint32_t p, bool wait = true) {
        if (wait) mbar_wait(bar[0], par[0]);
#pragma unroll
        for (int i = 0; i + 1 < WIN; i++) { bar[i] = bar[i + 1]; par[i] = par[i + 1]; }
        bar[WIN - 1] = b; par[WIN - 1] = p;
    }
};

__global__ void __launch_bounds__(NTHREADS, 1)
fused_decode_kernel(const __grid_constant__ CUtensorMap tmK, const __grid_constant__ CUtensorMap tmV,
                    const __grid_constant__ CUtensorMap tmMod, const __grid_constant__ CUtensorMap tmWq,
                    const __grid_constant__ CUtensorMap tmWo, const __grid_constant__ CUtensorMap tmW1,
                    const __grid_constant__ CUtensorMap tmW3, const __grid_constant__ CUtensorMap tmW2,
                    const __nv_bfloat16* __restrict__ x_in, const __nv_bfloat16* __restrict__ c_in,
                    __nv_bfloat16* __restrict__ out) {
    extern __shared__ __align__(1024) uint8_t smem[];
    const uint32_t sb = smem_u32(smem);
    const int tid = threadIdx.x, wid = tid >> 5, lane = tid & 31;
    const int cta = blockIdx.x, G = gridDim.x;
    const int grp = cta % NG, rank = cta / NG;
    const uint32_t bars = sb + SM_BARS;
    auto BAR = [&](int i) { return bars + 8u * i; };
    volatile uint32_t* meta = reinterpret_cast<volatile uint32_t*>(smem + SM_META);

    uint32_t in_c0 = 0, in_x0 = 0, in_c1 = 0, in_x1 = 0, in_epoch = 0;
    {
        const bool mf = cta < 40;
        const int b0 = mf ? B_MOD : B_WQ;
        if (wid == 8) {
            if (lane == 0) {
#pragma unroll 1
                for (int i = 0; i < 4; i++) mbar_init(BAR(b0 + i), 1);
                asm volatile("fence.mbarrier_init.release.cluster;" ::: "memory");
                asm volatile("fence.proxy.async.shared::cta;" ::: "memory");
                if (cta < 128) {
                    const CUtensorMap* tm = mf ? &tmMod : &tmWq;
#pragma unroll 1
                    for (int i = 0; i < 4; i++) {
                        const uint32_t bar = BAR(b0 + i);
                        mbar_expect_tx(bar, mf ? 10240 : 12288);
                        tma2d(sb + (mf ? SM_WMOD + i * 10240 : SM_WQ + i * 12288), tm, cta * (mf ? 32 : 48), i * (mf ? 160 : 128), bar);
                    }
                }
                asm volatile("ld.relaxed.gpu.global.u32 %0, [%1];" : "=r"(in_epoch) : "l"(&g_epoch) : "memory");
            }
        } else {
            const uint32_t* cg = reinterpret_cast<const uint32_t*>(c_in);
            const uint32_t* xg = reinterpret_cast<const uint32_t*>(x_in);
            in_c0 = __ldg(cg + tid); in_x0 = __ldg(xg + tid);
            if (tid < 64) { in_c1 = __ldg(cg + 256 + tid); in_x1 = __ldg(xg + 256 + tid); }
            if (tid == 0) asm volatile("ld.relaxed.gpu.global.u32 %0, [%1];" : "=r"(in_epoch) : "l"(&g_epoch) : "memory");
            if (lane == 0) {
#pragma unroll 1
                for (int i = wid; i < B_LAST; i += 8) {
                    if (i >= b0 && i < b0 + 4) continue;
                    mbar_init(BAR(i), (i >= B_EMPTY && i < B_MOD) ? 2 : ((i >= B_FLF && i < B_FLE) ? 4 : 1));
                }
                asm volatile("fence.mbarrier_init.release.cluster;" ::: "memory");
                asm volatile("fence.proxy.async.shared::cta;" ::: "memory");
            }
        }
    }
    __syncwarp();
    __syncthreads();
    if (sb & 1023u) __trap();

    if (wid == 8) {
        if (tid == 256) {
            Window win;
            const unsigned epoch = in_epoch;
            prefetch_tm(&tmWq); prefetch_tm(&tmMod); prefetch_tm(&tmK); prefetch_tm(&tmV);
            const int nmod = cta < 120 ? 4 : 0, nwq = cta < 128 ? 5 : 0;
            win.init(BAR(B_DUMMY));
            auto pro_issue = [&](int i, bool issue, bool wait) {
                const bool is_mod = cta < 40 ? i < nmod : i >= nwq;
                const int j = cta < 40 ? (is_mod ? i : i - nmod) : (is_mod ? i - nwq : i);
                const uint32_t bar = BAR((is_mod ? B_MOD : B_WQ) + j);
                win.push(bar, 0, wait);
                if (issue) {
                    mbar_expect_tx(bar, is_mod ? 10240 : 12288);
                    if (is_mod) tma2d(sb + SM_WMOD + j * 10240, &tmMod, cta * 32, j * 160, bar);
                    else tma2d(sb + SM_WQ + j * 12288, &tmWq, cta * 48, j * 128, bar);
                }
            };
            prefetch_tm(&tmWo); prefetch_tm(&tmW1); prefetch_tm(&tmW3); prefetch_tm(&tmW2);
            unsigned* ctr = &g_ctr[epoch & 1][grp * 32];
            unsigned* gctr = &g_ctr[epoch & 1][NG * 32];
            if (cta == 0) {
                for (int g = 0; g <= NG; g++) g_ctr[(epoch + 1) & 1][g * 32] = 0;
            }
            unsigned pend = atomicAdd(ctr, 1);
#pragma unroll 1
            for (int i = 0; i < nmod + nwq; i++) pro_issue(i, i >= 4, i >= P_PRONW);
            auto w13_issue = [&](int i) {
                const int m = i & 1, hf = i >> 1;
                const uint32_t bar = BAR((m ? B_W3 : B_W1) + hf);
                const uint32_t dst = sb + (m ? SM_W3 : SM_W1) + hf * 10240;
                const CUtensorMap* tm = m ? &tmW3 : &tmW1;
                win.push_tail(bar, 0, i < P_FFNWAIT);
                mbar_expect_tx(bar, 10240);
                tma2d(dst, tm, cta * 16, hf * 320, bar);
                tma2d(dst + 5120, tm, cta * 16, hf * 320 + 160, bar);
            };
            uint64_t pol;
            asm volatile("createpolicy.fractional.L2::evict_first.b64 %0, 1.0;" : "=l"(pol));
            int s = 0; uint32_t par = 0;
            int ntiles = 0, run = -1, last_head = -1, w13 = 0;
            bool glob = false;
#pragma unroll 1
            while (true) {
                unsigned t = pend;
                DBG(8);
                if (!glob && t >= (unsigned)GT) { glob = true; t = atomicAdd(gctr, 1); }
                if (glob && t >= (unsigned)PT) break;
                pend = atomicAdd(glob ? gctr : ctr, 1);
                ntiles++;
                const int hl = t / TPH, tile = t % TPH;
                const int head = glob ? NG * GH + hl : grp * GH + hl;
                const int qidx = glob ? GH + hl : hl;
                if (head != last_head) { last_head = head; run++; meta[16 + run] = head; }
                const int line0 = (head * SK + tile * TILE) * 3;
                const bool urgent = glob && t >= (unsigned)(PT - P_URG);
#pragma unroll 1
                for (int kv = 0; kv < 2; kv++) {
                    win.push(BAR(B_FULL + s), par, !urgent);
                    mbar_wait(BAR(B_EMPTY + s), par ^ 1);
                    meta[s] = run | (qidx << 8);
                    mbar_expect_tx(BAR(B_FULL + s), CHUNK);
                    tma2d_hint(sb + SM_RING + s * CHUNK, kv ? &tmV : &tmK, 0, line0, BAR(B_FULL + s), pol);
                    DBG(6 + kv);
                    if (++s == NSLOT) { s = 0; par ^= 1; }
                }
            }
            TS(5);
            meta[16 + run + 1] = 0xFFu;
#pragma unroll 1
            for (int e = 0; e < 2; e++) {
                mbar_wait(BAR(B_EMPTY + s), par ^ 1);
                meta[s] = (run + 1) | META_END;
                mbar_arrive(BAR(B_FULL + s));
                if (++s == NSLOT) { s = 0; par ^= 1; }
                if (++s == NSLOT) { s = 0; par ^= 1; }
            }
#pragma unroll
            for (int i = 0; i < WIN - P_HOLD; i++) mbar_wait(win.bar[i], win.par[i]);
            TS(12);
            if (cta < 128) {
                mbar_wait(BAR(B_PRO), 0);
#pragma unroll 1
                for (int i = 0; i < 5; i++) {
                    win.push_tail(BAR(B_WO + i), 0, i < P_WOWAIT);
                    mbar_expect_tx(BAR(B_WO + i), 12288);
                    tma2d(sb + SM_WO + (2 * i) * 6144, &tmWo, (2 * i) * 64, cta * 48, BAR(B_WO + i));
                    tma2d(sb + SM_WO + (2 * i + 1) * 6144, &tmWo, (2 * i + 1) * 64, cta * 48, BAR(B_WO + i));
                }
                if (cta < 96) {
#pragma unroll 1
                    for (; w13 < 4; w13++) w13_issue(w13);
#pragma unroll 1
                    for (int i = 0; i < 2; i++) {
                        win.push_tail(BAR(B_W2 + i), 0, 4 + i < P_FFNWAIT);
                        mbar_wait(BAR(B_EMPTY + s), par ^ 1);
                        meta[10 + i] = s;
                        mbar_expect_tx(BAR(B_W2 + i), 10240);
#pragma unroll 1
                        for (int b = 0; b < 5; b++)
                            tma2d(sb + SM_RING + s * CHUNK + b * 2048, &tmW2, (5 * i + b) * 64, cta * 16, BAR(B_W2 + i));
                        if (++s == NSLOT) { s = 0; par ^= 1; }
                    }
                }
            }
            TS(6);
        }
    } else {
    const int g4 = lane >> 2, j4 = lane & 3, mi = lane >> 3, l8 = lane & 7;
    uint32_t* sc32 = reinterpret_cast<uint32_t*>(smem + SM_SC);
    uint32_t* h32 = reinterpret_cast<uint32_t*>(smem + SM_H);
    uint32_t* x32 = reinterpret_cast<uint32_t*>(smem + SM_X);
    uint32_t* q32 = reinterpret_cast<uint32_t*>(smem + SM_Q);
    float* red = reinterpret_cast<float*>(smem + SM_RED);
    float* stage = reinterpret_cast<float*>(smem + SM_STAGE);
    float* own = reinterpret_cast<float*>(smem + SM_OWN);

    uint32_t tag;
    bool live = true;
    {
    {
        const uint32_t c0 = in_c0, x0 = in_x0, c1 = in_c1, x1 = in_x1, epoch = in_epoch;
        if (cta < 120 && tid >= 128 && tid < 136) st_zero16(reinterpret_cast<uint4*>(&g_mod[cta * 16]) + (tid - 128));
        if (cta < 128 && tid >= 32 && tid < 44) st_zero16(reinterpret_cast<uint4*>(&g_q[cta * 24]) + (tid - 32));
        sc32[tid] = pack_bf(silu(bf_lo(c0)), silu(bf_hi(c0))); x32[tid] = x0;
        if (tid < 64) { sc32[256 + tid] = pack_bf(silu(bf_lo(c1)), silu(bf_hi(c1))); x32[256 + tid] = x1; }
        if (tid == 0) meta[8] = epoch + 1;
    }
    bar_cons();
    tag = meta[8];
    if (wid == 0) EARLY(3);
    float mean_x = 0.f, rden_x = 1.f;
    if (cta < 128) {
        float xv[20];
#pragma unroll
        for (int i = 0; i < 10; i++) { uint32_t v = x32[lane + 32 * i]; xv[2 * i] = bf_lo(v); xv[2 * i + 1] = bf_hi(v); }
        float den;
        ln_stats(xv, mean_x, den);
        rden_x = __fdividef(1.0f, den);
    }

#pragma unroll 1
    for (int step = 0; step < 2; step++) {
    if (wid >= 4 && (step == 0 ? cta < 40 : (cta >= 40 && cta < 120))) {
        const int w4 = wid - 4;
        float acc[2][4] = {};
        const uint32_t base = sb + SM_WMOD + w4 * 10240;
        mbar_wait(BAR(B_MOD + w4), 0);
        EARLY(4 + w4);
#pragma unroll
        for (int hf = 0; hf < 2; hf++) {
            uint32_t a[5][2][4], bb[5][2];
#pragma unroll
            for (int ks = 0; ks < 5; ks++) {
                const int r0 = w4 * 160 + hf * 80 + ks * 16;
                bb[ks][0] = sc32[(r0 >> 1) + j4]; bb[ks][1] = sc32[(r0 >> 1) + 4 + j4];
                const int r = hf * 80 + ks * 16 + l8 + 8 * (mi >> 1);
#pragma unroll
                for (int mt = 0; mt < 2; mt++) ldsm4t(a[ks][mt], base + r * 64 + (((2 * mt + (mi & 1)) ^ ((r >> 1) & 3)) << 4));
            }
#pragma unroll
            for (int ks = 0; ks < 5; ks++) { mma16816(acc[0], a[ks][0], bb[ks][0], bb[ks][1]); mma16816(acc[1], a[ks][1], bb[ks][0], bb[ks][1]); }
        }
        float* red2 = reinterpret_cast<float*>(smem + SM_FIN);
        if (j4 == 0) {
#pragma unroll
            for (int mt = 0; mt < 2; mt++) { red2[w4 * 32 + mt * 16 + g4] = acc[mt][0]; red2[w4 * 32 + mt * 16 + 8 + g4] = acc[mt][2]; }
        }
        asm volatile("bar.sync 3, 128;" ::: "memory");
        if (wid == 4) EARLY(8);
        if (wid == 4) {
            float v = (red2[lane] + red2[32 + lane]) + (red2[64 + lane] + red2[96 + lane]);
            float o = __shfl_down_sync(0xffffffffu, v, 1);
            if (!(lane & 1)) st_pk8(&g_mod[cta * 16 + (lane >> 1)], pack_bf(v, o), tag);
            if (step == 1 && lane == 0) mbar_arrive(BAR(B_PRO));
        }
        TS(1);
    }
    if (step == 1) break;
    if (cta < 128) {
        {
            const int off[4] = {tid, 320 + tid, tid < 64 ? 256 + tid : tid, tid < 64 ? 576 + tid : 320 + tid};
            uint32_t val[4];
            poll8<4>(g_mod, off, val, tag);
#pragma unroll
            for (int rep = 0; rep < 2; rep++) {
                int p = tid + rep * 256;
                if (p < 320) {
                    uint32_t sa = val[2 * rep], ca = val[2 * rep + 1];
                    uint32_t xx = x32[p];
                    float n0 = bfr(bfr(bf_lo(xx) - mean_x) * rden_x), n1 = bfr(bfr(bf_hi(xx) - mean_x) * rden_x);
                    float h0 = bfr(n0 * bfr(1.0f + bf_lo(ca))) + bf_lo(sa);
                    float h1 = bfr(n1 * bfr(1.0f + bf_hi(ca))) + bf_hi(sa);
                    h32[p] = pack_bf(h0, h1);
                }
            }
        }
        bar_cons();
        TS(2);
        float acc[3][4] = {};
        uint32_t a[5][3][4], bb[5][2];
#pragma unroll
        for (int ks = 0; ks < 5; ks++) {
            const int r0 = wid * 80 + ks * 16;
            bb[ks][0] = h32[(r0 >> 1) + j4]; bb[ks][1] = h32[(r0 >> 1) + 4 + j4];
        }
        mbar_wait(BAR(B_WQ + ((wid * 80) >> 7)), 0);
        mbar_wait(BAR(B_WQ + ((wid * 80 + 79) >> 7)), 0);
        if (wid == 0) EARLY(9);
        if (wid == 7) EARLY(10);
#pragma unroll
        for (int ks = 0; ks < 5; ks++) {
            const int r = wid * 80 + ks * 16 + l8 + 8 * (mi >> 1);
#pragma unroll
            for (int mt = 0; mt < 3; mt++) ldsm4t(a[ks][mt], sb + SM_WQ + r * 96 + ((2 * mt + (mi & 1)) << 4));
        }
#pragma unroll
        for (int ks = 0; ks < 5; ks++) {
#pragma unroll
            for (int mt = 0; mt < 3; mt++) mma16816(acc[mt], a[ks][mt], bb[ks][0], bb[ks][1]);
        }
        if (j4 == 0) {
#pragma unroll
            for (int mt = 0; mt < 3; mt++) { red[wid * 64 + mt * 16 + g4] = acc[mt][0]; red[wid * 64 + mt * 16 + 8 + g4] = acc[mt][2]; }
        }
        bar_cons();
        if (tid < 64) {
            float v = 0.f;
            if (tid < 48) {
#pragma unroll
                for (int w = 0; w < 8; w++) v += red[w * 64 + tid];
            }
            float o = __shfl_down_sync(0xffffffffu, v, 1);
            if (tid < 48 && !(tid & 1)) st_pk8(&g_q[cta * 24 + (tid >> 1)], pack_bf(v, o), tag);
        }
        TS(3);
    }
    {
        int off[5];
#pragma unroll
        for (int j = 0; j < 5; j++) {
            int p = tid + 256 * j;
            if (p >= NQH * 96) p = tid;
            off[j] = p < GH * 96 ? grp * GH * 96 + p : NG * GH * 96 + (p - GH * 96);
        }
        uint32_t val[5];
        poll8<5>(g_q, off, val, tag);
#pragma unroll
        for (int j = 0; j < 5; j++)
            if (tid + 256 * j < NQH * 96) q32[tid + 256 * j] = val[j];
    }
    bar_cons();
    if (tid == 0 && !(cta >= 40 && cta < 120)) mbar_arrive(BAR(B_PRO));
    TS(4);
    }

    if (wid < 4) {
        const int pair = wid >> 1, half = wid & 1;
        uint32_t offK[3], offV[3];
        {
            const int rowK = half * 16 + l8 + 8 * (mi & 1), hiK = mi >> 1;
            const int rowV = half * 16 + l8 + 8 * (mi >> 1), hiV = mi & 1;
#pragma unroll
            for (int t = 0; t < 3; t++) {
                offK[t] = (rowK * 3 + t) * 128 + ((hiK ^ ((rowK * 3 + t) & 7)) << 4);
                offV[t] = (rowV * 3 + t) * 128 + ((hiV ^ ((rowV * 3 + t) & 7)) << 4);
                asm volatile("" : "+r"(offK[t]), "+r"(offV[t]));
            }
        }
        float acc[12][4];
#pragma unroll
        for (int i = 0; i < 12; i++) { acc[i][0] = acc[i][1] = acc[i][2] = acc[i][3] = 0.f; }
        float m_run = NEG_BIG, l_run = 0.f;
        uint32_t qf[12][2];
#pragma unroll
        for (int i = 0; i < 12; i++) { qf[i][0] = qf[i][1] = 0; }
        int cur = -1, flushed = 0, cnt = 0;
        int s = 2 * pair; uint32_t par = 0;
        int fb = 0; uint32_t fpar = 1;
        uint32_t ready = 0;
#pragma unroll 1
        while (true) {
            if (!ready) mbar_wait(BAR(B_FULL + s), par);
            const uint32_t mt_ = meta[s];
            const int run = mt_ & 0xff;
            if (mt_ & META_END) CLK(20);
            if ((mt_ & META_END) && half == 0) DBG(4 + pair);
            if (run != cur) {
#pragma unroll 1
                while (flushed < run) {
                    const uint32_t fle = mbar_try(BAR(B_FLE + fb), fpar);
                    float* mb = reinterpret_cast<float*>(smem + SM_MERGE) + (fb * 4 + wid) * 200;
                    if (flushed != cur) {
#pragma unroll
                        for (int i = 0; i < 12; i++) { acc[i][0] = acc[i][2] = 0.f; }
                        m_run = NEG_BIG; l_run = 0.f; cnt = 0;
                    }
                    float l = l_run;
                    l += __shfl_xor_sync(0xffffffffu, l, 4);
                    l += __shfl_xor_sync(0xffffffffu, l, 8);
                    l += __shfl_xor_sync(0xffffffffu, l, 16);
                    if (!fle) mbar_wait(BAR(B_FLE + fb), fpar);
                    if (j4 == 0) {
#pragma unroll
                        for (int i = 0; i < 12; i++) { mb[4 + 16 * i + g4] = acc[i][0]; mb[4 + 16 * i + 8 + g4] = acc[i][2]; }
                    }
                    if (lane == 0) { mb[0] = m_run; mb[1] = l; mb[2] = __int_as_float(cnt); }
                    __syncwarp();
                    if (lane == 0) mbar_arrive(BAR(B_FLF + fb));
                    if (++fb == NBUF) { fb = 0; fpar ^= 1; }
                    flushed++;
                    cur = -1;
                }
                if (mt_ & META_END) {
                    CLK(21);
                    if (flushed == 0 && lane == 0) mbar_arrive(BAR(B_FLF));
                    break;
                }
                cur = run;
                const int qi = (mt_ >> 8) & 0xff;
#pragma unroll
                for (int i = 0; i < 12; i++) { acc[i][0] = acc[i][1] = acc[i][2] = acc[i][3] = 0.f; }
                m_run = NEG_BIG; l_run = 0.f; cnt = 0;
#pragma unroll
                for (int ks = 0; ks < 12; ks++) {
                    qf[ks][0] = q32[qi * 96 + ks * 8 + j4];
                    qf[ks][1] = q32[qi * 96 + ks * 8 + 4 + j4];
                }
            }
            cnt++;
            if (half == 0) DBG(pair);
            const uint32_t kb = sb + SM_RING + s * CHUNK;
            int sv = s + 1; uint32_t parv = par;
            if (sv == NSLOT) { sv = 0; parv ^= 1; }
            float sc[6][4] = {};
            uint32_t vready;
            {
                uint32_t a[12][4];
#pragma unroll
                for (int t = 0; t < 3; t++) {
                    const uint32_t bt = kb + offK[t];
#pragma unroll
                    for (int kk = 0; kk < 4; kk++) ldsm4(a[t * 4 + kk], bt ^ (kk << 5));
                }
                vready = mbar_try(BAR(B_FULL + sv), parv);
#pragma unroll
                for (int i = 0; i < 12; i++) mma16816(sc[i % 6], a[i], qf[i][0], qf[i][1]);
            }
            __syncwarp();
            if (lane == 0) mbar_arrive(BAR(B_EMPTY + s));
            const float scale = 0.07216878364870322f;
            float s0 = bfr(bfr(((sc[0][0] + sc[1][0]) + (sc[2][0] + sc[3][0])) + (sc[4][0] + sc[5][0])) * scale);
            float s1 = bfr(bfr(((sc[0][2] + sc[1][2]) + (sc[2][2] + sc[3][2])) + (sc[4][2] + sc[5][2])) * scale);
            const float tm = warp_max(fmaxf(s0, s1));
            if (tm > m_run) {
                float alpha = ex2((m_run - tm) * LOG2E);
                l_run *= alpha;
#pragma unroll
                for (int i = 0; i < 12; i++) { acc[i][0] *= alpha; acc[i][1] *= alpha; acc[i][2] *= alpha; acc[i][3] *= alpha; }
                m_run = tm;
            }
            float p0 = ex2((s0 - m_run) * LOG2E);
            float p1 = ex2((s1 - m_run) * LOG2E);
            l_run += p0 + p1;
            const uint32_t pw = pack_bf(p0, p1);
            const uint32_t pa = __shfl_sync(0xffffffffu, pw, 8 * j4), pb = __shfl_sync(0xffffffffu, pw, 8 * j4 + 4);
            const uint32_t b0 = __byte_perm(pa, pb, 0x5410), b1 = __byte_perm(pa, pb, 0x7632);
            if (!vready) mbar_wait(BAR(B_FULL + sv), parv);
            s += 4;
            if (s >= NSLOT) { s -= NSLOT; par ^= 1; }
            if (half == 0) DBG(2 + pair);
            ready = mbar_try(BAR(B_FULL + s), par);
            const uint32_t vb = sb + SM_RING + sv * CHUNK;
            {
                uint32_t a[12][4];
#pragma unroll
                for (int t = 0; t < 3; t++) {
                    const uint32_t bt = vb + offV[t];
#pragma unroll
                    for (int kk = 0; kk < 4; kk++) ldsm4t(a[t * 4 + kk], bt ^ (kk << 5));
                }
#pragma unroll
                for (int i = 0; i < 12; i++) mma16816(acc[i], a[i], b0, b1);
            }
            __syncwarp();
            if (lane == 0) mbar_arrive(BAR(B_EMPTY + sv));
        }
        TS(7);
        CLK(18);
    } else if (wid == 4) {
        int fb = 0; uint32_t fpar = 0;
        mbar_wait(BAR(B_CLR), 0);
#pragma unroll 1
        for (int f = 0;; f++) {
            const float* mb = reinterpret_cast<const float*>(smem + SM_MERGE) + fb * 800;
            mbar_wait(BAR(B_FLF + fb), fpar);
            const int head = (int)meta[16 + f];
            if (head == 0xFF) break;
            float m0 = mb[0], m1 = mb[200], m2 = mb[400], m3 = mb[600];
            float M = fmaxf(fmaxf(m0, m1), fmaxf(m2, m3));
            float w0 = ex2((m0 - M) * LOG2E), w1 = ex2((m1 - M) * LOG2E);
            float w2 = ex2((m2 - M) * LOG2E), w3 = ex2((m3 - M) * LOG2E);
            const int idx = head < NG * GH ? rank : cta;
            uint4* dst = &g_dat[head][idx][0];
            float o[6];
#pragma unroll
            for (int i = 0; i < 6; i++) {
                int d = 4 + (i < 3 ? 3 * lane + i : 96 + 3 * lane + (i - 3));
                o[i] = w0 * mb[d] + w1 * mb[200 + d] + w2 * mb[400 + d] + w3 * mb[600 + d];
            }
            float L = w0 * mb[1] + w1 * mb[201] + w2 * mb[401] + w3 * mb[601];
            const uint32_t tiles = __float_as_int(mb[2]) + __float_as_int(mb[402]);
            st_pk16(dst + lane, __float_as_uint(o[0]), __float_as_uint(o[1]), __float_as_uint(o[2]), tag);
            st_pk16(dst + 32 + lane, __float_as_uint(o[3]), __float_as_uint(o[4]), __float_as_uint(o[5]), tag);
            if (lane == 0) st_pk16(&g_hdr[head][idx], __float_as_uint(M), __float_as_uint(L), tiles, tag);
            __syncwarp();
            if (lane == 0) mbar_arrive(BAR(B_FLE + fb));
            if (++fb == NBUF) { fb = 0; fpar ^= 1; }
            if (meta[16 + f + 1] == 0xFFu) break;
        }
        TS(8);
        CLK(18);
    } else if (wid == 5) {
        if (cta < 128) {
            if (lane < 2) st_zero16(&g_x2[cta][lane]);
#pragma unroll 1
            for (int i = lane; i < 256; i += 32) {
                st_zero16(&g_h1[i >> 1][cta][i & 1]);
                if (cta < 96) st_zero16(&g_h3[i >> 1][cta][i & 1]);
            }
        }
#pragma unroll 1
        for (int f = 0; f < NQH; f++) {
            const int head = f < GH ? grp * GH + f : NG * GH + (f - GH);
            const int idx = f < GH ? rank : cta;
            st_zero16(&g_dat[head][idx][lane]);
            st_zero16(&g_dat[head][idx][32 + lane]);
            if (lane == 0) st_zero16(&g_hdr[head][idx]);
        }
        __syncwarp();
        if (lane == 0) mbar_arrive(BAR(B_CLR));
    } else {
        if (cta < 128) {
            const int t = tid - 192;
            uint32_t* cb32 = reinterpret_cast<uint32_t*>(smem + SM_CB);
            uint32_t* sb32 = reinterpret_cast<uint32_t*>(smem + SM_SB);
            const int col = cta * 5 + t;
            int off[12];
            uint32_t val[12];
#pragma unroll
            for (int rep = 0; rep < 5; rep++) { off[2 * rep] = 960 + t + 64 * rep; off[2 * rep + 1] = 1280 + t + 64 * rep; }
            off[10] = t < 5 ? (1280 + col) >> 1 : 960;
            off[11] = t < 5 ? (3200 + col) >> 1 : 960;
            poll8<12>(g_mod, off, val, tag);
#pragma unroll
            for (int rep = 0; rep < 5; rep++) {
                sb32[t + 64 * rep] = val[2 * rep];
                cb32[t + 64 * rep] = pack_bf(1.0f + bf_lo(val[2 * rep + 1]), 1.0f + bf_hi(val[2 * rep + 1]));
            }
            if (t < 5) {
                own[t] = (col & 1) ? bf_hi(val[10]) : bf_lo(val[10]);
                own[8 + t] = (col & 1) ? bf_hi(val[11]) : bf_lo(val[11]);
                uint32_t xx = x32[col >> 1];
                own[16 + t] = (col & 1) ? bf_hi(xx) : bf_lo(xx);
            }
        }
        live = false;
    }
    }
    const uint32_t sb0 = sb;
    const int tid0 = tid;
#pragma unroll 1
    while (cta < 128) {
        uint32_t sb = sb0; int tid = tid0;
        asm volatile("" : "+r"(sb), "+r"(tid));
        const int wid = tid >> 5, lane = tid & 31;
        const int g4 = lane >> 2, j4 = lane & 3, mi = lane >> 3, l8 = lane & 7;
        CLK(19);
        if (wid >= 5) {
            const int h = cta >> 2, js = cta & 3;
            const bool gl = h >= NG * GH;
            const int ncand = gl ? G : (G - h / GH + NG - 1) / NG;
            const int k = lane & 15, rr = (wid - 5) * 2 + (lane >> 4);
            if (live) {
                const unsigned* cp = &g_ctr[(tag - 1) & 1][(gl ? NG : h / GH) * 32];
                const unsigned thr = ((gl ? h - NG * GH : h % GH) + 1) * TPH;
                uint32_t it = 0;
                while (true) {
                    unsigned v;
                    asm volatile("ld.relaxed.gpu.global.u32 %0, [%1];" : "=r"(v) : "l"(cp) : "memory");
                    if (v >= thr) break;
                    __nanosleep(300);
                    if (++it > SPIN_LIMIT) __trap();
                }
            }
            const uint4* hdr = &g_hdr[h][lane];
            const uint4* dat = &g_dat[h][rr][16 * js + k];
            float* part = stage;
            float L, a0, a1, a2;
            uint32_t it = 0;
            uint4 hd[5], dv[MAXG / 6];
#pragma unroll
            for (int i = 0; i < 5; i++) hd[i] = make_uint4(0, 0, 0, 0);
#pragma unroll
            for (int i = 0; i < MAXG / 6; i++) dv[i] = make_uint4(0, 0, 0, 0);
#pragma unroll 1
            while (true) {
                FreshN<5, 32>::run(hd, hdr, tag, live, lane, 32, ncand);
                FreshN<MAXG / 6, 6 * 64>::run(dv, dat, tag, live, rr, 6, ncand);
                float w[5], M = NEG_BIG;
                int c = 0;
#pragma unroll
                for (int i = 0; i < 5; i++) {
                    const bool v = hd[i].w == tag;
                    w[i] = v ? __uint_as_float(hd[i].x) : NEG_BIG;
                    M = fmaxf(M, w[i]);
                    c += v ? (int)hd[i].z : 0;
                }
                c = __reduce_add_sync(0xffffffffu, c);
                if (++it > SPIN_LIMIT) __trap();
                if (live && c != TPH) continue;
                CLK(1);
                M = warp_max(M);
                float ls = 0.f;
#pragma unroll
                for (int i = 0; i < 5; i++) {
                    const bool v = w[i] != NEG_BIG;
                    const float e = ex2((w[i] - M) * LOG2E);
                    w[i] = v ? e : -0.0f;
                    ls = fmaf(w[i], __uint_as_float(hd[i].y), ls);
                }
                float* wsm = reinterpret_cast<float*>(smem + SM_X2) + (wid - 5) * 160;
                if (live) {
#pragma unroll
                    for (int i = 0; i < 5; i++) wsm[lane + 32 * i] = w[i];
                }
                __syncwarp();
                L = warp_sum(ls);
                uint32_t badm = 0;
                a0 = a1 = a2 = 0.f;
#pragma unroll
                for (int i = 0; i < MAXG / 6; i++) {
                    const float wi = wsm[rr + 6 * i];
                    badm |= (dv[i].w ^ tag) & ~(uint32_t)(__float_as_int(wi) >> 31);
                    a0 = fmaf(wi, __uint_as_float(dv[i].x), a0);
                    a1 = fmaf(wi, __uint_as_float(dv[i].y), a1);
                    a2 = fmaf(wi, __uint_as_float(dv[i].z), a2);
                }
                const bool bad = badm != 0;
                if (!__any_sync(0xffffffffu, bad) || !live) break;
            }
            a0 += __shfl_xor_sync(0xffffffffu, a0, 16);
            a1 += __shfl_xor_sync(0xffffffffu, a1, 16);
            a2 += __shfl_xor_sync(0xffffffffu, a2, 16);
            CLK(2);
            if (live && lane < 16) { float* pp = part + (wid - 5) * 48 + 3 * k; pp[0] = a0; pp[1] = a1; pp[2] = a2; }
            if (live) asm volatile("bar.sync 2, 96;" ::: "memory");
            if (wid == 5 || !live) {
                uint16_t* osw = reinterpret_cast<uint16_t*>(smem + SM_SC);
                const float inv = __fdividef(1.0f, L);
                const float o0 = (part[lane] + part[48 + lane]) + part[96 + lane];
                const float o1 = (part[32 + (lane & 15)] + part[80 + (lane & 15)]) + part[128 + (lane & 15)];
                if (live) { osw[lane] = (uint16_t)(__float_as_uint(bfr(o0 * inv)) >> 16); if (lane < 16) osw[32 + lane] = (uint16_t)(__float_as_uint(bfr(o1 * inv)) >> 16); }
            }
            if (live) TS(10);
        }
        if (wid < 5 || !live) {
            const int w5 = wid < 5 ? wid : wid - 5;
            uint32_t wa[8][3][4];
            if (live) mbar_wait(BAR(B_WO + w5), 0);
#pragma unroll
            for (int i = 0; i < 8; i++) {
                const int cc = 2 * (i & 3) + (mi & 1);
#pragma unroll
                for (int ks = 0; ks < 3; ks++) {
                    const int r = ks * 16 + l8 + 8 * (mi >> 1);
                    ldsm4t(wa[i][ks], sb + SM_WO + (2 * w5 + (i >> 2)) * 6144 + r * 128 + ((cc ^ (r & 7)) << 4));
                }
            }
            if (live) bar_cons();
            if (live) TS(9);
            CLK(3);
            const uint32_t* os32 = reinterpret_cast<const uint32_t*>(smem + SM_SC);
            float acc[8][4] = {};
#pragma unroll
            for (int ks = 0; ks < 3; ks++) {
                const uint32_t b0 = os32[ks * 8 + j4], b1 = os32[ks * 8 + 4 + j4];
#pragma unroll
                for (int i = 0; i < 8; i++) mma16816(acc[i], wa[i][ks], b0, b1);
            }
            if (live && j4 == 0) {
#pragma unroll
                for (int i = 0; i < 8; i++) { stage[(w5 * 8 + i) * 16 + g4] = acc[i][0]; stage[(w5 * 8 + i) * 16 + 8 + g4] = acc[i][2]; }
            }
        } else {
            bar_cons();
        }
        CLK(4);
        if (live) bar_cons();
        {
            const int o = tid >> 1, kk = tid & 1;
            const float* sp = stage + o * 5 + kk * 3;
            float v0 = sp[0], v1 = sp[1], v2 = kk ? 0.f : sp[2];
            if (live) st_pk16(&g_h1[o][cta][kk], __float_as_uint(v0), __float_as_uint(v1), __float_as_uint(v2), tag);
        }
        if (live) TS(11);
        CLK(5);
        if (wid == 0 || !live) {
            const uint4* p = &g_h1[cta][0][0] + lane;
            uint4 v[8];
            uint32_t it = 0;
            while (true) {
                bool ok = true;
                LoadN<8, 32>::run(v, p, live, 0, 0, 1);
#pragma unroll
                for (int j = 0; j < 8; j++) ok = ok && v[j].w == tag;
                if (__all_sync(0xffffffffu, ok) || !live) break;
                if (++it > SPIN_LIMIT) __trap();
            }
            CLK(6);
            float a0 = 0.f, a1 = 0.f, a2 = 0.f;
#pragma unroll
            for (int j = 0; j < 8; j++) { a0 += __uint_as_float(v[j].x); a1 += __uint_as_float(v[j].y); a2 += __uint_as_float(v[j].z); }
#pragma unroll
            for (int o = 2; o <= 16; o <<= 1) {
                a0 += __shfl_xor_sync(0xffffffffu, a0, o);
                a1 += __shfl_xor_sync(0xffffffffu, a1, o);
                a2 += __shfl_xor_sync(0xffffffffu, a2, o);
            }
            const float gx = own[lane & 7], xx = own[16 + (lane & 7)];
            const float t0 = __shfl_sync(0xffffffffu, a0, lane >= 3), t1 = __shfl_sync(0xffffffffu, a1, lane >= 3);
            const float sum = (lane == 0 || lane == 3) ? t0 : (lane == 2 ? a2 : t1);
            const float x2 = bfr(xx + bfr(gx * bfr(sum)));
            if (live && lane < 5) own[24 + lane] = x2;
            const float y1 = __shfl_sync(0xffffffffu, x2, 1), y2 = __shfl_sync(0xffffffffu, x2, 2);
            const float y3 = __shfl_sync(0xffffffffu, x2, 3), y4 = __shfl_sync(0xffffffffu, x2, 4);
            if (live && lane == 0) st_pk16(&g_x2[cta][0], pack_bf(x2, y1), pack_bf(y2, y3), pack_bf(y4, 0.f), tag);
            if (live && cta < 96) asm volatile("bar.arrive 4, 160;" ::: "memory");
            if (live) TS(13);
        }
        CLK(8);
        if (cta < 96) {
            uint32_t a1[5][4], a3[5][4], a2[5][4];
            if (live) mbar_wait3(BAR(B_W1 + (wid >> 2)), BAR(B_W3 + (wid >> 2)), BAR(B_W2 + (wid >> 2)));
            const uint32_t w2b = sb + SM_RING + meta[10 + (wid >> 2)] % NSLOT * CHUNK;
#pragma unroll
            for (int ks = 0; ks < 5; ks++) {
                const int r = wid * 80 + ks * 16 + l8 + 8 * (mi >> 1);
                const uint32_t off = r * 32 + (((mi & 1) ^ ((r >> 2) & 1)) << 4);
                ldsm4t(a1[ks], sb + SM_W1 + off);
                ldsm4t(a3[ks], sb + SM_W3 + off);
            }
#pragma unroll
            for (int i = 0; i < 5; i++) {
                const int mt = (wid & 3) * 5 + i;
                const int cc = 2 * (mt & 3) + (mi & 1);
                const int r = l8 + 8 * (mi >> 1);
                ldsm4t(a2[i], w2b + (mt >> 2) * 2048 + r * 128 + ((cc ^ (r & 7)) << 4));
            }
            CLK(9);
            float* x2s = reinterpret_cast<float*>(smem + SM_X2);
            float* st8 = red + 256;
            if (wid >= 4) {
                if (live) { asm volatile("bar.sync 4, 160;" ::: "memory"); spin(P_DLY2); }
                uint4 v = poll16(&g_x2[tid - 128][0], tag, live);
                const float e0 = bf_lo(v.x), e1 = bf_hi(v.x), e2 = bf_lo(v.y), e3 = bf_hi(v.y), e4 = bf_lo(v.z);
                float* d = x2s + (tid - 128) * 5;
                if (live) { d[0] = e0; d[1] = e1; d[2] = e2; d[3] = e3; d[4] = e4; }
                const float pv = __shfl_sync(0xffffffffu, e0, 0);
                const float d0 = e0 - pv, d1 = e1 - pv, d2 = e2 - pv, d3 = e3 - pv, d4 = e4 - pv;
                float s1 = ((d0 + d1) + (d2 + d3)) + d4;
                float s2 = fmaf(d0, d0, fmaf(d1, d1, fmaf(d2, d2, fmaf(d3, d3, d4 * d4))));
#pragma unroll
                for (int o = 16; o > 0; o >>= 1) { s1 += __shfl_xor_sync(0xffffffffu, s1, o); s2 += __shfl_xor_sync(0xffffffffu, s2, o); }
                if (live && lane == 0) { st8[2 * (wid - 4)] = pv + s1 * (1.0f / 160.0f); st8[2 * (wid - 4) + 1] = s2 - s1 * s1 * (1.0f / 160.0f); }
            }
            if (live) bar_cons();
            if (live) TS(14);
            CLK(10);
            const float4 sA = *reinterpret_cast<const float4*>(st8), sB = *reinterpret_cast<const float4*>(st8 + 4);
            const float mean = ((sA.x + sA.z) + (sB.x + sB.z)) * 0.25f;
            const float u0 = sA.x - mean, u1 = sA.z - mean, u2 = sB.x - mean, u3 = sB.z - mean;
            const float m2 = ((sA.y + sA.w) + (sB.y + sB.w)) + 160.0f * ((u0 * u0 + u1 * u1) + (u2 * u2 + u3 * u3));
            const float mean_b = bfr(mean);
            const float rden = __fdividef(1.0f, bfr(fsqrt(bfr(bfr(m2 * (1.0f / 640.0f)) + 1e-5f))));
            const uint32_t* cb32 = reinterpret_cast<const uint32_t*>(smem + SM_CB);
            const uint32_t* sb32 = reinterpret_cast<const uint32_t*>(smem + SM_SB);
#pragma unroll
            for (int rep = 0; rep < 2; rep++) {
                const int p = lane + 32 * rep;
                if (p < 40) {
                    int pp = wid * 40 + p;
                    const float2 xv = *reinterpret_cast<const float2*>(x2s + 2 * pp);
                    uint32_t cv = cb32[pp], sv = sb32[pp];
                    float n0 = bfr(bfr(xv.x - mean_b) * rden), n1 = bfr(bfr(xv.y - mean_b) * rden);
                    uint32_t hv = pack_bf(bfr(n0 * bf_lo(cv)) + bf_lo(sv), bfr(n1 * bf_hi(cv)) + bf_hi(sv));
                    if (live) h32[pp] = hv;
                }
            }
            __syncwarp();
            CLK(11);
            float ag[2][4] = {}, au[2][4] = {};
#pragma unroll
            for (int ks = 0; ks < 5; ks++) {
                const int r0 = wid * 80 + ks * 16;
                const uint32_t b0 = h32[(r0 >> 1) + j4], b1 = h32[(r0 >> 1) + 4 + j4];
                mma16816(ag[ks & 1], a1[ks], b0, b1);
                mma16816(au[ks & 1], a3[ks], b0, b1);
            }
            if (live && j4 == 0) {
                red[wid * 32 + g4] = ag[0][0] + ag[1][0]; red[wid * 32 + 8 + g4] = ag[0][2] + ag[1][2];
                red[wid * 32 + 16 + g4] = au[0][0] + au[1][0]; red[wid * 32 + 24 + g4] = au[0][2] + au[1][2];
            }
            CLK(12);
            if (live) bar_cons();
            if (live) TS(15);
            CLK(13);
            float v = 0.f;
#pragma unroll
            for (int w = 0; w < 8; w++) v += red[w * 32 + lane];
            v = bfr(v);
            float up = __shfl_down_sync(0xffffffffu, v, 16);
            float hact = bfr(bfr(silu(v)) * up);
            float e0 = __shfl_sync(0xffffffffu, hact, 2 * j4), e1 = __shfl_sync(0xffffffffu, hact, 2 * j4 + 1);
            float e2 = __shfl_sync(0xffffffffu, hact, 2 * j4 + 8), e3 = __shfl_sync(0xffffffffu, hact, 2 * j4 + 9);
            const uint32_t b0 = pack_bf(e0, e1), b1 = pack_bf(e2, e3);
            float acc[5][4] = {};
#pragma unroll
            for (int i = 0; i < 5; i++) mma16816(acc[i], a2[i], b0, b1);
            if (live && j4 == 0) {
#pragma unroll
                for (int i = 0; i < 5; i++) { stage[(wid * 5 + i) * 16 + g4] = acc[i][0]; stage[(wid * 5 + i) * 16 + 8 + g4] = acc[i][2]; }
            }
            CLK(14);
            if (live) bar_cons();
            const int o = tid >> 1, k = tid & 1;
            const float* sp = stage + o * 5 + k * 3;
            float v0 = sp[0], v1 = sp[1], v2 = k ? 0.f : sp[2];
            if (live) st_pk16(&g_h3[o][cta][k], __float_as_uint(v0), __float_as_uint(v1), __float_as_uint(v2), tag);
        }
        if (live) TS(16);
        CLK(15);
        if (wid == 0 || !live) {
            const uint4* p = &g_h3[cta][0][0] + lane;
            uint4 v[6];
            uint32_t it = 0;
            if (live && cta < 96) spin(P_DLY);
            while (true) {
                bool ok = true;
                LoadN<6, 32>::run(v, p, live, 0, 0, 1);
#pragma unroll
                for (int j = 0; j < 6; j++) ok = ok && v[j].w == tag;
                if (__all_sync(0xffffffffu, ok) || !live) break;
                if (++it > SPIN_LIMIT) __trap();
            }
            CLK(16);
            float a0 = 0.f, a1 = 0.f, a2 = 0.f;
#pragma unroll
            for (int j = 0; j < 6; j++) { a0 += __uint_as_float(v[j].x); a1 += __uint_as_float(v[j].y); a2 += __uint_as_float(v[j].z); }
#pragma unroll
            for (int o = 2; o <= 16; o <<= 1) {
                a0 += __shfl_xor_sync(0xffffffffu, a0, o);
                a1 += __shfl_xor_sync(0xffffffffu, a1, o);
                a2 += __shfl_xor_sync(0xffffffffu, a2, o);
            }
            const float gx = own[8 + (lane & 7)], xx = own[24 + (lane & 7)];
            const float t0 = __shfl_sync(0xffffffffu, a0, lane >= 3), t1 = __shfl_sync(0xffffffffu, a1, lane >= 3);
            const float sum = (lane == 0 || lane == 3) ? t0 : (lane == 2 ? a2 : t1);
            const float y = xx + bfr(gx * bfr(sum));
            if (live && lane < 5) reinterpret_cast<uint16_t*>(out)[cta * 5 + lane] = (uint16_t)(__float_as_uint(bfr(y)) >> 16);
            if (live && cta == 0 && lane == 0) g_epoch = tag;
        }
        CLK(17);
        if (live) { TS(18); break; }
        live = true;
    }
    }
}

typedef CUresult (*EncodeFn)(CUtensorMap*, CUtensorMapDataType, cuuint32_t, void*, const cuuint64_t*, const cuuint64_t*,
                             const cuuint32_t*, const cuuint32_t*, CUtensorMapInterleave, CUtensorMapSwizzle,
                             CUtensorMapL2promotion, CUtensorMapFloatOOBfill);

void make_map(EncodeFn enc, CUtensorMap* tm, const void* ptr, uint64_t cols, uint64_t rows, uint32_t box_c, uint32_t box_r,
              CUtensorMapSwizzle sw, CUtensorMapL2promotion prom) {
    cuuint64_t dims[2] = {cols, rows};
    cuuint64_t strides[1] = {cols * 2};
    cuuint32_t box[2] = {box_c, box_r};
    cuuint32_t es[2] = {1, 1};
    enc(tm, CU_TENSOR_MAP_DATA_TYPE_BFLOAT16, 2, const_cast<void*>(ptr), dims, strides, box, es,
        CU_TENSOR_MAP_INTERLEAVE_NONE, sw, prom, CU_TENSOR_MAP_FLOAT_OOB_FILL_NONE);
}

}

extern "C" void kernel_launch(void* const* d_in, const int* in_sizes, int n_in, void* d_out, int out_size) {
    (void)in_sizes; (void)n_in; (void)out_size;
    static EncodeFn enc = nullptr;
    static int num_sms = 0;
    if (!enc) {
        void* fn = nullptr;
        cudaDriverEntryPointQueryResult qr;
        cudaGetDriverEntryPoint("cuTensorMapEncodeTiled", &fn, cudaEnableDefault, &qr);
        enc = (EncodeFn)fn;
        cudaDeviceGetAttribute(&num_sms, cudaDevAttrMultiProcessorCount, 0);
        cudaFuncSetAttribute(fused_decode_kernel, cudaFuncAttributeMaxDynamicSharedMemorySize, SM_TOTAL);
    }
    CUtensorMap tmK, tmV, tmMod, tmWq, tmWo, tmW1, tmW3, tmW2;
    const uint64_t kv_lines = (uint64_t)NH * SK * 3;
    make_map(enc, &tmK, d_in[1], 64, kv_lines, 64, 96, CU_TENSOR_MAP_SWIZZLE_128B, CU_TENSOR_MAP_L2_PROMOTION_L2_128B);
    make_map(enc, &tmV, d_in[2], 64, kv_lines, 64, 96, CU_TENSOR_MAP_SWIZZLE_128B, CU_TENSOR_MAP_L2_PROMOTION_L2_128B);
    make_map(enc, &tmWq, d_in[3], NH * DH, D, 48, 128, CU_TENSOR_MAP_SWIZZLE_NONE, CU_TENSOR_MAP_L2_PROMOTION_L2_128B);
    make_map(enc, &tmWo, d_in[4], D, NH * DH, 64, 48, CU_TENSOR_MAP_SWIZZLE_128B, CU_TENSOR_MAP_L2_PROMOTION_L2_128B);
    make_map(enc, &tmW1, d_in[6], FF, D, 16, 160, CU_TENSOR_MAP_SWIZZLE_32B, CU_TENSOR_MAP_L2_PROMOTION_L2_128B);
    make_map(enc, &tmW3, d_in[7], FF, D, 16, 160, CU_TENSOR_MAP_SWIZZLE_32B, CU_TENSOR_MAP_L2_PROMOTION_L2_128B);
    make_map(enc, &tmW2, d_in[8], D, FF, 64, 16, CU_TENSOR_MAP_SWIZZLE_128B, CU_TENSOR_MAP_L2_PROMOTION_L2_128B);
    make_map(enc, &tmMod, d_in[10], 6 * D, D, 32, 160, CU_TENSOR_MAP_SWIZZLE_64B, CU_TENSOR_MAP_L2_PROMOTION_L2_128B);
    int grid = num_sms < MAXG ? num_sms : MAXG;
    fused_decode_kernel<<<grid, NTHREADS, SM_TOTAL, cudaStreamPerThread>>>(
        tmK, tmV, tmMod, tmWq, tmWo, tmW1, tmW3, tmW2, (const __nv_bfloat16*)d_in[0], (const __nv_bfloat16*)d_in[9],
        (__nv_bfloat16*)d_out);
}
```

```cpp
#include <cuda_runtime.h>
#include <cuda_bf16.h>
#include <cuda.h>
#include <stdint.h>

namespace {

constexpr int D = 640, NH = 32, SK = 8192, DH = 192, FF = 1536;
constexpr int NG = 4;
constexpr int GH = 7;
constexpr int NGLOB = NH - NG * GH;
constexpr int NQH = GH + NGLOB;
constexpr int TILE = 32;
constexpr int TPH = SK / TILE;
constexpr int GT = GH * TPH;
constexpr int PT = NGLOB * TPH;
constexpr int CHUNK = TILE * DH * 2;
#define P_NSLOT 8
#define P_WIN 3
#define P_URG 0
#define P_HOLD 3
#define P_FFNWAIT 6
#define P_FFNDEEP false
#define P_WODEEP false
#define P_WOWAIT 5
#define P_BACKOFF 100
#define P_W13AT 0
#define P_PW 4
#define P_ILV 0
#define P_DLY 450
constexpr int NSLOT = P_NSLOT;
constexpr int WIN = P_WIN;
#define P_NBUF 2
constexpr int NBUF = P_NBUF;
constexpr int NLATE = 4;
constexpr int MAXG = 132;
constexpr int NTHREADS = 288;
constexpr float NEG_BIG = -3.402823466e38f;

constexpr int SM_WMOD = 0;
constexpr int SM_WQ = 40960;
constexpr int SM_WO = 0;
constexpr int SM_W1 = 61440;
constexpr int SM_W3 = 81920;
constexpr int SM_RING = 102400;
constexpr int SM_MISC = SM_RING + NSLOT * CHUNK;
constexpr int SM_BARS = SM_MISC;
constexpr int SM_META = SM_BARS + 512;
constexpr int SM_Q = SM_META + 256;
constexpr int SM_SC = SM_Q + NQH * DH * 2;
constexpr int SM_H = SM_SC + 1280;
constexpr int SM_X = SM_H + 1280;
constexpr int SM_CB = SM_X + 1280;
constexpr int SM_SB = SM_CB + 1280;
constexpr int SM_GA = SM_SB + 1280;
constexpr int SM_OWN = SM_GA + 1280;
constexpr int SM_RED = SM_OWN + 128;
constexpr int SM_MERGE = SM_RED + 2048;
constexpr int SM_STAGE = SM_MERGE + NBUF * 3200;
constexpr int SM_X2 = SM_STAGE + 2560;
constexpr int SM_FIN = SM_X2 + 2560;
constexpr int SM_TOTAL = SM_FIN + 512;
static_assert(SM_TOTAL <= 232448, "shared memory budget");

constexpr int B_FULL = 0;
constexpr int B_EMPTY = 8;
constexpr int B_MOD = 16;
constexpr int B_WQ = 20;
constexpr int B_WO = 25;
constexpr int B_W1 = 30;
constexpr int B_W3 = 32;
constexpr int B_W2 = 34;
constexpr int B_PRO = 36, B_DUMMY = 37, B_CLR = 38;
constexpr int B_FLF = 40, B_FLE = 44;
constexpr int B_LAST = 48;
static_assert(NSLOT <= 8 && NSLOT >= 6 && WIN <= 4 && WIN <= NSLOT - 3, "barrier map / end markers vs window");
constexpr uint32_t META_END = 0x10000u;

__device__ unsigned g_epoch;
__device__ unsigned g_ctr[2][(NG + 1) * 32];
__device__ __align__(128) unsigned long long g_mod[1920];
__device__ __align__(128) unsigned long long g_q[3072];
__device__ __align__(128) uint4 g_hdr[NH][MAXG];
__device__ __align__(128) uint4 g_dat[NH][MAXG][64];
__device__ __align__(128) uint4 g_h1[128][128][2];
__device__ __align__(128) uint4 g_es[128][2];
__device__ __align__(128) uint4 g_late[NLATE][128][2];
__device__ __align__(128) uint4 g_h3[128][96][2];

#define TS(k) do {} while (0)
#define DBG(k) do {} while (0)
#define EARLY(k) do {} while (0)
#define CLK(k) do {} while (0)

__device__ __forceinline__ uint32_t smem_u32(const void* p) { return (uint32_t)__cvta_generic_to_shared(p); }
__device__ __forceinline__ void mbar_init(uint32_t bar, uint32_t cnt) {
    asm volatile("mbarrier.init.shared::cta.b64 [%0], %1;" ::"r"(bar), "r"(cnt) : "memory");
}
__device__ __forceinline__ void mbar_expect_tx(uint32_t bar, uint32_t bytes) {
    asm volatile("mbarrier.arrive.expect_tx.shared::cta.b64 _, [%0], %1;" ::"r"(bar), "r"(bytes) : "memory");
}
__device__ __forceinline__ void mbar_arrive(uint32_t bar) {
    asm volatile("mbarrier.arrive.shared::cta.b64 _, [%0];" ::"r"(bar) : "memory");
}
constexpr uint32_t SPIN_LIMIT = 1u << 22;
__device__ __forceinline__ void mbar_wait(uint32_t bar, uint32_t parity) {
    asm volatile(
        "{\n.reg .pred p;\n.reg .u32 c;\nmov.u32 c, 0;\n"
        "LW:\nmbarrier.try_wait.parity.shared::cta.b64 p, [%0], %1;\n@p bra LD;\n"
        "add.u32 c, c, 1;\nsetp.lt.u32 p, c, 0x400000;\n@p bra LW;\ntrap;\nLD:\n}" ::"r"(bar), "r"(parity)
        : "memory");
}
__device__ __forceinline__ uint32_t mbar_try(uint32_t bar, uint32_t parity) {
    uint32_t ok;
    asm volatile("{\n.reg .pred p;\nmbarrier.try_wait.parity.shared::cta.b64 p, [%1], %2;\nselp.u32 %0, 1, 0, p;\n}"
                 : "=r"(ok) : "r"(bar), "r"(parity) : "memory");
    return ok;
}
__device__ __forceinline__ void mbar_wait3(uint32_t b0, uint32_t b1, uint32_t b2) {
    asm volatile(
        "{\n.reg .pred p, q, r;\n.reg .u32 c;\nmov.u32 c, 0;\n"
        "LW:\nmbarrier.try_wait.parity.shared::cta.b64 p, [%0], 0;\n"
        "mbarrier.try_wait.parity.shared::cta.b64 q, [%1], 0;\n"
        "mbarrier.try_wait.parity.shared::cta.b64 r, [%2], 0;\n"
        "and.pred p, p, q;\nand.pred p, p, r;\n@p bra LD;\n"
        "add.u32 c, c, 1;\nsetp.lt.u32 p, c, 0x400000;\n@p bra LW;\ntrap;\nLD:\n}" ::"r"(b0), "r"(b1), "r"(b2)
        : "memory");
}
__device__ __forceinline__ void tma2d(uint32_t dst, const CUtensorMap* tm, int c0, int c1, uint32_t bar) {
    asm volatile(
        "cp.async.bulk.tensor.2d.shared::cluster.global.mbarrier::complete_tx::bytes [%0], [%1, {%3, %4}], [%2];" ::"r"(dst),
        "l"(tm), "r"(bar), "r"(c0), "r"(c1)
        : "memory");
}
__device__ __forceinline__ void tma2d_hint(uint32_t dst, const CUtensorMap* tm, int c0, int c1, uint32_t bar, uint64_t pol) {
    asm volatile(
        "cp.async.bulk.tensor.2d.shared::cluster.global.mbarrier::complete_tx::bytes.L2::cache_hint [%0], [%1, {%3, %4}], [%2], %5;" ::"r"(dst),
        "l"(tm), "r"(bar), "r"(c0), "r"(c1), "l"(pol)
        : "memory");
}
__device__ __forceinline__ void prefetch_tm(const CUtensorMap* tm) {
    asm volatile("prefetch.tensormap [%0];" ::"l"(tm) : "memory");
}
__device__ __forceinline__ void ldsm4(uint32_t (&r)[4], uint32_t addr) {
    asm volatile("ldmatrix.sync.aligned.m8n8.x4.shared.b16 {%0,%1,%2,%3}, [%4];"
                 : "=r"(r[0]), "=r"(r[1]), "=r"(r[2]), "=r"(r[3])
                 : "r"(addr));
}
__device__ __forceinline__ void ldsm4t(uint32_t (&r)[4], uint32_t addr) {
    asm volatile("ldmatrix.sync.aligned.m8n8.x4.trans.shared.b16 {%0,%1,%2,%3}, [%4];"
                 : "=r"(r[0]), "=r"(r[1]), "=r"(r[2]), "=r"(r[3])
                 : "r"(addr));
}
__device__ __forceinline__ void mma16816(float (&d)[4], const uint32_t (&a)[4], uint32_t b0, uint32_t b1) {
    asm volatile(
        "mma.sync.aligned.m16n8k16.row.col.f32.bf16.bf16.f32 {%0,%1,%2,%3}, {%4,%5,%6,%7}, {%8,%9}, {%0,%1,%2,%3};"
        : "+f"(d[0]), "+f"(d[1]), "+f"(d[2]), "+f"(d[3])
        : "r"(a[0]), "r"(a[1]), "r"(a[2]), "r"(a[3]), "r"(b0), "r"(b1));
}
__device__ __forceinline__ void bar_cons() { asm volatile("bar.sync 1, 256;" ::: "memory"); }
__device__ __forceinline__ void spin(int cycles) {
    long long t0 = clock64();
    while (clock64() - t0 < cycles) {}
}

__device__ __forceinline__ float bfr(float x) {
    uint32_t r;
    asm("cvt.rn.bf16x2.f32 %0, %1, %2;" : "=r"(r) : "f"(x), "f"(0.0f));
    return __uint_as_float(r);
}
__device__ __forceinline__ uint32_t pack_bf(float lo, float hi) {
    __nv_bfloat162 t = __floats2bfloat162_rn(lo, hi);
    return *reinterpret_cast<uint32_t*>(&t);
}
__device__ __forceinline__ float bf_lo(uint32_t v) { return __uint_as_float(v << 16); }
__device__ __forceinline__ float bf_hi(uint32_t v) { return __uint_as_float(v & 0xffff0000u); }

__device__ __forceinline__ void st_pk8(unsigned long long* p, uint32_t v, uint32_t tag) {
    unsigned long long w = ((unsigned long long)tag << 32) | v;
    asm volatile("st.relaxed.gpu.global.b64 [%0], %1;" ::"l"(p), "l"(w) : "memory");
}
template <int N>
__device__ __forceinline__ void poll8(const unsigned long long* base, const int (&off)[N], uint32_t (&val)[N], uint32_t tag) {
    uint32_t tg[N];
#pragma unroll
    for (int i = 0; i < N; i++) { val[i] = 0; tg[i] = 0; }
    uint32_t it = 0;
    while (true) {
#pragma unroll
        for (int i = 0; i < N; i++)
            asm volatile("{\n.reg .pred q;\n.reg .b64 t;\nsetp.ne.u32 q, %1, %3;\nmov.b64 t, {%0, %1};\n"
                         "@q ld.relaxed.gpu.global.b64 t, [%2];\nmov.b64 {%0, %1}, t;\n}"
                         : "+r"(val[i]), "+r"(tg[i]) : "l"(base + off[i]), "r"(tag) : "memory");
        bool ok = true;
#pragma unroll
        for (int i = 0; i < N; i++) ok = ok && tg[i] == tag;
        if (__all_sync(0xffffffffu, ok)) break;
        if (++it > SPIN_LIMIT) __trap();
        __nanosleep(P_BACKOFF);
    }
}
__device__ __forceinline__ void st_pk16(uint4* p, uint32_t a, uint32_t b, uint32_t c, uint32_t tag) {
    asm volatile(
        "{\n.reg .b128 t;\n.reg .b64 lo, hi;\nmov.b64 lo, {%1, %2};\nmov.b64 hi, {%3, %4};\nmov.b128 t, {lo, hi};\n"
        "st.relaxed.gpu.global.b128 [%0], t;\n}" ::"l"(p), "r"(a), "r"(b), "r"(c), "r"(tag)
        : "memory");
}
template <int OFF = 0>
__device__ __forceinline__ uint4 ld_raw16p(const uint4* p, uint32_t on) {
    uint4 v;
    asm volatile(
        "{\n.reg .b128 t;\n.reg .b64 lo, hi;\n.reg .pred q;\nsetp.ne.u32 q, %5, 0;\n"
        "mov.b64 lo, 0;\nmov.b128 t, {lo, lo};\n"
        "@q ld.relaxed.gpu.global.b128 t, [%4 + %6];\nmov.b128 {lo, hi}, t;\n"
        "mov.b64 {%0, %1}, lo;\nmov.b64 {%2, %3}, hi;\n}"
        : "=r"(v.x), "=r"(v.y), "=r"(v.z), "=r"(v.w)
        : "l"(p), "r"(on), "n"(OFF * 16)
        : "memory");
    return v;
}
template <int OFF>
__device__ __forceinline__ void ld_fresh16(uint4& v, const uint4* p, uint32_t tag, uint32_t on) {
    asm volatile(
        "{\n.reg .b128 t;\n.reg .b64 lo, hi;\n.reg .pred q;\nsetp.ne.u32 q, %3, %5;\nsetp.ne.and.u32 q, %6, 0, q;\n"
        "mov.b64 lo, {%0, %1};\nmov.b64 hi, {%2, %3};\nmov.b128 t, {lo, hi};\n"
        "@q ld.relaxed.gpu.global.b128 t, [%4 + %7];\nmov.b128 {lo, hi}, t;\n"
        "mov.b64 {%0, %1}, lo;\nmov.b64 {%2, %3}, hi;\n}"
        : "+r"(v.x), "+r"(v.y), "+r"(v.z), "+r"(v.w)
        : "l"(p), "r"(tag), "r"(on), "n"(OFF * 16)
        : "memory");
}
template <int N, int STRIDE, int I = 0>
struct FreshN {
    static __device__ __forceinline__ void run(uint4* v, const uint4* p, uint32_t tag, bool live, int base, int step, int lim) {
        ld_fresh16<I * STRIDE>(v[I], p, tag, live && base + step * I < lim);
        FreshN<N, STRIDE, I + 1>::run(v, p, tag, live, base, step, lim);
    }
};
template <int N, int STRIDE>
struct FreshN<N, STRIDE, N> {
    static __device__ __forceinline__ void run(uint4*, const uint4*, uint32_t, bool, int, int, int) {}
};
template <int N, int STRIDE, int I = 0>
struct LoadN {
    static __device__ __forceinline__ void run(uint4* v, const uint4* p, bool live, int base, int step, int lim) {
        v[I] = ld_raw16p<I * STRIDE>(p, live && base + step * I < lim);
        LoadN<N, STRIDE, I + 1>::run(v, p, live, base, step, lim);
    }
};
template <int N, int STRIDE>
struct LoadN<N, STRIDE, N> {
    static __device__ __forceinline__ void run(uint4*, const uint4*, bool, int, int, int) {}
};
__device__ __forceinline__ void st_zero16(void* p) {
    asm volatile("st.relaxed.gpu.global.v4.u32 [%0], {%1, %1, %1, %1};" ::"l"(p), "r"(0u) : "memory");
}
__device__ __forceinline__ float ex2(float x) {
    float y;
    asm("ex2.approx.ftz.f32 %0, %1;" : "=f"(y) : "f"(x));
    return y;
}
__device__ __forceinline__ float fsqrt(float x) {
    float y;
    asm("sqrt.approx.f32 %0, %1;" : "=f"(y) : "f"(x));
    return y;
}
constexpr float LOG2E = 1.4426950408889634f;
__device__ __forceinline__ float silu(float a) { return __fdividef(a, 1.0f + ex2(-a * LOG2E)); }
__device__ __forceinline__ float warp_max(float v) {
    int k = __float_as_int(v);
    k ^= (k >> 31) & 0x7fffffff;
    k = __reduce_max_sync(0xffffffffu, k);
    k ^= (k >> 31) & 0x7fffffff;
    return __int_as_float(k);
}
__device__ __forceinline__ float warp_sum(float v) {
#pragma unroll
    for (int o = 16; o > 0; o >>= 1) v += __shfl_xor_sync(0xffffffffu, v, o);
    return v;
}

__device__ __forceinline__ void ln_stats(const float (&v)[20], float& mean_b, float& den_b) {
    float s = 0.f;
#pragma unroll
    for (int i = 0; i < 20; i++) s += v[i];
    s = warp_sum(s);
    float mean = s * (1.0f / 640.0f);
    float q = 0.f;
#pragma unroll
    for (int i = 0; i < 20; i++) { float d = v[i] - mean; q += d * d; }
    q = warp_sum(q);
    float var_b = bfr(q * (1.0f / 640.0f));
    mean_b = bfr(mean);
    den_b = bfr(fsqrt(bfr(var_b + 1e-5f)));
}

constexpr int WMAX = P_PW > WIN ? P_PW : WIN;
struct Window {
    uint32_t bar[WMAX];
    uint32_t par[WMAX];
    __device__ __forceinline__ void init(uint32_t dummy) {
#pragma unroll
        for (int i = 0; i < WMAX; i++) { bar[i] = dummy; par[i] = 1; }
    }
    __device__ __forceinline__ void push(uint32_t b, uint32_t p, bool wait = true, bool deep = false) {
        if (wait) mbar_wait(deep ? bar[WMAX - P_PW] : bar[WMAX - WIN], deep ? par[WMAX - P_PW] : par[WMAX - WIN]);
#pragma unroll
        for (int i = 0; i + 1 < WMAX; i++) { bar[i] = bar[i + 1]; par[i] = par[i + 1]; }
        bar[WMAX - 1] = b; par[WMAX - 1] = p;
    }
    __device__ __forceinline__ void push_tail(uint32_t b, uint32_t p, bool wait = true, bool deep = false) { push(b, p, wait, deep); }
};

__global__ void __launch_bounds__(NTHREADS, 1)
fused_decode_kernel(const __grid_constant__ CUtensorMap tmK, const __grid_constant__ CUtensorMap tmV,
                    const __grid_constant__ CUtensorMap tmMod, const __grid_constant__ CUtensorMap tmWq,
                    const __grid_constant__ CUtensorMap tmWo, const __grid_constant__ CUtensorMap tmW1,
                    const __grid_constant__ CUtensorMap tmW3, const __grid_constant__ CUtensorMap tmW2,
                    const __nv_bfloat16* __restrict__ x_in, const __nv_bfloat16* __restrict__ c_in,
                    __nv_bfloat16* __restrict__ out) {
    extern __shared__ __align__(1024) uint8_t smem[];
    const uint32_t sb = smem_u32(smem);
    const int tid = threadIdx.x, wid = tid >> 5, lane = tid & 31;
    const int cta = blockIdx.x, G = gridDim.x;
    const int grp = cta % NG, rank = cta / NG;
    const uint32_t bars = sb + SM_BARS;
    auto BAR = [&](int i) { return bars + 8u * i; };
    volatile uint32_t* meta = reinterpret_cast<volatile uint32_t*>(smem + SM_META);

    uint32_t in_c0 = 0, in_x0 = 0, in_c1 = 0, in_x1 = 0, in_epoch = 0;
    {
        const bool mf = cta < 40;
        const int b0 = mf ? B_MOD : B_WQ;
        if (wid == 8) {
            if (lane == 0) {
#pragma unroll 1
                for (int i = 0; i < 4; i++) mbar_init(BAR(b0 + i), 1);
                asm volatile("fence.mbarrier_init.release.cluster;" ::: "memory");
                asm volatile("fence.proxy.async.shared::cta;" ::: "memory");
                if (cta < 128) {
                    const CUtensorMap* tm = mf ? &tmMod : &tmWq;
#pragma unroll 1
                    for (int i = 0; i < 4; i++) {
                        const uint32_t bar = BAR(b0 + i);
                        mbar_expect_tx(bar, mf ? 10240 : 12288);
                        tma2d(sb + (mf ? SM_WMOD + i * 10240 : SM_WQ + i * 12288), tm, cta * (mf ? 32 : 48), i * (mf ? 160 : 128), bar);
                    }
                }
                asm volatile("ld.relaxed.gpu.global.u32 %0, [%1];" : "=r"(in_epoch) : "l"(&g_epoch) : "memory");
            }
        } else {
            const uint32_t* cg = reinterpret_cast<const uint32_t*>(c_in);
            const uint32_t* xg = reinterpret_cast<const uint32_t*>(x_in);
            in_c0 = __ldg(cg + tid); in_x0 = __ldg(xg + tid);
            if (tid < 64) { in_c1 = __ldg(cg + 256 + tid); in_x1 = __ldg(xg + 256 + tid); }
            if (tid == 0) asm volatile("ld.relaxed.gpu.global.u32 %0, [%1];" : "=r"(in_epoch) : "l"(&g_epoch) : "memory");
            if (lane == 0) {
#pragma unroll 1
                for (int i = wid; i < B_LAST; i += 8) {
                    if (i >= b0 && i < b0 + 4) continue;
                    mbar_init(BAR(i), (i >= B_EMPTY && i < B_MOD) ? 2 : ((i >= B_FLF && i < B_FLE) ? 4 : 1));
                }
                asm volatile("fence.mbarrier_init.release.cluster;" ::: "memory");
                asm volatile("fence.proxy.async.shared::cta;" ::: "memory");
            }
        }
    }
    __syncwarp();
    __syncthreads();
    if (sb & 1023u) __trap();

    if (wid == 8) {
        if (tid == 256) {
            Window win;
            const unsigned epoch = in_epoch;
            prefetch_tm(&tmWq); prefetch_tm(&tmMod); prefetch_tm(&tmK); prefetch_tm(&tmV);
            const int nmod = cta < 120 ? 4 : 0, nwq = cta < 128 ? 5 : 0;
            win.init(BAR(B_DUMMY));
            auto pro_issue = [&](int i, bool issue, bool wait) {
                const bool is_mod = cta < 40 ? i < nmod : i >= nwq;
                const int j = cta < 40 ? (is_mod ? i : i - nmod) : (is_mod ? i - nwq : i);
                const uint32_t bar = BAR((is_mod ? B_MOD : B_WQ) + j);
                win.push(bar, 0, wait, true);
                if (issue) {
                    mbar_expect_tx(bar, is_mod ? 10240 : 12288);
                    if (is_mod) tma2d(sb + SM_WMOD + j * 10240, &tmMod, cta * 32, j * 160, bar);
                    else tma2d(sb + SM_WQ + j * 12288, &tmWq, cta * 48, j * 128, bar);
                }
            };
            prefetch_tm(&tmWo); prefetch_tm(&tmW1); prefetch_tm(&tmW3); prefetch_tm(&tmW2);
            unsigned* ctr = &g_ctr[epoch & 1][grp * 32];
            unsigned* gctr = &g_ctr[epoch & 1][NG * 32];
            if (cta == 0) {
                for (int g = 0; g <= NG; g++) g_ctr[(epoch + 1) & 1][g * 32] = 0;
            }
            unsigned pend = atomicAdd(ctr, 1);
            const int npro = nmod + nwq;
            int pro_i = 0;
#pragma unroll 1
            for (; pro_i < npro && (pro_i < 4 || !P_ILV); pro_i++) pro_issue(pro_i, pro_i >= 4, pro_i >= 4);
            auto w13_issue = [&](int i) {
                const int m = i & 1, hf = i >> 1;
                const uint32_t bar = BAR((m ? B_W3 : B_W1) + hf);
                const uint32_t dst = sb + (m ? SM_W3 : SM_W1) + hf * 10240;
                const CUtensorMap* tm = m ? &tmW3 : &tmW1;
                win.push_tail(bar, 0, i < P_FFNWAIT, P_FFNDEEP);
                mbar_expect_tx(bar, 10240);
                tma2d(dst, tm, cta * 16, hf * 320, bar);
                tma2d(dst + 5120, tm, cta * 16, hf * 320 + 160, bar);
            };
            uint64_t pol;
            asm volatile("createpolicy.fractional.L2::evict_first.b64 %0, 1.0;" : "=l"(pol));
            int s = 0; uint32_t par = 0;
            int ntiles = 0, run = -1, last_head = -1, w13 = 0;
            bool glob = false;
#pragma unroll 1
            while (true) {
                unsigned t = pend;
                DBG(8);
                if (!glob && t >= (unsigned)GT) { glob = true; t = atomicAdd(gctr, 1); }
                if (glob && t >= (unsigned)PT) break;
                pend = atomicAdd(glob ? gctr : ctr, 1);
                ntiles++;
                const int hl = t / TPH, tile = t % TPH;
                const int head = glob ? NG * GH + hl : grp * GH + hl;
                const int qidx = glob ? GH + hl : hl;
                if (head != last_head) { last_head = head; run++; meta[16 + run] = head; }
                const int line0 = (head * SK + tile * TILE) * 3;
                const bool urgent = glob && t >= (unsigned)(PT - P_URG);
#pragma unroll 1
                for (int kv = 0; kv < 2; kv++) {
                    const bool early = pro_i < npro;
                    win.push(BAR(B_FULL + s), par, !urgent, early);
                    mbar_wait(BAR(B_EMPTY + s), par ^ 1);
                    meta[s] = run | (qidx << 8);
                    mbar_expect_tx(BAR(B_FULL + s), CHUNK);
                    tma2d_hint(sb + SM_RING + s * CHUNK, kv ? &tmV : &tmK, 0, line0, BAR(B_FULL + s), pol);
                    DBG(6 + kv);
                    if (++s == NSLOT) { s = 0; par ^= 1; }
                    if (early) { pro_issue(pro_i, true, true); pro_i++; }
                }
            }
#pragma unroll 1
            for (; pro_i < npro; pro_i++) pro_issue(pro_i, true, true);
            TS(5);
            meta[16 + run + 1] = 0xFFu;
#pragma unroll 1
            for (int e = 0; e < 2; e++) {
                mbar_wait(BAR(B_EMPTY + s), par ^ 1);
                meta[s] = (run + 1) | META_END;
                mbar_arrive(BAR(B_FULL + s));
                if (++s == NSLOT) { s = 0; par ^= 1; }
                if (++s == NSLOT) { s = 0; par ^= 1; }
            }
#pragma unroll
            for (int i = 0; i < WIN - P_HOLD; i++) mbar_wait(win.bar[WMAX - WIN + i], win.par[WMAX - WIN + i]);
            TS(12);
            if (cta < 128) {
                mbar_wait(BAR(B_PRO), 0);
#pragma unroll 1
                for (int i = 0; i < 5; i++) {
                    win.push_tail(BAR(B_WO + i), 0, i < P_WOWAIT, P_WODEEP);
                    mbar_expect_tx(BAR(B_WO + i), 12288);
                    tma2d(sb + SM_WO + (2 * i) * 6144, &tmWo, (2 * i) * 64, cta * 48, BAR(B_WO + i));
                    tma2d(sb + SM_WO + (2 * i + 1) * 6144, &tmWo, (2 * i + 1) * 64, cta * 48, BAR(B_WO + i));
                }
                if (cta < 96) {
#pragma unroll 1
                    for (; w13 < 4; w13++) w13_issue(w13);
#pragma unroll 1
                    for (int i = 0; i < 2; i++) {
                        win.push_tail(BAR(B_W2 + i), 0, 4 + i < P_FFNWAIT, P_FFNDEEP);
                        mbar_wait(BAR(B_EMPTY + s), par ^ 1);
                        meta[10 + i] = s;
                        mbar_expect_tx(BAR(B_W2 + i), 10240);
#pragma unroll 1
                        for (int b = 0; b < 5; b++)
                            tma2d(sb + SM_RING + s * CHUNK + b * 2048, &tmW2, (5 * i + b) * 64, cta * 16, BAR(B_W2 + i));
                        if (++s == NSLOT) { s = 0; par ^= 1; }
                    }
                }
            }
            TS(6);
        }
    } else {
    const int g4 = lane >> 2, j4 = lane & 3, mi = lane >> 3, l8 = lane & 7;
    uint32_t* sc32 = reinterpret_cast<uint32_t*>(smem + SM_SC);
    uint32_t* h32 = reinterpret_cast<uint32_t*>(smem + SM_H);
    uint32_t* x32 = reinterpret_cast<uint32_t*>(smem + SM_X);
    uint32_t* q32 = reinterpret_cast<uint32_t*>(smem + SM_Q);
    float* red = reinterpret_cast<float*>(smem + SM_RED);
    float* stage = reinterpret_cast<float*>(smem + SM_STAGE);
    float* own = reinterpret_cast<float*>(smem + SM_OWN);

    uint32_t tag;
    bool live = true;
    {
    {
        const uint32_t c0 = in_c0, x0 = in_x0, c1 = in_c1, x1 = in_x1, epoch = in_epoch;
        if (cta < 120 && tid >= 128 && tid < 136) st_zero16(reinterpret_cast<uint4*>(&g_mod[cta * 16]) + (tid - 128));
        if (cta < 128 && tid >= 32 && tid < 44) st_zero16(reinterpret_cast<uint4*>(&g_q[cta * 24]) + (tid - 32));
        sc32[tid] = pack_bf(silu(bf_lo(c0)), silu(bf_hi(c0))); x32[tid] = x0;
        if (tid < 64) { sc32[256 + tid] = pack_bf(silu(bf_lo(c1)), silu(bf_hi(c1))); x32[256 + tid] = x1; }
        if (tid == 0) meta[8] = epoch + 1;
    }
    bar_cons();
    tag = meta[8];
    if (wid == 0) EARLY(3);
    float mean_x = 0.f, rden_x = 1.f;
    if (cta < 128) {
        float xv[20];
#pragma unroll
        for (int i = 0; i < 10; i++) { uint32_t v = x32[lane + 32 * i]; xv[2 * i] = bf_lo(v); xv[2 * i + 1] = bf_hi(v); }
        float den;
        ln_stats(xv, mean_x, den);
        rden_x = __fdividef(1.0f, den);
    }

#pragma unroll 1
    for (int step = 0; step < 2; step++) {
    if (wid >= 4 && (step == 0 ? cta < 40 : (cta >= 40 && cta < 120))) {
        const int w4 = wid - 4;
        float acc[2][4] = {};
        const uint32_t base = sb + SM_WMOD + w4 * 10240;
        mbar_wait(BAR(B_MOD + w4), 0);
        EARLY(4 + w4);
#pragma unroll
        for (int hf = 0; hf < 2; hf++) {
            uint32_t a[5][2][4], bb[5][2];
#pragma unroll
            for (int ks = 0; ks < 5; ks++) {
                const int r0 = w4 * 160 + hf * 80 + ks * 16;
                bb[ks][0] = sc32[(r0 >> 1) + j4]; bb[ks][1] = sc32[(r0 >> 1) + 4 + j4];
                const int r = hf * 80 + ks * 16 + l8 + 8 * (mi >> 1);
#pragma unroll
                for (int mt = 0; mt < 2; mt++) ldsm4t(a[ks][mt], base + r * 64 + (((2 * mt + (mi & 1)) ^ ((r >> 1) & 3)) << 4));
            }
#pragma unroll
            for (int ks = 0; ks < 5; ks++) { mma16816(acc[0], a[ks][0], bb[ks][0], bb[ks][1]); mma16816(acc[1], a[ks][1], bb[ks][0], bb[ks][1]); }
        }
        float* red2 = reinterpret_cast<float*>(smem + SM_FIN);
        if (j4 == 0) {
#pragma unroll
            for (int mt = 0; mt < 2; mt++) { red2[w4 * 32 + mt * 16 + g4] = acc[mt][0]; red2[w4 * 32 + mt * 16 + 8 + g4] = acc[mt][2]; }
        }
        asm volatile("bar.sync 3, 128;" ::: "memory");
        if (wid == 4) EARLY(8);
        if (wid == 4) {
            float v = (red2[lane] + red2[32 + lane]) + (red2[64 + lane] + red2[96 + lane]);
            float o = __shfl_down_sync(0xffffffffu, v, 1);
            if (!(lane & 1)) st_pk8(&g_mod[cta * 16 + (lane >> 1)], pack_bf(v, o), tag);
            if (step == 1 && lane == 0) mbar_arrive(BAR(B_PRO));
        }
        TS(1);
    }
    if (step == 1) break;
    if (cta < 128) {
        {
            const int off[4] = {tid, 320 + tid, tid < 64 ? 256 + tid : tid, tid < 64 ? 576 + tid : 320 + tid};
            uint32_t val[4];
            poll8<4>(g_mod, off, val, tag);
#pragma unroll
            for (int rep = 0; rep < 2; rep++) {
                int p = tid + rep * 256;
                if (p < 320) {
                    uint32_t sa = val[2 * rep], ca = val[2 * rep + 1];
                    uint32_t xx = x32[p];
                    float n0 = bfr(bfr(bf_lo(xx) - mean_x) * rden_x), n1 = bfr(bfr(bf_hi(xx) - mean_x) * rden_x);
                    float h0 = bfr(n0 * bfr(1.0f + bf_lo(ca))) + bf_lo(sa);
                    float h1 = bfr(n1 * bfr(1.0f + bf_hi(ca))) + bf_hi(sa);
                    h32[p] = pack_bf(h0, h1);
                }
            }
        }
        bar_cons();
        TS(2);
        float acc[3][4] = {};
        uint32_t a[5][3][4], bb[5][2];
#pragma unroll
        for (int ks = 0; ks < 5; ks++) {
            const int r0 = wid * 80 + ks * 16;
            bb[ks][0] = h32[(r0 >> 1) + j4]; bb[ks][1] = h32[(r0 >> 1) + 4 + j4];
        }
        mbar_wait(BAR(B_WQ + ((wid * 80) >> 7)), 0);
        mbar_wait(BAR(B_WQ + ((wid * 80 + 79) >> 7)), 0);
        if (wid == 0) EARLY(9);
        if (wid == 7) EARLY(10);
#pragma unroll
        for (int ks = 0; ks < 5; ks++) {
            const int r = wid * 80 + ks * 16 + l8 + 8 * (mi >> 1);
#pragma unroll
            for (int mt = 0; mt < 3; mt++) ldsm4t(a[ks][mt], sb + SM_WQ + r * 96 + ((2 * mt + (mi & 1)) << 4));
        }
#pragma unroll
        for (int ks = 0; ks < 5; ks++) {
#pragma unroll
            for (int mt = 0; mt < 3; mt++) mma16816(acc[mt], a[ks][mt], bb[ks][0], bb[ks][1]);
        }
        if (j4 == 0) {
#pragma unroll
            for (int mt = 0; mt < 3; mt++) { red[wid * 64 + mt * 16 + g4] = acc[mt][0]; red[wid * 64 + mt * 16 + 8 + g4] = acc[mt][2]; }
        }
        bar_cons();
        if (tid < 64) {
            float v = 0.f;
            if (tid < 48) {
#pragma unroll
                for (int w = 0; w < 8; w++) v += red[w * 64 + tid];
            }
            float o = __shfl_down_sync(0xffffffffu, v, 1);
            if (tid < 48 && !(tid & 1)) st_pk8(&g_q[cta * 24 + (tid >> 1)], pack_bf(v, o), tag);
        }
        TS(3);
    }
    {
        int off[5];
#pragma unroll
        for (int j = 0; j < 5; j++) {
            int p = tid + 256 * j;
            if (p >= NQH * 96) p = tid;
            off[j] = p < GH * 96 ? grp * GH * 96 + p : NG * GH * 96 + (p - GH * 96);
        }
        uint32_t val[5];
        poll8<5>(g_q, off, val, tag);
#pragma unroll
        for (int j = 0; j < 5; j++)
            if (tid + 256 * j < NQH * 96) q32[tid + 256 * j] = val[j];
    }
    bar_cons();
    if (tid == 0 && !(cta >= 40 && cta < 120)) mbar_arrive(BAR(B_PRO));
    TS(4);
    }

    if (wid < 4) {
        const int pair = wid >> 1, half = wid & 1;
        uint32_t offK[3], offV[3];
        {
            const int rowK = half * 16 + l8 + 8 * (mi & 1), hiK = mi >> 1;
            const int rowV = half * 16 + l8 + 8 * (mi >> 1), hiV = mi & 1;
#pragma unroll
            for (int t = 0; t < 3; t++) {
                offK[t] = (rowK * 3 + t) * 128 + ((hiK ^ ((rowK * 3 + t) & 7)) << 4);
                offV[t] = (rowV * 3 + t) * 128 + ((hiV ^ ((rowV * 3 + t) & 7)) << 4);
                asm volatile("" : "+r"(offK[t]), "+r"(offV[t]));
            }
        }
        float acc[12][4];
#pragma unroll
        for (int i = 0; i < 12; i++) { acc[i][0] = acc[i][1] = acc[i][2] = acc[i][3] = 0.f; }
        float m_run = NEG_BIG, l_run = 0.f;
        uint32_t qf[12][2];
#pragma unroll
        for (int i = 0; i < 12; i++) { qf[i][0] = qf[i][1] = 0; }
        int cur = -1, flushed = 0, cnt = 0;
        int s = 2 * pair; uint32_t par = 0;
        int fb = 0; uint32_t fpar = 1;
        uint32_t ready = 0;
#pragma unroll 1
        while (true) {
            if (!ready) mbar_wait(BAR(B_FULL + s), par);
            const uint32_t mt_ = meta[s];
            const int run = mt_ & 0xff;
            if (mt_ & META_END) CLK(20);
            if ((mt_ & META_END) && half == 0) DBG(4 + pair);
            if (run != cur) {
#pragma unroll 1
                while (flushed < run) {
                    const uint32_t fle = mbar_try(BAR(B_FLE + fb), fpar);
                    float* mb = reinterpret_cast<float*>(smem + SM_MERGE) + (fb * 4 + wid) * 200;
                    if (flushed != cur) {
#pragma unroll
                        for (int i = 0; i < 12; i++) { acc[i][0] = acc[i][2] = 0.f; }
                        m_run = NEG_BIG; l_run = 0.f; cnt = 0;
                    }
                    float l = l_run;
                    l += __shfl_xor_sync(0xffffffffu, l, 4);
                    l += __shfl_xor_sync(0xffffffffu, l, 8);
                    l += __shfl_xor_sync(0xffffffffu, l, 16);
                    if (!fle) mbar_wait(BAR(B_FLE + fb), fpar);
                    if (j4 == 0) {
#pragma unroll
                        for (int i = 0; i < 12; i++) { mb[4 + 16 * i + g4] = acc[i][0]; mb[4 + 16 * i + 8 + g4] = acc[i][2]; }
                    }
                    if (lane == 0) { mb[0] = m_run; mb[1] = l; mb[2] = __int_as_float(cnt); }
                    __syncwarp();
                    if (lane == 0) mbar_arrive(BAR(B_FLF + fb));
                    if (++fb == NBUF) { fb = 0; fpar ^= 1; }
                    flushed++;
                    cur = -1;
                }
                if (mt_ & META_END) {
                    CLK(21);
                    if (flushed == 0 && lane == 0) mbar_arrive(BAR(B_FLF));
                    break;
                }
                cur = run;
                const int qi = (mt_ >> 8) & 0xff;
#pragma unroll
                for (int i = 0; i < 12; i++) { acc[i][0] = acc[i][1] = acc[i][2] = acc[i][3] = 0.f; }
                m_run = NEG_BIG; l_run = 0.f; cnt = 0;
#pragma unroll
                for (int ks = 0; ks < 12; ks++) {
                    qf[ks][0] = q32[qi * 96 + ks * 8 + j4];
                    qf[ks][1] = q32[qi * 96 + ks * 8 + 4 + j4];
                }
            }
            cnt++;
            if (half == 0) DBG(pair);
            const uint32_t kb = sb + SM_RING + s * CHUNK;
            int sv = s + 1; uint32_t parv = par;
            if (sv == NSLOT) { sv = 0; parv ^= 1; }
            float sc[6][4] = {};
            uint32_t vready;
            {
                uint32_t a[12][4];
#pragma unroll
                for (int t = 0; t < 3; t++) {
                    const uint32_t bt = kb + offK[t];
#pragma unroll
                    for (int kk = 0; kk < 4; kk++) ldsm4(a[t * 4 + kk], bt ^ (kk << 5));
                }
                vready = mbar_try(BAR(B_FULL + sv), parv);
#pragma unroll
                for (int i = 0; i < 12; i++) mma16816(sc[i % 6], a[i], qf[i][0], qf[i][1]);
            }
            __syncwarp();
            if (lane == 0) mbar_arrive(BAR(B_EMPTY + s));
            const float scale = 0.07216878364870322f;
            float s0 = bfr(bfr(((sc[0][0] + sc[1][0]) + (sc[2][0] + sc[3][0])) + (sc[4][0] + sc[5][0])) * scale);
            float s1 = bfr(bfr(((sc[0][2] + sc[1][2]) + (sc[2][2] + sc[3][2])) + (sc[4][2] + sc[5][2])) * scale);
            const float tm = warp_max(fmaxf(s0, s1));
            if (tm > m_run) {
                float alpha = ex2((m_run - tm) * LOG2E);
                l_run *= alpha;
#pragma unroll
                for (int i = 0; i < 12; i++) { acc[i][0] *= alpha; acc[i][1] *= alpha; acc[i][2] *= alpha; acc[i][3] *= alpha; }
                m_run = tm;
            }
            float p0 = ex2((s0 - m_run) * LOG2E);
            float p1 = ex2((s1 - m_run) * LOG2E);
            l_run += p0 + p1;
            const uint32_t pw = pack_bf(p0, p1);
            const uint32_t pa = __shfl_sync(0xffffffffu, pw, 8 * j4), pb = __shfl_sync(0xffffffffu, pw, 8 * j4 + 4);
            const uint32_t b0 = __byte_perm(pa, pb, 0x5410), b1 = __byte_perm(pa, pb, 0x7632);
            if (!vready) mbar_wait(BAR(B_FULL + sv), parv);
            s += 4;
            if (s >= NSLOT) { s -= NSLOT; par ^= 1; }
            if (half == 0) DBG(2 + pair);
            ready = mbar_try(BAR(B_FULL + s), par);
            const uint32_t vb = sb + SM_RING + sv * CHUNK;
            {
                uint32_t a[12][4];
#pragma unroll
                for (int t = 0; t < 3; t++) {
                    const uint32_t bt = vb + offV[t];
#pragma unroll
                    for (int kk = 0; kk < 4; kk++) ldsm4t(a[t * 4 + kk], bt ^ (kk << 5));
                }
#pragma unroll
                for (int i = 0; i < 12; i++) mma16816(acc[i], a[i], b0, b1);
            }
            __syncwarp();
            if (lane == 0) mbar_arrive(BAR(B_EMPTY + sv));
        }
        TS(7);
        CLK(18);
    } else if (wid == 4) {
        int fb = 0; uint32_t fpar = 0;
        mbar_wait(BAR(B_CLR), 0);
#pragma unroll 1
        for (int f = 0;; f++) {
            const float* mb = reinterpret_cast<const float*>(smem + SM_MERGE) + fb * 800;
            mbar_wait(BAR(B_FLF + fb), fpar);
            const int head = (int)meta[16 + f];
            if (head == 0xFF) break;
            float m0 = mb[0], m1 = mb[200], m2 = mb[400], m3 = mb[600];
            float M = fmaxf(fmaxf(m0, m1), fmaxf(m2, m3));
            float w0 = ex2((m0 - M) * LOG2E), w1 = ex2((m1 - M) * LOG2E);
            float w2 = ex2((m2 - M) * LOG2E), w3 = ex2((m3 - M) * LOG2E);
            const int idx = head < NG * GH ? rank : cta;
            uint4* dst = &g_dat[head][idx][0];
            float o[6];
#pragma unroll
            for (int i = 0; i < 6; i++) {
                int d = 4 + (i < 3 ? 3 * lane + i : 96 + 3 * lane + (i - 3));
                o[i] = w0 * mb[d] + w1 * mb[200 + d] + w2 * mb[400 + d] + w3 * mb[600 + d];
            }
            float L = w0 * mb[1] + w1 * mb[201] + w2 * mb[401] + w3 * mb[601];
            const uint32_t tiles = __float_as_int(mb[2]) + __float_as_int(mb[402]);
            st_pk16(dst + lane, __float_as_uint(o[0]), __float_as_uint(o[1]), __float_as_uint(o[2]), tag);
            st_pk16(dst + 32 + lane, __float_as_uint(o[3]), __float_as_uint(o[4]), __float_as_uint(o[5]), tag);
            if (lane == 0) st_pk16(&g_hdr[head][idx], __float_as_uint(M), __float_as_uint(L), tiles, tag);
            __syncwarp();
            if (lane == 0) mbar_arrive(BAR(B_FLE + fb));
            if (++fb == NBUF) { fb = 0; fpar ^= 1; }
            if (meta[16 + f + 1] == 0xFFu) break;
        }
        TS(8);
        CLK(18);
    } else if (wid == 5) {
        if (cta < 128) {
            if (lane < 2) st_zero16(&g_es[cta][lane]);
#pragma unroll 1
            for (int i = lane; i < 256; i += 32) {
                st_zero16(cta >= 128 - NLATE ? &g_late[cta - (128 - NLATE)][i >> 1][i & 1] : &g_h1[i >> 1][cta][i & 1]);
                if (cta < 96) st_zero16(&g_h3[i >> 1][cta][i & 1]);
            }
        }
#pragma unroll 1
        for (int f = 0; f < NQH; f++) {
            const int head = f < GH ? grp * GH + f : NG * GH + (f - GH);
            const int idx = f < GH ? rank : cta;
            st_zero16(&g_dat[head][idx][lane]);
            st_zero16(&g_dat[head][idx][32 + lane]);
            if (lane == 0) st_zero16(&g_hdr[head][idx]);
        }
        __syncwarp();
        if (lane == 0) mbar_arrive(BAR(B_CLR));
    } else {
        if (cta < 128) {
            const int t = tid - 192;
            uint32_t* cb32 = reinterpret_cast<uint32_t*>(smem + SM_CB);
            uint32_t* sb32 = reinterpret_cast<uint32_t*>(smem + SM_SB);
            uint32_t* ga32 = reinterpret_cast<uint32_t*>(smem + SM_GA);
            const int col = cta * 5 + t;
            int off[16];
            uint32_t val[16];
#pragma unroll
            for (int rep = 0; rep < 5; rep++) { off[3 * rep] = 960 + t + 64 * rep; off[3 * rep + 1] = 1280 + t + 64 * rep; off[3 * rep + 2] = 640 + t + 64 * rep; }
            off[15] = t < 5 ? (3200 + col) >> 1 : 960;
            poll8<16>(g_mod, off, val, tag);
#pragma unroll
            for (int rep = 0; rep < 5; rep++) {
                sb32[t + 64 * rep] = val[3 * rep];
                cb32[t + 64 * rep] = pack_bf(1.0f + bf_lo(val[3 * rep + 1]), 1.0f + bf_hi(val[3 * rep + 1]));
                ga32[t + 64 * rep] = val[3 * rep + 2];
            }
            if (t < 5) own[8 + t] = (col & 1) ? bf_hi(val[15]) : bf_lo(val[15]);
        }
        live = false;
    }
    }
    const uint32_t sb0 = sb;
    const int tid0 = tid;
#pragma unroll 1
    while (cta < 128) {
        uint32_t sb = sb0; int tid = tid0;
        asm volatile("" : "+r"(sb), "+r"(tid));
        const int wid = tid >> 5, lane = tid & 31;
        const int g4 = lane >> 2, j4 = lane & 3, mi = lane >> 3, l8 = lane & 7;
        CLK(19);
        if (wid >= 5) {
            const int h = cta >> 2, js = cta & 3;
            const bool gl = h >= NG * GH;
            const int ncand = gl ? G : (G - h / GH + NG - 1) / NG;
            const int k = lane & 15, rr = (wid - 5) * 2 + (lane >> 4);
            if (live) {
                const unsigned* cp = &g_ctr[(tag - 1) & 1][(gl ? NG : h / GH) * 32];
                const unsigned thr = ((gl ? h - NG * GH : h % GH) + 1) * TPH;
                uint32_t it = 0;
                while (true) {
                    unsigned v;
                    asm volatile("ld.relaxed.gpu.global.u32 %0, [%1];" : "=r"(v) : "l"(cp) : "memory");
                    if (v >= thr) break;
                    __nanosleep(300);
                    if (++it > SPIN_LIMIT) __trap();
                }
            }
            const uint4* hdr = &g_hdr[h][lane];
            const uint4* dat = &g_dat[h][rr][16 * js + k];
            float* part = stage;
            float L, a0, a1, a2;
            uint32_t it = 0;
            uint4 hd[5], dv[MAXG / 6];
#pragma unroll
            for (int i = 0; i < 5; i++) hd[i] = make_uint4(0, 0, 0, 0);
#pragma unroll
            for (int i = 0; i < MAXG / 6; i++) dv[i] = make_uint4(0, 0, 0, 0);
#pragma unroll 1
            while (true) {
                FreshN<5, 32>::run(hd, hdr, tag, live, lane, 32, ncand);
                FreshN<MAXG / 6, 6 * 64>::run(dv, dat, tag, live, rr, 6, ncand);
                float w[5], M = NEG_BIG;
                int c = 0;
#pragma unroll
                for (int i = 0; i < 5; i++) {
                    const bool v = hd[i].w == tag;
                    w[i] = v ? __uint_as_float(hd[i].x) : NEG_BIG;
                    M = fmaxf(M, w[i]);
                    c += v ? (int)hd[i].z : 0;
                }
                c = __reduce_add_sync(0xffffffffu, c);
                if (++it > SPIN_LIMIT) __trap();
                if (live && c != TPH) continue;
                CLK(1);
                M = warp_max(M);
                float ls = 0.f;
#pragma unroll
                for (int i = 0; i < 5; i++) {
                    const bool v = w[i] != NEG_BIG;
                    const float e = ex2((w[i] - M) * LOG2E);
                    w[i] = v ? e : -0.0f;
                    ls = fmaf(w[i], __uint_as_float(hd[i].y), ls);
                }
                float* wsm = reinterpret_cast<float*>(smem + SM_X2) + (wid - 5) * 160;
                if (live) {
#pragma unroll
                    for (int i = 0; i < 5; i++) wsm[lane + 32 * i] = w[i];
                }
                __syncwarp();
                L = warp_sum(ls);
                uint32_t badm = 0;
                a0 = a1 = a2 = 0.f;
#pragma unroll
                for (int i = 0; i < MAXG / 6; i++) {
                    const float wi = wsm[rr + 6 * i];
                    badm |= (dv[i].w ^ tag) & ~(uint32_t)(__float_as_int(wi) >> 31);
                    a0 = fmaf(wi, __uint_as_float(dv[i].x), a0);
                    a1 = fmaf(wi, __uint_as_float(dv[i].y), a1);
                    a2 = fmaf(wi, __uint_as_float(dv[i].z), a2);
                }
                const bool bad = badm != 0;
                if (!__any_sync(0xffffffffu, bad) || !live) break;
            }
            a0 += __shfl_xor_sync(0xffffffffu, a0, 16);
            a1 += __shfl_xor_sync(0xffffffffu, a1, 16);
            a2 += __shfl_xor_sync(0xffffffffu, a2, 16);
            CLK(2);
            if (live && lane < 16) { float* pp = part + (wid - 5) * 48 + 3 * k; pp[0] = a0; pp[1] = a1; pp[2] = a2; }
            if (live) asm volatile("bar.sync 2, 96;" ::: "memory");
            if (wid == 5 || !live) {
                uint16_t* osw = reinterpret_cast<uint16_t*>(smem + SM_SC);
                const float inv = __fdividef(1.0f, L);
                const float o0 = (part[lane] + part[48 + lane]) + part[96 + lane];
                const float o1 = (part[32 + (lane & 15)] + part[80 + (lane & 15)]) + part[128 + (lane & 15)];
                if (live) { osw[lane] = (uint16_t)(__float_as_uint(bfr(o0 * inv)) >> 16); if (lane < 16) osw[32 + lane] = (uint16_t)(__float_as_uint(bfr(o1 * inv)) >> 16); }
            }
            if (live) TS(10);
        }
        if (wid < 5 || !live) {
            const int w5 = wid < 5 ? wid : wid - 5;
            uint32_t wa[8][3][4];
            if (live) mbar_wait(BAR(B_WO + w5), 0);
#pragma unroll
            for (int i = 0; i < 8; i++) {
                const int cc = 2 * (i & 3) + (mi & 1);
#pragma unroll
                for (int ks = 0; ks < 3; ks++) {
                    const int r = ks * 16 + l8 + 8 * (mi >> 1);
                    ldsm4t(wa[i][ks], sb + SM_WO + (2 * w5 + (i >> 2)) * 6144 + r * 128 + ((cc ^ (r & 7)) << 4));
                }
            }
            if (live) bar_cons();
            if (live) TS(9);
            CLK(3);
            const uint32_t* os32 = reinterpret_cast<const uint32_t*>(smem + SM_SC);
            float acc[8][4] = {};
#pragma unroll
            for (int ks = 0; ks < 3; ks++) {
                const uint32_t b0 = os32[ks * 8 + j4], b1 = os32[ks * 8 + 4 + j4];
#pragma unroll
                for (int i = 0; i < 8; i++) mma16816(acc[i], wa[i][ks], b0, b1);
            }
            if (live && j4 == 0) {
#pragma unroll
                for (int i = 0; i < 8; i++) { stage[(w5 * 8 + i) * 16 + g4] = acc[i][0]; stage[(w5 * 8 + i) * 16 + 8 + g4] = acc[i][2]; }
            }
        } else {
            bar_cons();
        }
        CLK(4);
        if (live) bar_cons();
        {
            const int o = tid >> 1, kk = tid & 1;
            const float* sp = stage + o * 5 + kk * 3;
            float v0 = sp[0], v1 = sp[1], v2 = kk ? 0.f : sp[2];
            uint4* dst = cta >= 128 - NLATE ? &g_late[cta - (128 - NLATE)][o][kk] : &g_h1[o][cta][kk];
            if (live) st_pk16(dst, __float_as_uint(v0), __float_as_uint(v1), __float_as_uint(v2), tag);
        }
        if (live) TS(11);
        CLK(5);
        if (wid == 0 || !live) {
            const uint4* p = &g_h1[cta][0][0] + lane;
            uint4 v[8];
#pragma unroll
            for (int j = 0; j < 8; j++) v[j] = make_uint4(0, 0, 0, 0);
            if (lane >= 32 - 2 * NLATE) v[7].w = tag;
            uint32_t it = 0;
            while (true) {
                FreshN<8, 32>::run(v, p, tag, live, 0, 0, 1);
                bool ok = true;
#pragma unroll
                for (int j = 0; j < 8; j++) ok = ok && v[j].w == tag;
                if (__all_sync(0xffffffffu, ok) || !live) break;
                if (++it > SPIN_LIMIT) __trap();
            }
            CLK(6);
            float a0, a1, a2;
            a0 = ((__uint_as_float(v[0].x) + __uint_as_float(v[1].x)) + (__uint_as_float(v[2].x) + __uint_as_float(v[3].x))) +
                 ((__uint_as_float(v[4].x) + __uint_as_float(v[5].x)) + (__uint_as_float(v[6].x) + __uint_as_float(v[7].x)));
            a1 = ((__uint_as_float(v[0].y) + __uint_as_float(v[1].y)) + (__uint_as_float(v[2].y) + __uint_as_float(v[3].y))) +
                 ((__uint_as_float(v[4].y) + __uint_as_float(v[5].y)) + (__uint_as_float(v[6].y) + __uint_as_float(v[7].y)));
            a2 = ((__uint_as_float(v[0].z) + __uint_as_float(v[1].z)) + (__uint_as_float(v[2].z) + __uint_as_float(v[3].z))) +
                 ((__uint_as_float(v[4].z) + __uint_as_float(v[5].z)) + (__uint_as_float(v[6].z) + __uint_as_float(v[7].z)));
#pragma unroll
            for (int o = 2; o <= 16; o <<= 1) {
                a0 += __shfl_xor_sync(0xffffffffu, a0, o);
                a1 += __shfl_xor_sync(0xffffffffu, a1, o);
                a2 += __shfl_xor_sync(0xffffffffu, a2, o);
            }
            if (live && lane < 2) st_pk16(&g_es[cta][lane], __float_as_uint(a0), __float_as_uint(a1), __float_as_uint(a2), tag);
            if (live) TS(13);
        }
        CLK(8);
        float* x2s = reinterpret_cast<float*>(smem + SM_X2);
        {
            uint32_t a1[5][4], a3[5][4];
            if (live && cta < 96) mbar_wait3(BAR(B_W1 + (wid >> 2)), BAR(B_W3 + (wid >> 2)), BAR(B_W1 + (wid >> 2)));
#pragma unroll
            for (int ks = 0; ks < 5; ks++) {
                const int r = wid * 80 + ks * 16 + l8 + 8 * (mi >> 1);
                const uint32_t off = r * 32 + (((mi & 1) ^ ((r >> 2) & 1)) << 4);
                ldsm4t(a1[ks], sb + SM_W1 + off);
                ldsm4t(a3[ks], sb + SM_W3 + off);
            }
            CLK(9);
            const int o = tid >> 1, k = tid & 1, c0 = 5 * o + 3 * k;
            const uint16_t* x16 = reinterpret_cast<const uint16_t*>(smem + SM_X);
            const uint16_t* ga16 = reinterpret_cast<const uint16_t*>(smem + SM_GA);
            const uint16_t* cb16 = reinterpret_cast<const uint16_t*>(smem + SM_CB);
            const uint16_t* sb16 = reinterpret_cast<const uint16_t*>(smem + SM_SB);
            float xin[3], gin[3], cin[3], sin_[3];
#pragma unroll
            for (int e = 0; e < 3; e++) {
                const int c = c0 + ((e == 2 && k) ? 1 : e);
                xin[e] = __uint_as_float((uint32_t)x16[c] << 16); gin[e] = __uint_as_float((uint32_t)ga16[c] << 16);
                cin[e] = __uint_as_float((uint32_t)cb16[c] << 16); sin_[e] = __uint_as_float((uint32_t)sb16[c] << 16);
            }
            uint4 v[1 + NLATE];
#pragma unroll
            for (int j = 0; j <= NLATE; j++) v[j] = make_uint4(0, 0, 0, 0);
            const uint4* pe = &g_es[o][k];
            const uint4* pl = &g_late[0][o][k];
            uint32_t it = 0;
            while (true) {
                ld_fresh16<0>(v[0], pe, tag, live);
                FreshN<NLATE, 256>::run(v + 1, pl, tag, live, 0, 0, 1);
                bool ok = true;
#pragma unroll
                for (int j = 0; j <= NLATE; j++) ok = ok && v[j].w == tag;
                if (__all_sync(0xffffffffu, ok) || !live) break;
                if (++it > SPIN_LIMIT) __trap();
            }
            float x2[3];
            x2[0] = (__uint_as_float(v[0].x) + (__uint_as_float(v[1].x) + __uint_as_float(v[2].x))) + (__uint_as_float(v[3].x) + __uint_as_float(v[4].x));
            x2[1] = (__uint_as_float(v[0].y) + (__uint_as_float(v[1].y) + __uint_as_float(v[2].y))) + (__uint_as_float(v[3].y) + __uint_as_float(v[4].y));
            x2[2] = (__uint_as_float(v[0].z) + (__uint_as_float(v[1].z) + __uint_as_float(v[2].z))) + (__uint_as_float(v[3].z) + __uint_as_float(v[4].z));
#pragma unroll
            for (int e = 0; e < 3; e++) x2[e] = bfr(xin[e] + bfr(gin[e] * bfr(x2[e])));
            if (live && o == cta) { x2s[3 * k] = x2[0]; x2s[3 * k + 1] = x2[1]; if (!k) x2s[2] = x2[2]; }
            float* st8 = red + 256;
            {
                const float pv = __shfl_sync(0xffffffffu, x2[0], 0);
                const float d0 = x2[0] - pv, d1 = x2[1] - pv, d2 = k ? 0.f : x2[2] - pv;
                float s1 = (d0 + d1) + d2;
                float s2 = fmaf(d0, d0, fmaf(d1, d1, d2 * d2));
#pragma unroll
                for (int q = 16; q > 0; q >>= 1) { s1 += __shfl_xor_sync(0xffffffffu, s1, q); s2 += __shfl_xor_sync(0xffffffffu, s2, q); }
                if (live && lane == 0) { st8[wid] = pv + s1 * (1.0f / 80.0f); st8[8 + wid] = s2 - s1 * s1 * (1.0f / 80.0f); }
            }
            if (live) bar_cons();
            if (live) TS(14);
            CLK(10);
            if (cta < 96) {
            const float4 mA = *reinterpret_cast<const float4*>(st8), mB = *reinterpret_cast<const float4*>(st8 + 4);
            const float4 qA = *reinterpret_cast<const float4*>(st8 + 8), qB = *reinterpret_cast<const float4*>(st8 + 12);
            const float mean = (((mA.x + mA.y) + (mA.z + mA.w)) + ((mB.x + mB.y) + (mB.z + mB.w))) * 0.125f;
            const float u0 = mA.x - mean, u1 = mA.y - mean, u2 = mA.z - mean, u3 = mA.w - mean;
            const float u4 = mB.x - mean, u5 = mB.y - mean, u6 = mB.z - mean, u7 = mB.w - mean;
            const float m2 = (((qA.x + qA.y) + (qA.z + qA.w)) + ((qB.x + qB.y) + (qB.z + qB.w))) +
                             80.0f * (((u0 * u0 + u1 * u1) + (u2 * u2 + u3 * u3)) + ((u4 * u4 + u5 * u5) + (u6 * u6 + u7 * u7)));
            const float mean_b = bfr(mean);
            const float rden = __fdividef(1.0f, bfr(fsqrt(bfr(bfr(m2 * (1.0f / 640.0f)) + 1e-5f))));
            {
                uint16_t* h16 = reinterpret_cast<uint16_t*>(smem + SM_H);
#pragma unroll
                for (int e = 0; e < 3; e++) {
                    const float n = bfr(bfr(x2[e] - mean_b) * rden);
                    const float hv = bfr(bfr(n * cin[e]) + sin_[e]);
                    if (live && !(e == 2 && k)) h16[c0 + e] = (uint16_t)(__float_as_uint(hv) >> 16);
                }
            }
            __syncwarp();
            CLK(11);
            float ag[2][4] = {}, au[2][4] = {};
#pragma unroll
            for (int ks = 0; ks < 5; ks++) {
                const int r0 = wid * 80 + ks * 16;
                const uint32_t b0 = h32[(r0 >> 1) + j4], b1 = h32[(r0 >> 1) + 4 + j4];
                mma16816(ag[ks & 1], a1[ks], b0, b1);
                mma16816(au[ks & 1], a3[ks], b0, b1);
            }
            if (live && j4 == 0) {
                red[wid * 32 + g4] = ag[0][0] + ag[1][0]; red[wid * 32 + 8 + g4] = ag[0][2] + ag[1][2];
                red[wid * 32 + 16 + g4] = au[0][0] + au[1][0]; red[wid * 32 + 24 + g4] = au[0][2] + au[1][2];
            }
            uint32_t a2[5][4];
            if (live) mbar_wait(BAR(B_W2 + (wid >> 2)), 0);
            const uint32_t w2b = sb + SM_RING + meta[10 + (wid >> 2)] % NSLOT * CHUNK;
#pragma unroll
            for (int i = 0; i < 5; i++) {
                const int mt = (wid & 3) * 5 + i;
                const int cc = 2 * (mt & 3) + (mi & 1);
                const int r = l8 + 8 * (mi >> 1);
                ldsm4t(a2[i], w2b + (mt >> 2) * 2048 + r * 128 + ((cc ^ (r & 7)) << 4));
            }
            CLK(12);
            if (live) bar_cons();
            if (live) TS(15);
            CLK(13);
            float v = 0.f;
#pragma unroll
            for (int w = 0; w < 8; w++) v += red[w * 32 + lane];
            v = bfr(v);
            float up = __shfl_down_sync(0xffffffffu, v, 16);
            float hact = bfr(bfr(silu(v)) * up);
            float e0 = __shfl_sync(0xffffffffu, hact, 2 * j4), e1 = __shfl_sync(0xffffffffu, hact, 2 * j4 + 1);
            float e2 = __shfl_sync(0xffffffffu, hact, 2 * j4 + 8), e3 = __shfl_sync(0xffffffffu, hact, 2 * j4 + 9);
            const uint32_t b0 = pack_bf(e0, e1), b1 = pack_bf(e2, e3);
            float acc[5][4] = {};
#pragma unroll
            for (int i = 0; i < 5; i++) mma16816(acc[i], a2[i], b0, b1);
            if (live && j4 == 0) {
#pragma unroll
                for (int i = 0; i < 5; i++) { stage[(wid * 5 + i) * 16 + g4] = acc[i][0]; stage[(wid * 5 + i) * 16 + 8 + g4] = acc[i][2]; }
            }
            CLK(14);
            if (live) bar_cons();
            const float* sp = stage + o * 5 + k * 3;
            float v0 = sp[0], v1 = sp[1], v2 = k ? 0.f : sp[2];
            if (live) st_pk16(&g_h3[o][cta][k], __float_as_uint(v0), __float_as_uint(v1), __float_as_uint(v2), tag);
            }
        }
        if (live) TS(16);
        CLK(15);
        if (wid == 0 || !live) {
            const uint4* p = &g_h3[cta][0][0] + lane;
            uint4 v[6];
            uint32_t it = 0;
            if (live && cta < 96) spin(P_DLY);
            while (true) {
                bool ok = true;
                LoadN<6, 32>::run(v, p, live, 0, 0, 1);
#pragma unroll
                for (int j = 0; j < 6; j++) ok = ok && v[j].w == tag;
                if (__all_sync(0xffffffffu, ok) || !live) break;
                if (++it > SPIN_LIMIT) __trap();
            }
            CLK(16);
            float a0 = 0.f, a1 = 0.f, a2 = 0.f;
#pragma unroll
            for (int j = 0; j < 6; j++) { a0 += __uint_as_float(v[j].x); a1 += __uint_as_float(v[j].y); a2 += __uint_as_float(v[j].z); }
#pragma unroll
            for (int o = 2; o <= 16; o <<= 1) {
                a0 += __shfl_xor_sync(0xffffffffu, a0, o);
                a1 += __shfl_xor_sync(0xffffffffu, a1, o);
                a2 += __shfl_xor_sync(0xffffffffu, a2, o);
            }
            const float gx = own[8 + (lane & 7)], xx = x2s[lane & 7];
            const float t0 = __shfl_sync(0xffffffffu, a0, lane >= 3), t1 = __shfl_sync(0xffffffffu, a1, lane >= 3);
            const float sum = (lane == 0 || lane == 3) ? t0 : (lane == 2 ? a2 : t1);
            const float y = xx + bfr(gx * bfr(sum));
            if (live && lane < 5) reinterpret_cast<uint16_t*>(out)[cta * 5 + lane] = (uint16_t)(__float_as_uint(bfr(y)) >> 16);
            if (live && cta == 0 && lane == 0) g_epoch = tag;
        }
        CLK(17);
        if (live) { TS(18); break; }
        live = true;
    }
    }
}

typedef CUresult (*EncodeFn)(CUtensorMap*, CUtensorMapDataType, cuuint32_t, void*, const cuuint64_t*, const cuuint64_t*,
                             const cuuint32_t*, const cuuint32_t*, CUtensorMapInterleave, CUtensorMapSwizzle,
                             CUtensorMapL2promotion, CUtensorMapFloatOOBfill);

void make_map(EncodeFn enc, CUtensorMap* tm, const void* ptr, uint64_t cols, uint64_t rows, uint32_t box_c, uint32_t box_r,
              CUtensorMapSwizzle sw, CUtensorMapL2promotion prom) {
    cuuint64_t dims[2] = {cols, rows};
    cuuint64_t strides[1] = {cols * 2};
    cuuint32_t box[2] = {box_c, box_r};
    cuuint32_t es[2] = {1, 1};
    enc(tm, CU_TENSOR_MAP_DATA_TYPE_BFLOAT16, 2, const_cast<void*>(ptr), dims, strides, box, es,
        CU_TENSOR_MAP_INTERLEAVE_NONE, sw, prom, CU_TENSOR_MAP_FLOAT_OOB_FILL_NONE);
}

}

extern "C" void kernel_launch(void* const* d_in, const int* in_sizes, int n_in, void* d_out, int out_size) {
    (void)in_sizes; (void)n_in; (void)out_size;
    static EncodeFn enc = nullptr;
    static int num_sms = 0;
    if (!enc) {
        void* fn = nullptr;
        cudaDriverEntryPointQueryResult qr;
        cudaGetDriverEntryPoint("cuTensorMapEncodeTiled", &fn, cudaEnableDefault, &qr);
        enc = (EncodeFn)fn;
        cudaDeviceGetAttribute(&num_sms, cudaDevAttrMultiProcessorCount, 0);
        cudaFuncSetAttribute(fused_decode_kernel, cudaFuncAttributeMaxDynamicSharedMemorySize, SM_TOTAL);
    }
    CUtensorMap tmK, tmV, tmMod, tmWq, tmWo, tmW1, tmW3, tmW2;
    const uint64_t kv_lines = (uint64_t)NH * SK * 3;
    make_map(enc, &tmK, d_in[1], 64, kv_lines, 64, 96, CU_TENSOR_MAP_SWIZZLE_128B, CU_TENSOR_MAP_L2_PROMOTION_L2_128B);
    make_map(enc, &tmV, d_in[2], 64, kv_lines, 64, 96, CU_TENSOR_MAP_SWIZZLE_128B, CU_TENSOR_MAP_L2_PROMOTION_L2_128B);
    make_map(enc, &tmWq, d_in[3], NH * DH, D, 48, 128, CU_TENSOR_MAP_SWIZZLE_NONE, CU_TENSOR_MAP_L2_PROMOTION_L2_128B);
    make_map(enc, &tmWo, d_in[4], D, NH * DH, 64, 48, CU_TENSOR_MAP_SWIZZLE_128B, CU_TENSOR_MAP_L2_PROMOTION_L2_128B);
    make_map(enc, &tmW1, d_in[6], FF, D, 16, 160, CU_TENSOR_MAP_SWIZZLE_32B, CU_TENSOR_MAP_L2_PROMOTION_L2_128B);
    make_map(enc, &tmW3, d_in[7], FF, D, 16, 160, CU_TENSOR_MAP_SWIZZLE_32B, CU_TENSOR_MAP_L2_PROMOTION_L2_128B);
    make_map(enc, &tmW2, d_in[8], D, FF, 64, 16, CU_TENSOR_MAP_SWIZZLE_128B, CU_TENSOR_MAP_L2_PROMOTION_L2_128B);
    make_map(enc, &tmMod, d_in[10], 6 * D, D, 32, 160, CU_TENSOR_MAP_SWIZZLE_64B, CU_TENSOR_MAP_L2_PROMOTION_L2_128B);
    int grid = num_sms < MAXG ? num_sms : MAXG;
    fused_decode_kernel<<<grid, NTHREADS, SM_TOTAL, cudaStreamPerThread>>>(
        tmK, tmV, tmMod, tmWq, tmWo, tmW1, tmW3, tmW2, (const __nv_bfloat16*)d_in[0], (const __nv_bfloat16*)d_in[9],
        (__nv_bfloat16*)d_out);
}
```

```cpp
#include <cuda_runtime.h>
#include <cuda_bf16.h>
#include <cuda.h>
#include <stdint.h>

namespace {

constexpr int D = 640, NH = 32, SK = 8192, DH = 192, FF = 1536;
constexpr int NG = 4;
constexpr int GH = 7;
constexpr int NGLOB = NH - NG * GH;
constexpr int NQH = GH + NGLOB;
constexpr int TILE = 32;
constexpr int TPH = SK / TILE;
constexpr int GT = GH * TPH;
constexpr int PT = NGLOB * TPH;
constexpr int CHUNK = TILE * DH * 2;
constexpr int NSLOT = 8;
constexpr int WIN = 3;
constexpr int WPRO = 4;
constexpr int POLL_DELAY = 450;
constexpr int NBUF = 2;
constexpr int NLATE = 4;
constexpr int MAXG = 132;
constexpr int NTHREADS = 288;
constexpr float NEG_BIG = -3.402823466e38f;

constexpr int SM_WMOD = 0;
constexpr int SM_WQ = 40960;
constexpr int SM_WO = 0;
constexpr int SM_W1 = 61440;
constexpr int SM_W3 = 81920;
constexpr int SM_RING = 102400;
constexpr int SM_MISC = SM_RING + NSLOT * CHUNK;
constexpr int SM_BARS = SM_MISC;
constexpr int SM_META = SM_BARS + 512;
constexpr int SM_Q = SM_META + 128;
constexpr int SM_SC = SM_Q + NQH * DH * 2;
constexpr int SM_H = SM_SC + 1280;
constexpr int SM_X = SM_H + 1280;
constexpr int SM_CB = SM_X + 1280;
constexpr int SM_SB = SM_CB + 1280;
constexpr int SM_GA = SM_SB + 1280;
constexpr int SM_OWN = SM_GA + 1280;
constexpr int SM_RED = SM_OWN + 128;
constexpr int SM_MERGE = SM_RED + 2048;
constexpr int SM_STAGE = SM_MERGE + NBUF * 3200;
constexpr int SM_X2 = SM_STAGE + 2560;
constexpr int SM_FIN = SM_X2 + 2560;
constexpr int SM_TOTAL = SM_FIN + 512;
static_assert(SM_TOTAL <= 232448, "shared memory budget");

constexpr int B_FULL = 0;
constexpr int B_EMPTY = 8;
constexpr int B_MOD = 16;
constexpr int B_WQ = 20;
constexpr int B_WO = 25;
constexpr int B_W1 = 30;
constexpr int B_W3 = 32;
constexpr int B_W2 = 34;
constexpr int B_PRO = 36, B_DUMMY = 37, B_CLR = 38;
constexpr int B_FLF = 40, B_FLE = 44;
constexpr int B_LAST = 48;
static_assert(NSLOT <= 8 && NSLOT >= 6 && WIN <= WPRO && WIN <= NSLOT - 3 && NBUF <= 4, "barrier map / end markers vs window");
constexpr uint32_t META_END = 0x10000u;

__device__ unsigned g_epoch;
__device__ unsigned g_ctr[2][(NG + 1) * 32];
__device__ __align__(128) unsigned long long g_mod[1920];
__device__ __align__(128) unsigned long long g_q[3072];
__device__ __align__(128) uint4 g_hdr[NH][MAXG];
__device__ __align__(128) uint4 g_dat[NH][MAXG][64];
__device__ __align__(128) uint4 g_h1[128][128][2];
__device__ __align__(128) uint4 g_es[128][2];
__device__ __align__(128) uint4 g_late[NLATE][128][2];
__device__ __align__(128) uint4 g_h3[128][96][2];


__device__ __forceinline__ uint32_t smem_u32(const void* p) { return (uint32_t)__cvta_generic_to_shared(p); }
__device__ __forceinline__ void mbar_init(uint32_t bar, uint32_t cnt) {
    asm volatile("mbarrier.init.shared::cta.b64 [%0], %1;" ::"r"(bar), "r"(cnt) : "memory");
}
__device__ __forceinline__ void mbar_expect_tx(uint32_t bar, uint32_t bytes) {
    asm volatile("mbarrier.arrive.expect_tx.shared::cta.b64 _, [%0], %1;" ::"r"(bar), "r"(bytes) : "memory");
}
__device__ __forceinline__ void mbar_arrive(uint32_t bar) {
    asm volatile("mbarrier.arrive.shared::cta.b64 _, [%0];" ::"r"(bar) : "memory");
}
constexpr uint32_t SPIN_LIMIT = 1u << 22;
__device__ __forceinline__ void mbar_wait(uint32_t bar, uint32_t parity) {
    asm volatile(
        "{\n.reg .pred p;\n.reg .u32 c;\nmov.u32 c, 0;\n"
        "LW:\nmbarrier.try_wait.parity.shared::cta.b64 p, [%0], %1;\n@p bra LD;\n"
        "add.u32 c, c, 1;\nsetp.lt.u32 p, c, 0x400000;\n@p bra LW;\ntrap;\nLD:\n}" ::"r"(bar), "r"(parity)
        : "memory");
}
__device__ __forceinline__ uint32_t mbar_try(uint32_t bar, uint32_t parity) {
    uint32_t ok;
    asm volatile("{\n.reg .pred p;\nmbarrier.try_wait.parity.shared::cta.b64 p, [%1], %2;\nselp.u32 %0, 1, 0, p;\n}"
                 : "=r"(ok) : "r"(bar), "r"(parity) : "memory");
    return ok;
}
__device__ __forceinline__ void mbar_wait3(uint32_t b0, uint32_t b1, uint32_t b2) {
    asm volatile(
        "{\n.reg .pred p, q, r;\n.reg .u32 c;\nmov.u32 c, 0;\n"
        "LW:\nmbarrier.try_wait.parity.shared::cta.b64 p, [%0], 0;\n"
        "mbarrier.try_wait.parity.shared::cta.b64 q, [%1], 0;\n"
        "mbarrier.try_wait.parity.shared::cta.b64 r, [%2], 0;\n"
        "and.pred p, p, q;\nand.pred p, p, r;\n@p bra LD;\n"
        "add.u32 c, c, 1;\nsetp.lt.u32 p, c, 0x400000;\n@p bra LW;\ntrap;\nLD:\n}" ::"r"(b0), "r"(b1), "r"(b2)
        : "memory");
}
__device__ __forceinline__ void tma2d(uint32_t dst, const CUtensorMap* tm, int c0, int c1, uint32_t bar) {
    asm volatile(
        "cp.async.bulk.tensor.2d.shared::cluster.global.mbarrier::complete_tx::bytes [%0], [%1, {%3, %4}], [%2];" ::"r"(dst),
        "l"(tm), "r"(bar), "r"(c0), "r"(c1)
        : "memory");
}
__device__ __forceinline__ void tma2d_hint(uint32_t dst, const CUtensorMap* tm, int c0, int c1, uint32_t bar, uint64_t pol) {
    asm volatile(
        "cp.async.bulk.tensor.2d.shared::cluster.global.mbarrier::complete_tx::bytes.L2::cache_hint [%0], [%1, {%3, %4}], [%2], %5;" ::"r"(dst),
        "l"(tm), "r"(bar), "r"(c0), "r"(c1), "l"(pol)
        : "memory");
}
__device__ __forceinline__ void prefetch_tm(const CUtensorMap* tm) {
    asm volatile("prefetch.tensormap [%0];" ::"l"(tm) : "memory");
}
__device__ __forceinline__ void ldsm4(uint32_t (&r)[4], uint32_t addr) {
    asm volatile("ldmatrix.sync.aligned.m8n8.x4.shared.b16 {%0,%1,%2,%3}, [%4];"
                 : "=r"(r[0]), "=r"(r[1]), "=r"(r[2]), "=r"(r[3])
                 : "r"(addr));
}
__device__ __forceinline__ void ldsm4t(uint32_t (&r)[4], uint32_t addr) {
    asm volatile("ldmatrix.sync.aligned.m8n8.x4.trans.shared.b16 {%0,%1,%2,%3}, [%4];"
                 : "=r"(r[0]), "=r"(r[1]), "=r"(r[2]), "=r"(r[3])
                 : "r"(addr));
}
__device__ __forceinline__ void mma16816(float (&d)[4], const uint32_t (&a)[4], uint32_t b0, uint32_t b1) {
    asm volatile(
        "mma.sync.aligned.m16n8k16.row.col.f32.bf16.bf16.f32 {%0,%1,%2,%3}, {%4,%5,%6,%7}, {%8,%9}, {%0,%1,%2,%3};"
        : "+f"(d[0]), "+f"(d[1]), "+f"(d[2]), "+f"(d[3])
        : "r"(a[0]), "r"(a[1]), "r"(a[2]), "r"(a[3]), "r"(b0), "r"(b1));
}
__device__ __forceinline__ void bar_cons() { asm volatile("bar.sync 1, 256;" ::: "memory"); }
__device__ __forceinline__ void spin(int cycles) {
    long long t0 = clock64();
    while (clock64() - t0 < cycles) {}
}

__device__ __forceinline__ float bfr(float x) {
    uint32_t r;
    asm("cvt.rn.bf16x2.f32 %0, %1, %2;" : "=r"(r) : "f"(x), "f"(0.0f));
    return __uint_as_float(r);
}
__device__ __forceinline__ uint32_t pack_bf(float lo, float hi) {
    __nv_bfloat162 t = __floats2bfloat162_rn(lo, hi);
    return *reinterpret_cast<uint32_t*>(&t);
}
__device__ __forceinline__ float bf_lo(uint32_t v) { return __uint_as_float(v << 16); }
__device__ __forceinline__ float bf_hi(uint32_t v) { return __uint_as_float(v & 0xffff0000u); }

__device__ __forceinline__ void st_pk8(unsigned long long* p, uint32_t v, uint32_t tag) {
    unsigned long long w = ((unsigned long long)tag << 32) | v;
    asm volatile("st.relaxed.gpu.global.b64 [%0], %1;" ::"l"(p), "l"(w) : "memory");
}
template <int N>
__device__ __forceinline__ void poll8(const unsigned long long* base, const int (&off)[N], uint32_t (&val)[N], uint32_t tag) {
    uint32_t tg[N];
#pragma unroll
    for (int i = 0; i < N; i++) { val[i] = 0; tg[i] = 0; }
    uint32_t it = 0;
    while (true) {
#pragma unroll
        for (int i = 0; i < N; i++) {
            asm volatile("{\n.reg .pred q;\n.reg .b64 t;\nsetp.ne.u32 q, %1, %3;\nmov.b64 t, {%0, %1};\n"
                             "@q ld.relaxed.gpu.global.b64 t, [%2];\nmov.b64 {%0, %1}, t;\n}"
                             : "+r"(val[i]), "+r"(tg[i]) : "l"(base + off[i]), "r"(tag) : "memory");
        }
        bool ok = true;
#pragma unroll
        for (int i = 0; i < N; i++) ok = ok && tg[i] == tag;
        if (__all_sync(0xffffffffu, ok)) break;
        if (++it > SPIN_LIMIT) __trap();
        __nanosleep(100);
    }
}
__device__ __forceinline__ void st_pk16(uint4* p, uint32_t a, uint32_t b, uint32_t c, uint32_t tag) {
    asm volatile(
        "{\n.reg .b128 t;\n.reg .b64 lo, hi;\nmov.b64 lo, {%1, %2};\nmov.b64 hi, {%3, %4};\nmov.b128 t, {lo, hi};\n"
        "st.relaxed.gpu.global.b128 [%0], t;\n}" ::"l"(p), "r"(a), "r"(b), "r"(c), "r"(tag)
        : "memory");
}
template <int OFF = 0>
__device__ __forceinline__ uint4 ld_raw16p(const uint4* p, uint32_t on) {
    uint4 v;
    asm volatile(
        "{\n.reg .b128 t;\n.reg .b64 lo, hi;\n.reg .pred q;\nsetp.ne.u32 q, %5, 0;\n"
        "mov.b64 lo, 0;\nmov.b128 t, {lo, lo};\n"
        "@q ld.relaxed.gpu.global.b128 t, [%4 + %6];\nmov.b128 {lo, hi}, t;\n"
        "mov.b64 {%0, %1}, lo;\nmov.b64 {%2, %3}, hi;\n}"
        : "=r"(v.x), "=r"(v.y), "=r"(v.z), "=r"(v.w)
        : "l"(p), "r"(on), "n"(OFF * 16)
        : "memory");
    return v;
}
template <int OFF>
__device__ __forceinline__ void ld_fresh16(uint4& v, const uint4* p, uint32_t tag, uint32_t on) {
    asm volatile(
        "{\n.reg .b128 t;\n.reg .b64 lo, hi;\n.reg .pred q;\nsetp.ne.u32 q, %3, %5;\nsetp.ne.and.u32 q, %6, 0, q;\n"
        "mov.b64 lo, {%0, %1};\nmov.b64 hi, {%2, %3};\nmov.b128 t, {lo, hi};\n"
        "@q ld.relaxed.gpu.global.b128 t, [%4 + %7];\nmov.b128 {lo, hi}, t;\n"
        "mov.b64 {%0, %1}, lo;\nmov.b64 {%2, %3}, hi;\n}"
        : "+r"(v.x), "+r"(v.y), "+r"(v.z), "+r"(v.w)
        : "l"(p), "r"(tag), "r"(on), "n"(OFF * 16)
        : "memory");
}
template <int N, int STRIDE, int I = 0>
struct FreshN {
    static __device__ __forceinline__ void run(uint4* v, const uint4* p, uint32_t tag, bool live, int base, int step, int lim) {
        ld_fresh16<I * STRIDE>(v[I], p, tag, live && base + step * I < lim);
        FreshN<N, STRIDE, I + 1>::run(v, p, tag, live, base, step, lim);
    }
};
template <int N, int STRIDE>
struct FreshN<N, STRIDE, N> {
    static __device__ __forceinline__ void run(uint4*, const uint4*, uint32_t, bool, int, int, int) {}
};
template <int N, int STRIDE, int I = 0>
struct LoadN {
    static __device__ __forceinline__ void run(uint4* v, const uint4* p, bool live, int base, int step, int lim) {
        v[I] = ld_raw16p<I * STRIDE>(p, live && base + step * I < lim);
        LoadN<N, STRIDE, I + 1>::run(v, p, live, base, step, lim);
    }
};
template <int N, int STRIDE>
struct LoadN<N, STRIDE, N> {
    static __device__ __forceinline__ void run(uint4*, const uint4*, bool, int, int, int) {}
};
__device__ __forceinline__ void st_zero16(void* p) {
    asm volatile("st.relaxed.gpu.global.v4.u32 [%0], {%1, %1, %1, %1};" ::"l"(p), "r"(0u) : "memory");
}
__device__ __forceinline__ float ex2(float x) {
    float y;
    asm("ex2.approx.ftz.f32 %0, %1;" : "=f"(y) : "f"(x));
    return y;
}
__device__ __forceinline__ float fsqrt(float x) {
    float y;
    asm("sqrt.approx.f32 %0, %1;" : "=f"(y) : "f"(x));
    return y;
}
constexpr float LOG2E = 1.4426950408889634f;
__device__ __forceinline__ float silu(float a) { return __fdividef(a, 1.0f + ex2(-a * LOG2E)); }
__device__ __forceinline__ float warp_max(float v) {
    int k = __float_as_int(v);
    k ^= (k >> 31) & 0x7fffffff;
    k = __reduce_max_sync(0xffffffffu, k);
    k ^= (k >> 31) & 0x7fffffff;
    return __int_as_float(k);
}
__device__ __forceinline__ float warp_sum(float v) {
#pragma unroll
    for (int o = 16; o > 0; o >>= 1) v += __shfl_xor_sync(0xffffffffu, v, o);
    return v;
}

__device__ __forceinline__ void ln_stats(const float (&v)[20], float& mean_b, float& den_b) {
    float s = 0.f;
#pragma unroll
    for (int i = 0; i < 20; i++) s += v[i];
    s = warp_sum(s);
    float mean = s * (1.0f / 640.0f);
    float q = 0.f;
#pragma unroll
    for (int i = 0; i < 20; i++) { float d = v[i] - mean; q += d * d; }
    q = warp_sum(q);
    float var_b = bfr(q * (1.0f / 640.0f));
    mean_b = bfr(mean);
    den_b = bfr(fsqrt(bfr(var_b + 1e-5f)));
}

struct Window {
    uint32_t bar[WPRO];
    uint32_t par[WPRO];
    __device__ __forceinline__ void init(uint32_t dummy) {
#pragma unroll
        for (int i = 0; i < WPRO; i++) { bar[i] = dummy; par[i] = 1; }
    }
    __device__ __forceinline__ void push(uint32_t b, uint32_t p, bool wait = true, bool deep = false) {
        if (wait) mbar_wait(deep ? bar[0] : bar[WPRO - WIN], deep ? par[0] : par[WPRO - WIN]);
#pragma unroll
        for (int i = 0; i + 1 < WPRO; i++) { bar[i] = bar[i + 1]; par[i] = par[i + 1]; }
        bar[WPRO - 1] = b; par[WPRO - 1] = p;
    }
};

__global__ void __launch_bounds__(NTHREADS, 1)
fused_decode_kernel(const __grid_constant__ CUtensorMap tmK, const __grid_constant__ CUtensorMap tmV,
                    const __grid_constant__ CUtensorMap tmMod, const __grid_constant__ CUtensorMap tmWq,
                    const __grid_constant__ CUtensorMap tmWo, const __grid_constant__ CUtensorMap tmW1,
                    const __grid_constant__ CUtensorMap tmW3, const __grid_constant__ CUtensorMap tmW2,
                    const __nv_bfloat16* __restrict__ x_in, const __nv_bfloat16* __restrict__ c_in,
                    __nv_bfloat16* __restrict__ out) {
    extern __shared__ __align__(1024) uint8_t smem[];
    const uint32_t sb = smem_u32(smem);
    const int tid = threadIdx.x, wid = tid >> 5, lane = tid & 31;
    const int cta = blockIdx.x, G = gridDim.x;
    const int grp = cta % NG, rank = cta / NG;
    const uint32_t bars = sb + SM_BARS;
    auto BAR = [&](int i) { return bars + 8u * i; };
    volatile uint32_t* meta = reinterpret_cast<volatile uint32_t*>(smem + SM_META);

    uint32_t in_c0 = 0, in_x0 = 0, in_c1 = 0, in_x1 = 0, in_epoch = 0;
    {
        const bool mf = cta < 40;
        const int b0 = mf ? B_MOD : B_WQ;
        if (wid == 8) {
            if (lane == 0) {
#pragma unroll 1
                for (int i = 0; i < 4; i++) mbar_init(BAR(b0 + i), 1);
                asm volatile("fence.mbarrier_init.release.cluster;" ::: "memory");
                asm volatile("fence.proxy.async.shared::cta;" ::: "memory");
                if (cta < 128) {
                    const CUtensorMap* tm = mf ? &tmMod : &tmWq;
#pragma unroll 1
                    for (int i = 0; i < 4; i++) {
                        const uint32_t bar = BAR(b0 + i);
                        mbar_expect_tx(bar, mf ? 10240 : 12288);
                        tma2d(sb + (mf ? SM_WMOD + i * 10240 : SM_WQ + i * 12288), tm, cta * (mf ? 32 : 48), i * (mf ? 160 : 128), bar);
                    }
                }
                asm volatile("ld.relaxed.gpu.global.u32 %0, [%1];" : "=r"(in_epoch) : "l"(&g_epoch) : "memory");
            }
        } else {
            const uint32_t* cg = reinterpret_cast<const uint32_t*>(c_in);
            const uint32_t* xg = reinterpret_cast<const uint32_t*>(x_in);
            in_c0 = __ldg(cg + tid); in_x0 = __ldg(xg + tid);
            if (tid < 64) { in_c1 = __ldg(cg + 256 + tid); in_x1 = __ldg(xg + 256 + tid); }
            if (tid == 0) asm volatile("ld.relaxed.gpu.global.u32 %0, [%1];" : "=r"(in_epoch) : "l"(&g_epoch) : "memory");
            if (lane == 0) {
#pragma unroll 1
                for (int i = wid; i < B_LAST; i += 8) {
                    if (i >= b0 && i < b0 + 4) continue;
                    mbar_init(BAR(i), (i >= B_EMPTY && i < B_MOD) ? 2 : ((i >= B_FLF && i < B_FLE) ? 4 : 1));
                }
                asm volatile("fence.mbarrier_init.release.cluster;" ::: "memory");
                asm volatile("fence.proxy.async.shared::cta;" ::: "memory");
            }
        }
    }
    __syncwarp();
    __syncthreads();
    if (sb & 1023u) __trap();

    if (wid == 8) {
        if (tid == 256) {
            Window win;
            const unsigned epoch = in_epoch;
            prefetch_tm(&tmWq); prefetch_tm(&tmMod); prefetch_tm(&tmK); prefetch_tm(&tmV);
            const int nmod = cta < 120 ? 4 : 0, nwq = cta < 128 ? 5 : 0;
            win.init(BAR(B_DUMMY));
            prefetch_tm(&tmWo); prefetch_tm(&tmW1); prefetch_tm(&tmW3); prefetch_tm(&tmW2);
            unsigned* ctr = &g_ctr[epoch & 1][grp * 32];
            unsigned* gctr = &g_ctr[epoch & 1][NG * 32];
            if (cta == 0) {
                for (int g = 0; g <= NG; g++) g_ctr[(epoch + 1) & 1][g * 32] = 0;
            }
            unsigned pend = atomicAdd(ctr, 1);
#pragma unroll 1
            for (int i = 0; i < nmod + nwq; i++) {
                const bool is_mod = cta < 40 ? i < nmod : i >= nwq;
                const int j = cta < 40 ? (is_mod ? i : i - nmod) : (is_mod ? i - nwq : i);
                const uint32_t bar = BAR((is_mod ? B_MOD : B_WQ) + j);
                win.push(bar, 0, i >= 4, true);
                if (i >= 4) {
                    mbar_expect_tx(bar, is_mod ? 10240 : 12288);
                    if (is_mod) tma2d(sb + SM_WMOD + j * 10240, &tmMod, cta * 32, j * 160, bar);
                    else tma2d(sb + SM_WQ + j * 12288, &tmWq, cta * 48, j * 128, bar);
                }
            }
            uint64_t pol;
            asm volatile("createpolicy.fractional.L2::evict_first.b64 %0, 1.0;" : "=l"(pol));
            int s = 0; uint32_t par = 0;
            int run = -1, last_head = -1;
            bool glob = false;
#pragma unroll 1
            while (true) {
                unsigned t = pend;
                if (!glob && t >= (unsigned)GT) { glob = true; t = atomicAdd(gctr, 1); }
                if (glob && t >= (unsigned)PT) break;
                pend = atomicAdd(glob ? gctr : ctr, 1);
                const int hl = t / TPH, tile = t % TPH;
                const int head = glob ? NG * GH + hl : grp * GH + hl;
                const int qidx = glob ? GH + hl : hl;
                if (head != last_head) { last_head = head; run++; meta[16 + run] = head; }
                const int line0 = (head * SK + tile * TILE) * 3;
#pragma unroll 1
                for (int kv = 0; kv < 2; kv++) {
                    win.push(BAR(B_FULL + s), par);
                    mbar_wait(BAR(B_EMPTY + s), par ^ 1);
                    meta[s] = run | (qidx << 8);
                    mbar_expect_tx(BAR(B_FULL + s), CHUNK);
                    tma2d_hint(sb + SM_RING + s * CHUNK, kv ? &tmV : &tmK, 0, line0, BAR(B_FULL + s), pol);
                    if (++s == NSLOT) { s = 0; par ^= 1; }
                }
            }
            meta[16 + run + 1] = 0xFFu;
#pragma unroll 1
            for (int e = 0; e < 2; e++) {
                mbar_wait(BAR(B_EMPTY + s), par ^ 1);
                meta[s] = (run + 1) | META_END;
                mbar_arrive(BAR(B_FULL + s));
                if (++s == NSLOT) { s = 0; par ^= 1; }
                if (++s == NSLOT) { s = 0; par ^= 1; }
            }
            if (cta < 128) {
                mbar_wait(BAR(B_PRO), 0);
#pragma unroll 1
                for (int i = 0; i < 5; i++) {
                    win.push(BAR(B_WO + i), 0);
                    mbar_expect_tx(BAR(B_WO + i), 12288);
                    tma2d(sb + SM_WO + (2 * i) * 6144, &tmWo, (2 * i) * 64, cta * 48, BAR(B_WO + i));
                    tma2d(sb + SM_WO + (2 * i + 1) * 6144, &tmWo, (2 * i + 1) * 64, cta * 48, BAR(B_WO + i));
                }
                if (cta < 96) {
#pragma unroll 1
                    for (int i = 0; i < 4; i++) {
                        const int m = i & 1, hf = i >> 1;
                        const uint32_t bar = BAR((m ? B_W3 : B_W1) + hf);
                        const uint32_t dst = sb + (m ? SM_W3 : SM_W1) + hf * 10240;
                        const CUtensorMap* tm = m ? &tmW3 : &tmW1;
                        win.push(bar, 0);
                        mbar_expect_tx(bar, 10240);
                        tma2d(dst, tm, cta * 16, hf * 320, bar);
                        tma2d(dst + 5120, tm, cta * 16, hf * 320 + 160, bar);
                    }
#pragma unroll 1
                    for (int i = 0; i < 2; i++) {
                        win.push(BAR(B_W2 + i), 0);
                        mbar_wait(BAR(B_EMPTY + s), par ^ 1);
                        meta[10 + i] = s;
                        mbar_expect_tx(BAR(B_W2 + i), 10240);
#pragma unroll 1
                        for (int b = 0; b < 5; b++)
                            tma2d(sb + SM_RING + s * CHUNK + b * 2048, &tmW2, (5 * i + b) * 64, cta * 16, BAR(B_W2 + i));
                        if (++s == NSLOT) { s = 0; par ^= 1; }
                    }
                }
            }
        }
    } else {
    const int g4 = lane >> 2, j4 = lane & 3, mi = lane >> 3, l8 = lane & 7;
    uint32_t* sc32 = reinterpret_cast<uint32_t*>(smem + SM_SC);
    uint32_t* h32 = reinterpret_cast<uint32_t*>(smem + SM_H);
    uint32_t* x32 = reinterpret_cast<uint32_t*>(smem + SM_X);
    uint32_t* q32 = reinterpret_cast<uint32_t*>(smem + SM_Q);
    float* red = reinterpret_cast<float*>(smem + SM_RED);
    float* stage = reinterpret_cast<float*>(smem + SM_STAGE);
    float* own = reinterpret_cast<float*>(smem + SM_OWN);

    uint32_t tag;
    bool live = true;
    {
        const uint32_t c0 = in_c0, x0 = in_x0, c1 = in_c1, x1 = in_x1, epoch = in_epoch;
        if (cta < 120 && tid >= 128 && tid < 136) st_zero16(reinterpret_cast<uint4*>(&g_mod[cta * 16]) + (tid - 128));
        if (cta < 128 && tid >= 32 && tid < 44) st_zero16(reinterpret_cast<uint4*>(&g_q[cta * 24]) + (tid - 32));
        sc32[tid] = pack_bf(silu(bf_lo(c0)), silu(bf_hi(c0))); x32[tid] = x0;
        if (tid < 64) { sc32[256 + tid] = pack_bf(silu(bf_lo(c1)), silu(bf_hi(c1))); x32[256 + tid] = x1; }
        if (tid == 0) meta[8] = epoch + 1;
    }
    bar_cons();
    tag = meta[8];
    float mean_x = 0.f, rden_x = 1.f;
    if (cta < 128) {
        float xv[20];
#pragma unroll
        for (int i = 0; i < 10; i++) { uint32_t v = x32[lane + 32 * i]; xv[2 * i] = bf_lo(v); xv[2 * i + 1] = bf_hi(v); }
        float den;
        ln_stats(xv, mean_x, den);
        rden_x = __fdividef(1.0f, den);
    }

#pragma unroll 1
    for (int step = 0; step < 2; step++) {
    if (wid >= 4 && (step == 0 ? cta < 40 : (cta >= 40 && cta < 120))) {
        const int w4 = wid - 4;
        float acc[2][4] = {};
        const uint32_t base = sb + SM_WMOD + w4 * 10240;
        mbar_wait(BAR(B_MOD + w4), 0);
#pragma unroll
        for (int hf = 0; hf < 2; hf++) {
            uint32_t a[5][2][4], bb[5][2];
#pragma unroll
            for (int ks = 0; ks < 5; ks++) {
                const int r0 = w4 * 160 + hf * 80 + ks * 16;
                bb[ks][0] = sc32[(r0 >> 1) + j4]; bb[ks][1] = sc32[(r0 >> 1) + 4 + j4];
                const int r = hf * 80 + ks * 16 + l8 + 8 * (mi >> 1);
#pragma unroll
                for (int mt = 0; mt < 2; mt++) ldsm4t(a[ks][mt], base + r * 64 + (((2 * mt + (mi & 1)) ^ ((r >> 1) & 3)) << 4));
            }
#pragma unroll
            for (int ks = 0; ks < 5; ks++) { mma16816(acc[0], a[ks][0], bb[ks][0], bb[ks][1]); mma16816(acc[1], a[ks][1], bb[ks][0], bb[ks][1]); }
        }
        float* red2 = reinterpret_cast<float*>(smem + SM_FIN);
        if (j4 == 0) {
#pragma unroll
            for (int mt = 0; mt < 2; mt++) { red2[w4 * 32 + mt * 16 + g4] = acc[mt][0]; red2[w4 * 32 + mt * 16 + 8 + g4] = acc[mt][2]; }
        }
        asm volatile("bar.sync 3, 128;" ::: "memory");
        if (wid == 4) {
            float v = (red2[lane] + red2[32 + lane]) + (red2[64 + lane] + red2[96 + lane]);
            float o = __shfl_down_sync(0xffffffffu, v, 1);
            if (!(lane & 1)) st_pk8(&g_mod[cta * 16 + (lane >> 1)], pack_bf(v, o), tag);
            if (step == 1 && lane == 0) mbar_arrive(BAR(B_PRO));
        }
    }
    if (step == 1) break;
    if (cta < 128) {
        {
            const int off[4] = {tid, 320 + tid, tid < 64 ? 256 + tid : tid, tid < 64 ? 576 + tid : 320 + tid};
            uint32_t val[4];
            poll8<4>(g_mod, off, val, tag);
#pragma unroll
            for (int rep = 0; rep < 2; rep++) {
                int p = tid + rep * 256;
                if (p < 320) {
                    uint32_t sa = val[2 * rep], ca = val[2 * rep + 1];
                    uint32_t xx = x32[p];
                    float n0 = bfr(bfr(bf_lo(xx) - mean_x) * rden_x), n1 = bfr(bfr(bf_hi(xx) - mean_x) * rden_x);
                    float h0 = bfr(n0 * bfr(1.0f + bf_lo(ca))) + bf_lo(sa);
                    float h1 = bfr(n1 * bfr(1.0f + bf_hi(ca))) + bf_hi(sa);
                    h32[p] = pack_bf(h0, h1);
                }
            }
        }
        bar_cons();
        float acc[3][4] = {};
        uint32_t a[5][3][4], bb[5][2];
#pragma unroll
        for (int ks = 0; ks < 5; ks++) {
            const int r0 = wid * 80 + ks * 16;
            bb[ks][0] = h32[(r0 >> 1) + j4]; bb[ks][1] = h32[(r0 >> 1) + 4 + j4];
        }
        mbar_wait(BAR(B_WQ + ((wid * 80) >> 7)), 0);
        mbar_wait(BAR(B_WQ + ((wid * 80 + 79) >> 7)), 0);
#pragma unroll
        for (int ks = 0; ks < 5; ks++) {
            const int r = wid * 80 + ks * 16 + l8 + 8 * (mi >> 1);
#pragma unroll
            for (int mt = 0; mt < 3; mt++) ldsm4t(a[ks][mt], sb + SM_WQ + r * 96 + ((2 * mt + (mi & 1)) << 4));
        }
#pragma unroll
        for (int ks = 0; ks < 5; ks++) {
#pragma unroll
            for (int mt = 0; mt < 3; mt++) mma16816(acc[mt], a[ks][mt], bb[ks][0], bb[ks][1]);
        }
        if (j4 == 0) {
#pragma unroll
            for (int mt = 0; mt < 3; mt++) { red[wid * 64 + mt * 16 + g4] = acc[mt][0]; red[wid * 64 + mt * 16 + 8 + g4] = acc[mt][2]; }
        }
        bar_cons();
        if (tid < 64) {
            float v = 0.f;
            if (tid < 48) {
#pragma unroll
                for (int w = 0; w < 8; w++) v += red[w * 64 + tid];
            }
            float o = __shfl_down_sync(0xffffffffu, v, 1);
            if (tid < 48 && !(tid & 1)) st_pk8(&g_q[cta * 24 + (tid >> 1)], pack_bf(v, o), tag);
        }
    }
    {
        int off[5];
#pragma unroll
        for (int j = 0; j < 5; j++) {
            int p = tid + 256 * j;
            if (p >= NQH * 96) p = tid;
            off[j] = p < GH * 96 ? grp * GH * 96 + p : NG * GH * 96 + (p - GH * 96);
        }
        uint32_t val[5];
        poll8<5>(g_q, off, val, tag);
#pragma unroll
        for (int j = 0; j < 5; j++)
            if (tid + 256 * j < NQH * 96) q32[tid + 256 * j] = val[j];
    }
    bar_cons();
    if (tid == 0 && !(cta >= 40 && cta < 120)) mbar_arrive(BAR(B_PRO));
    }

    if (wid < 4) {
        const int pair = wid >> 1, half = wid & 1;
        uint32_t offK[3], offV[3];
        {
            const int rowK = half * 16 + l8 + 8 * (mi & 1), hiK = mi >> 1;
            const int rowV = half * 16 + l8 + 8 * (mi >> 1), hiV = mi & 1;
#pragma unroll
            for (int t = 0; t < 3; t++) {
                offK[t] = (rowK * 3 + t) * 128 + ((hiK ^ ((rowK * 3 + t) & 7)) << 4);
                offV[t] = (rowV * 3 + t) * 128 + ((hiV ^ ((rowV * 3 + t) & 7)) << 4);
                asm volatile("" : "+r"(offK[t]), "+r"(offV[t]));
            }
        }
        float acc[12][4];
#pragma unroll
        for (int i = 0; i < 12; i++) { acc[i][0] = acc[i][1] = acc[i][2] = acc[i][3] = 0.f; }
        float m_run = NEG_BIG, l_run = 0.f;
        uint32_t qf[12][2];
#pragma unroll
        for (int i = 0; i < 12; i++) { qf[i][0] = qf[i][1] = 0; }
        int cur = -1, flushed = 0, cnt = 0;
        int s = 2 * pair; uint32_t par = 0;
        int fb = 0; uint32_t fpar = 1;
        uint32_t ready = 0;
#pragma unroll 1
        while (true) {
            if (!ready) mbar_wait(BAR(B_FULL + s), par);
            const uint32_t mt_ = meta[s];
            const int run = mt_ & 0xff;
            if (run != cur) {
#pragma unroll 1
                while (flushed < run) {
                    const uint32_t fle = mbar_try(BAR(B_FLE + fb), fpar);
                    float* mb = reinterpret_cast<float*>(smem + SM_MERGE) + (fb * 4 + wid) * 200;
                    if (flushed != cur) {
#pragma unroll
                        for (int i = 0; i < 12; i++) { acc[i][0] = acc[i][2] = 0.f; }
                        m_run = NEG_BIG; l_run = 0.f; cnt = 0;
                    }
                    float l = l_run;
                    l += __shfl_xor_sync(0xffffffffu, l, 4);
                    l += __shfl_xor_sync(0xffffffffu, l, 8);
                    l += __shfl_xor_sync(0xffffffffu, l, 16);
                    if (!fle) mbar_wait(BAR(B_FLE + fb), fpar);
                    if (j4 == 0) {
#pragma unroll
                        for (int i = 0; i < 12; i++) { mb[4 + 16 * i + g4] = acc[i][0]; mb[4 + 16 * i + 8 + g4] = acc[i][2]; }
                    }
                    if (lane == 0) { mb[0] = m_run; mb[1] = l; mb[2] = __int_as_float(cnt); }
                    __syncwarp();
                    if (lane == 0) mbar_arrive(BAR(B_FLF + fb));
                    if (++fb == NBUF) { fb = 0; fpar ^= 1; }
                    flushed++;
                    cur = -1;
                }
                if (mt_ & META_END) {
                    if (flushed == 0 && lane == 0) mbar_arrive(BAR(B_FLF));
                    break;
                }
                cur = run;
                const int qi = (mt_ >> 8) & 0xff;
#pragma unroll
                for (int i = 0; i < 12; i++) { acc[i][0] = acc[i][1] = acc[i][2] = acc[i][3] = 0.f; }
                m_run = NEG_BIG; l_run = 0.f; cnt = 0;
#pragma unroll
                for (int ks = 0; ks < 12; ks++) {
                    qf[ks][0] = q32[qi * 96 + ks * 8 + j4];
                    qf[ks][1] = q32[qi * 96 + ks * 8 + 4 + j4];
                }
            }
            cnt++;
            const uint32_t kb = sb + SM_RING + s * CHUNK;
            int sv = s + 1; uint32_t parv = par;
            if (sv == NSLOT) { sv = 0; parv ^= 1; }
            float sc[6][4] = {};
            uint32_t vready;
            {
                uint32_t a[12][4];
#pragma unroll
                for (int t = 0; t < 3; t++) {
                    const uint32_t bt = kb + offK[t];
#pragma unroll
                    for (int kk = 0; kk < 4; kk++) ldsm4(a[t * 4 + kk], bt ^ (kk << 5));
                }
                vready = mbar_try(BAR(B_FULL + sv), parv);
#pragma unroll
                for (int i = 0; i < 12; i++) mma16816(sc[i % 6], a[i], qf[i][0], qf[i][1]);
            }
            __syncwarp();
            if (lane == 0) mbar_arrive(BAR(B_EMPTY + s));
            const float scale = 0.07216878364870322f;
            float s0 = bfr(bfr(((sc[0][0] + sc[1][0]) + (sc[2][0] + sc[3][0])) + (sc[4][0] + sc[5][0])) * scale);
            float s1 = bfr(bfr(((sc[0][2] + sc[1][2]) + (sc[2][2] + sc[3][2])) + (sc[4][2] + sc[5][2])) * scale);
            const float tm = warp_max(fmaxf(s0, s1));
            if (tm > m_run) {
                float alpha = ex2((m_run - tm) * LOG2E);
                l_run *= alpha;
#pragma unroll
                for (int i = 0; i < 12; i++) { acc[i][0] *= alpha; acc[i][1] *= alpha; acc[i][2] *= alpha; acc[i][3] *= alpha; }
                m_run = tm;
            }
            float p0 = ex2((s0 - m_run) * LOG2E);
            float p1 = ex2((s1 - m_run) * LOG2E);
            l_run += p0 + p1;
            const uint32_t pw = pack_bf(p0, p1);
            const uint32_t pa = __shfl_sync(0xffffffffu, pw, 8 * j4), pb = __shfl_sync(0xffffffffu, pw, 8 * j4 + 4);
            const uint32_t b0 = __byte_perm(pa, pb, 0x5410), b1 = __byte_perm(pa, pb, 0x7632);
            if (!vready) mbar_wait(BAR(B_FULL + sv), parv);
            s += 4;
            if (s >= NSLOT) { s -= NSLOT; par ^= 1; }
            ready = mbar_try(BAR(B_FULL + s), par);
            const uint32_t vb = sb + SM_RING + sv * CHUNK;
            {
                uint32_t a[12][4];
#pragma unroll
                for (int t = 0; t < 3; t++) {
                    const uint32_t bt = vb + offV[t];
#pragma unroll
                    for (int kk = 0; kk < 4; kk++) ldsm4t(a[t * 4 + kk], bt ^ (kk << 5));
                }
#pragma unroll
                for (int i = 0; i < 12; i++) mma16816(acc[i], a[i], b0, b1);
            }
            __syncwarp();
            if (lane == 0) mbar_arrive(BAR(B_EMPTY + sv));
        }
    } else if (wid == 4) {
        int fb = 0; uint32_t fpar = 0;
        mbar_wait(BAR(B_CLR), 0);
#pragma unroll 1
        for (int f = 0;; f++) {
            const float* mb = reinterpret_cast<const float*>(smem + SM_MERGE) + fb * 800;
            mbar_wait(BAR(B_FLF + fb), fpar);
            const int head = (int)meta[16 + f];
            if (head == 0xFF) break;
            float m0 = mb[0], m1 = mb[200], m2 = mb[400], m3 = mb[600];
            float M = fmaxf(fmaxf(m0, m1), fmaxf(m2, m3));
            float w0 = ex2((m0 - M) * LOG2E), w1 = ex2((m1 - M) * LOG2E);
            float w2 = ex2((m2 - M) * LOG2E), w3 = ex2((m3 - M) * LOG2E);
            const int idx = head < NG * GH ? rank : cta;
            uint4* dst = &g_dat[head][idx][0];
            float o[6];
#pragma unroll
            for (int i = 0; i < 6; i++) {
                int d = 4 + (i < 3 ? 3 * lane + i : 96 + 3 * lane + (i - 3));
                o[i] = w0 * mb[d] + w1 * mb[200 + d] + w2 * mb[400 + d] + w3 * mb[600 + d];
            }
            float L = w0 * mb[1] + w1 * mb[201] + w2 * mb[401] + w3 * mb[601];
            const uint32_t tiles = __float_as_int(mb[2]) + __float_as_int(mb[402]);
            st_pk16(dst + lane, __float_as_uint(o[0]), __float_as_uint(o[1]), __float_as_uint(o[2]), tag);
            st_pk16(dst + 32 + lane, __float_as_uint(o[3]), __float_as_uint(o[4]), __float_as_uint(o[5]), tag);
            if (lane == 0) st_pk16(&g_hdr[head][idx], __float_as_uint(M), __float_as_uint(L), tiles, tag);
            __syncwarp();
            if (lane == 0) mbar_arrive(BAR(B_FLE + fb));
            if (++fb == NBUF) { fb = 0; fpar ^= 1; }
            if (meta[16 + f + 1] == 0xFFu) break;
        }
    } else if (wid == 5) {
        if (cta < 128) {
            if (lane < 2) st_zero16(&g_es[cta][lane]);
#pragma unroll 1
            for (int i = lane; i < 256; i += 32) {
                st_zero16(cta >= 128 - NLATE ? &g_late[cta - (128 - NLATE)][i >> 1][i & 1] : &g_h1[i >> 1][cta][i & 1]);
                if (cta < 96) st_zero16(&g_h3[i >> 1][cta][i & 1]);
            }
        }
#pragma unroll 1
        for (int f = 0; f < NQH; f++) {
            const int head = f < GH ? grp * GH + f : NG * GH + (f - GH);
            const int idx = f < GH ? rank : cta;
            st_zero16(&g_dat[head][idx][lane]);
            st_zero16(&g_dat[head][idx][32 + lane]);
            if (lane == 0) st_zero16(&g_hdr[head][idx]);
        }
        __syncwarp();
        if (lane == 0) mbar_arrive(BAR(B_CLR));
    } else {
        if (cta < 128) {
            const int t = tid - 192;
            uint32_t* cb32 = reinterpret_cast<uint32_t*>(smem + SM_CB);
            uint32_t* sb32 = reinterpret_cast<uint32_t*>(smem + SM_SB);
            uint32_t* ga32 = reinterpret_cast<uint32_t*>(smem + SM_GA);
            const int col = cta * 5 + t;
            int off[16];
            uint32_t val[16];
#pragma unroll
            for (int rep = 0; rep < 5; rep++) { off[3 * rep] = 960 + t + 64 * rep; off[3 * rep + 1] = 1280 + t + 64 * rep; off[3 * rep + 2] = 640 + t + 64 * rep; }
            off[15] = t < 5 ? (3200 + col) >> 1 : 960;
            poll8<16>(g_mod, off, val, tag);
#pragma unroll
            for (int rep = 0; rep < 5; rep++) {
                sb32[t + 64 * rep] = val[3 * rep];
                cb32[t + 64 * rep] = pack_bf(1.0f + bf_lo(val[3 * rep + 1]), 1.0f + bf_hi(val[3 * rep + 1]));
                ga32[t + 64 * rep] = val[3 * rep + 2];
            }
            if (t < 5) own[8 + t] = (col & 1) ? bf_hi(val[15]) : bf_lo(val[15]);
        }
        live = false;
    }
    const uint32_t sb0 = sb;
    const int tid0 = tid;
#pragma unroll 1
    while (cta < 128) {
        uint32_t sb = sb0; int tid = tid0;
        asm volatile("" : "+r"(sb), "+r"(tid));
        const int wid = tid >> 5, lane = tid & 31;
        const int g4 = lane >> 2, j4 = lane & 3, mi = lane >> 3, l8 = lane & 7;
        if (wid >= 5) {
            const int h = cta >> 2, js = cta & 3;
            const bool gl = h >= NG * GH;
            const int ncand = gl ? G : (G - h / GH + NG - 1) / NG;
            const int k = lane & 15, rr = (wid - 5) * 2 + (lane >> 4);
            if (live) {
                const unsigned* cp = &g_ctr[(tag - 1) & 1][(gl ? NG : h / GH) * 32];
                const unsigned thr = ((gl ? h - NG * GH : h % GH) + 1) * TPH;
                uint32_t it = 0;
                while (true) {
                    unsigned v;
                    asm volatile("ld.relaxed.gpu.global.u32 %0, [%1];" : "=r"(v) : "l"(cp) : "memory");
                    if (v >= thr) break;
                    __nanosleep(300);
                    if (++it > SPIN_LIMIT) __trap();
                }
            }
            const uint4* hdr = &g_hdr[h][lane];
            const uint4* dat = &g_dat[h][rr][16 * js + k];
            float* part = stage;
            float L, a0, a1, a2;
            uint32_t it = 0;
            uint4 hd[5], dv[MAXG / 6];
#pragma unroll
            for (int i = 0; i < 5; i++) hd[i] = make_uint4(0, 0, 0, 0);
#pragma unroll
            for (int i = 0; i < MAXG / 6; i++) dv[i] = make_uint4(0, 0, 0, 0);
#pragma unroll 1
            while (true) {
                FreshN<5, 32>::run(hd, hdr, tag, live, lane, 32, ncand);
                FreshN<MAXG / 6, 6 * 64>::run(dv, dat, tag, live, rr, 6, ncand);
                float w[5], M = NEG_BIG;
                int c = 0;
#pragma unroll
                for (int i = 0; i < 5; i++) {
                    const bool v = hd[i].w == tag;
                    w[i] = v ? __uint_as_float(hd[i].x) : NEG_BIG;
                    M = fmaxf(M, w[i]);
                    c += v ? (int)hd[i].z : 0;
                }
                c = __reduce_add_sync(0xffffffffu, c);
                if (++it > SPIN_LIMIT) __trap();
                if (live && c != TPH) continue;
                M = warp_max(M);
                float ls = 0.f;
#pragma unroll
                for (int i = 0; i < 5; i++) {
                    const bool v = w[i] != NEG_BIG;
                    const float e = ex2((w[i] - M) * LOG2E);
                    w[i] = v ? e : -0.0f;
                    ls = fmaf(w[i], __uint_as_float(hd[i].y), ls);
                }
                float* wsm = reinterpret_cast<float*>(smem + SM_X2) + (wid - 5) * 160;
                if (live) {
#pragma unroll
                    for (int i = 0; i < 5; i++) wsm[lane + 32 * i] = w[i];
                }
                __syncwarp();
                L = warp_sum(ls);
                uint32_t badm = 0;
                a0 = a1 = a2 = 0.f;
#pragma unroll
                for (int i = 0; i < MAXG / 6; i++) {
                    const float wi = wsm[rr + 6 * i];
                    badm |= (dv[i].w ^ tag) & ~(uint32_t)(__float_as_int(wi) >> 31);
                    a0 = fmaf(wi, __uint_as_float(dv[i].x), a0);
                    a1 = fmaf(wi, __uint_as_float(dv[i].y), a1);
                    a2 = fmaf(wi, __uint_as_float(dv[i].z), a2);
                }
                const bool bad = badm != 0;
                if (!__any_sync(0xffffffffu, bad) || !live) break;
            }
            a0 += __shfl_xor_sync(0xffffffffu, a0, 16);
            a1 += __shfl_xor_sync(0xffffffffu, a1, 16);
            a2 += __shfl_xor_sync(0xffffffffu, a2, 16);
            if (live && lane < 16) { float* pp = part + (wid - 5) * 48 + 3 * k; pp[0] = a0; pp[1] = a1; pp[2] = a2; }
            if (live) asm volatile("bar.sync 2, 96;" ::: "memory");
            if (wid == 5 || !live) {
                uint16_t* osw = reinterpret_cast<uint16_t*>(smem + SM_SC);
                const float inv = __fdividef(1.0f, L);
                const float o0 = (part[lane] + part[48 + lane]) + part[96 + lane];
                const float o1 = (part[32 + (lane & 15)] + part[80 + (lane & 15)]) + part[128 + (lane & 15)];
                if (live) { osw[lane] = (uint16_t)(__float_as_uint(bfr(o0 * inv)) >> 16); if (lane < 16) osw[32 + lane] = (uint16_t)(__float_as_uint(bfr(o1 * inv)) >> 16); }
            }
        }
        if (wid < 5 || !live) {
            const int w5 = wid < 5 ? wid : wid - 5;
            uint32_t wa[8][3][4];
            if (live) mbar_wait(BAR(B_WO + w5), 0);
#pragma unroll
            for (int i = 0; i < 8; i++) {
                const int cc = 2 * (i & 3) + (mi & 1);
#pragma unroll
                for (int ks = 0; ks < 3; ks++) {
                    const int r = ks * 16 + l8 + 8 * (mi >> 1);
                    ldsm4t(wa[i][ks], sb + SM_WO + (2 * w5 + (i >> 2)) * 6144 + r * 128 + ((cc ^ (r & 7)) << 4));
                }
            }
            if (live) bar_cons();
            const uint32_t* os32 = reinterpret_cast<const uint32_t*>(smem + SM_SC);
            float acc[8][4] = {};
#pragma unroll
            for (int ks = 0; ks < 3; ks++) {
                const uint32_t b0 = os32[ks * 8 + j4], b1 = os32[ks * 8 + 4 + j4];
#pragma unroll
                for (int i = 0; i < 8; i++) mma16816(acc[i], wa[i][ks], b0, b1);
            }
            if (live && j4 == 0) {
#pragma unroll
                for (int i = 0; i < 8; i++) { stage[(w5 * 8 + i) * 16 + g4] = acc[i][0]; stage[(w5 * 8 + i) * 16 + 8 + g4] = acc[i][2]; }
            }
        } else {
            bar_cons();
        }
        if (live) bar_cons();
        {
            const int o = tid >> 1, kk = tid & 1;
            const float* sp = stage + o * 5 + kk * 3;
            float v0 = sp[0], v1 = sp[1], v2 = kk ? 0.f : sp[2];
            uint4* dst = cta >= 128 - NLATE ? &g_late[cta - (128 - NLATE)][o][kk] : &g_h1[o][cta][kk];
            if (live) st_pk16(dst, __float_as_uint(v0), __float_as_uint(v1), __float_as_uint(v2), tag);
        }
        if (wid == 0 || !live) {
            const uint4* p = &g_h1[cta][0][0] + lane;
            uint4 v[8];
#pragma unroll
            for (int j = 0; j < 8; j++) v[j] = make_uint4(0, 0, 0, 0);
            if (lane >= 32 - 2 * NLATE) v[7].w = tag;
            uint32_t it = 0;
            while (true) {
                FreshN<8, 32>::run(v, p, tag, live, 0, 0, 1);
                bool ok = true;
#pragma unroll
                for (int j = 0; j < 8; j++) ok = ok && v[j].w == tag;
                if (__all_sync(0xffffffffu, ok) || !live) break;
                if (++it > SPIN_LIMIT) __trap();
            }
            float a0, a1, a2;
            a0 = ((__uint_as_float(v[0].x) + __uint_as_float(v[1].x)) + (__uint_as_float(v[2].x) + __uint_as_float(v[3].x))) +
                 ((__uint_as_float(v[4].x) + __uint_as_float(v[5].x)) + (__uint_as_float(v[6].x) + __uint_as_float(v[7].x)));
            a1 = ((__uint_as_float(v[0].y) + __uint_as_float(v[1].y)) + (__uint_as_float(v[2].y) + __uint_as_float(v[3].y))) +
                 ((__uint_as_float(v[4].y) + __uint_as_float(v[5].y)) + (__uint_as_float(v[6].y) + __uint_as_float(v[7].y)));
            a2 = ((__uint_as_float(v[0].z) + __uint_as_float(v[1].z)) + (__uint_as_float(v[2].z) + __uint_as_float(v[3].z))) +
                 ((__uint_as_float(v[4].z) + __uint_as_float(v[5].z)) + (__uint_as_float(v[6].z) + __uint_as_float(v[7].z)));
#pragma unroll
            for (int o = 2; o <= 16; o <<= 1) {
                a0 += __shfl_xor_sync(0xffffffffu, a0, o);
                a1 += __shfl_xor_sync(0xffffffffu, a1, o);
                a2 += __shfl_xor_sync(0xffffffffu, a2, o);
            }
            if (live && lane < 2) st_pk16(&g_es[cta][lane], __float_as_uint(a0), __float_as_uint(a1), __float_as_uint(a2), tag);
        }
        float* x2s = reinterpret_cast<float*>(smem + SM_X2);
        {
            uint32_t a1[5][4], a3[5][4];
            if (live && cta < 96) mbar_wait3(BAR(B_W1 + (wid >> 2)), BAR(B_W3 + (wid >> 2)), BAR(B_W1 + (wid >> 2)));
#pragma unroll
            for (int ks = 0; ks < 5; ks++) {
                const int r = wid * 80 + ks * 16 + l8 + 8 * (mi >> 1);
                const uint32_t off = r * 32 + (((mi & 1) ^ ((r >> 2) & 1)) << 4);
                ldsm4t(a1[ks], sb + SM_W1 + off);
                ldsm4t(a3[ks], sb + SM_W3 + off);
            }
            const int o = tid >> 1, k = tid & 1, c0 = 5 * o + 3 * k;
            const uint16_t* x16 = reinterpret_cast<const uint16_t*>(smem + SM_X);
            const uint16_t* ga16 = reinterpret_cast<const uint16_t*>(smem + SM_GA);
            const uint16_t* cb16 = reinterpret_cast<const uint16_t*>(smem + SM_CB);
            const uint16_t* sb16 = reinterpret_cast<const uint16_t*>(smem + SM_SB);
            float xin[3], gin[3], cin[3], sin_[3];
#pragma unroll
            for (int e = 0; e < 3; e++) {
                const int c = c0 + ((e == 2 && k) ? 1 : e);
                xin[e] = __uint_as_float((uint32_t)x16[c] << 16); gin[e] = __uint_as_float((uint32_t)ga16[c] << 16);
                cin[e] = __uint_as_float((uint32_t)cb16[c] << 16); sin_[e] = __uint_as_float((uint32_t)sb16[c] << 16);
            }
            uint4 v[1 + NLATE];
#pragma unroll
            for (int j = 0; j <= NLATE; j++) v[j] = make_uint4(0, 0, 0, 0);
            const uint4* pe = &g_es[o][k];
            const uint4* pl = &g_late[0][o][k];
            uint32_t it = 0;
            while (true) {
                FreshN<1, 1>::run(v, pe, tag, live, 0, 0, 1);
                FreshN<NLATE, 256>::run(v + 1, pl, tag, live, 0, 0, 1);
                bool ok = true;
#pragma unroll
                for (int j = 0; j <= NLATE; j++) ok = ok && v[j].w == tag;
                if (__all_sync(0xffffffffu, ok) || !live) break;
                if (++it > SPIN_LIMIT) __trap();
            }
            float x2[3];
            x2[0] = (__uint_as_float(v[0].x) + (__uint_as_float(v[1].x) + __uint_as_float(v[2].x))) + (__uint_as_float(v[3].x) + __uint_as_float(v[4].x));
            x2[1] = (__uint_as_float(v[0].y) + (__uint_as_float(v[1].y) + __uint_as_float(v[2].y))) + (__uint_as_float(v[3].y) + __uint_as_float(v[4].y));
            x2[2] = (__uint_as_float(v[0].z) + (__uint_as_float(v[1].z) + __uint_as_float(v[2].z))) + (__uint_as_float(v[3].z) + __uint_as_float(v[4].z));
#pragma unroll
            for (int e = 0; e < 3; e++) x2[e] = bfr(xin[e] + bfr(gin[e] * bfr(x2[e])));
            if (live && o == cta) { x2s[3 * k] = x2[0]; x2s[3 * k + 1] = x2[1]; if (!k) x2s[2] = x2[2]; }
            float* st8 = red + 256;
            {
                const float pv = __shfl_sync(0xffffffffu, x2[0], 0);
                const float d0 = x2[0] - pv, d1 = x2[1] - pv, d2 = k ? 0.f : x2[2] - pv;
                float s1 = (d0 + d1) + d2;
                float s2 = fmaf(d0, d0, fmaf(d1, d1, d2 * d2));
#pragma unroll
                for (int q = 16; q > 0; q >>= 1) { s1 += __shfl_xor_sync(0xffffffffu, s1, q); s2 += __shfl_xor_sync(0xffffffffu, s2, q); }
                if (live && lane == 0) { st8[wid] = pv + s1 * (1.0f / 80.0f); st8[8 + wid] = s2 - s1 * s1 * (1.0f / 80.0f); }
            }
            if (live) bar_cons();
            if (cta < 96) {
            const float4 mA = *reinterpret_cast<const float4*>(st8), mB = *reinterpret_cast<const float4*>(st8 + 4);
            const float4 qA = *reinterpret_cast<const float4*>(st8 + 8), qB = *reinterpret_cast<const float4*>(st8 + 12);
            const float mean = (((mA.x + mA.y) + (mA.z + mA.w)) + ((mB.x + mB.y) + (mB.z + mB.w))) * 0.125f;
            const float u0 = mA.x - mean, u1 = mA.y - mean, u2 = mA.z - mean, u3 = mA.w - mean;
            const float u4 = mB.x - mean, u5 = mB.y - mean, u6 = mB.z - mean, u7 = mB.w - mean;
            const float m2 = (((qA.x + qA.y) + (qA.z + qA.w)) + ((qB.x + qB.y) + (qB.z + qB.w))) +
                             80.0f * (((u0 * u0 + u1 * u1) + (u2 * u2 + u3 * u3)) + ((u4 * u4 + u5 * u5) + (u6 * u6 + u7 * u7)));
            const float mean_b = bfr(mean);
            const float rden = __fdividef(1.0f, bfr(fsqrt(bfr(bfr(m2 * (1.0f / 640.0f)) + 1e-5f))));
            {
                uint16_t* h16 = reinterpret_cast<uint16_t*>(smem + SM_H);
#pragma unroll
                for (int e = 0; e < 3; e++) {
                    const float n = bfr(bfr(x2[e] - mean_b) * rden);
                    const float hv = bfr(bfr(n * cin[e]) + sin_[e]);
                    if (live && !(e == 2 && k)) h16[c0 + e] = (uint16_t)(__float_as_uint(hv) >> 16);
                }
            }
            __syncwarp();
            const uint32_t w2ready = mbar_try(BAR(B_W2 + (wid >> 2)), 0);
            float ag[2][4] = {}, au[2][4] = {};
#pragma unroll
            for (int ks = 0; ks < 5; ks++) {
                const int r0 = wid * 80 + ks * 16;
                const uint32_t b0 = h32[(r0 >> 1) + j4], b1 = h32[(r0 >> 1) + 4 + j4];
                mma16816(ag[ks & 1], a1[ks], b0, b1);
                mma16816(au[ks & 1], a3[ks], b0, b1);
            }
            if (live && j4 == 0) {
                red[wid * 32 + g4] = ag[0][0] + ag[1][0]; red[wid * 32 + 8 + g4] = ag[0][2] + ag[1][2];
                red[wid * 32 + 16 + g4] = au[0][0] + au[1][0]; red[wid * 32 + 24 + g4] = au[0][2] + au[1][2];
            }
            uint32_t a2[5][4];
            if (live && !w2ready) mbar_wait(BAR(B_W2 + (wid >> 2)), 0);
            const uint32_t w2b = sb + SM_RING + meta[10 + (wid >> 2)] % NSLOT * CHUNK;
#pragma unroll
            for (int i = 0; i < 5; i++) {
                const int mt = (wid & 3) * 5 + i;
                const int cc = 2 * (mt & 3) + (mi & 1);
                const int r = l8 + 8 * (mi >> 1);
                ldsm4t(a2[i], w2b + (mt >> 2) * 2048 + r * 128 + ((cc ^ (r & 7)) << 4));
            }
            if (live) bar_cons();
            float v = ((red[lane] + red[32 + lane]) + (red[64 + lane] + red[96 + lane])) + ((red[128 + lane] + red[160 + lane]) + (red[192 + lane] + red[224 + lane]));
            v = bfr(v);
            float up = __shfl_down_sync(0xffffffffu, v, 16);
            float hact = bfr(bfr(silu(v)) * up);
            float e0 = __shfl_sync(0xffffffffu, hact, 2 * j4), e1 = __shfl_sync(0xffffffffu, hact, 2 * j4 + 1);
            float e2 = __shfl_sync(0xffffffffu, hact, 2 * j4 + 8), e3 = __shfl_sync(0xffffffffu, hact, 2 * j4 + 9);
            const uint32_t b0 = pack_bf(e0, e1), b1 = pack_bf(e2, e3);
            float acc[5][4] = {};
#pragma unroll
            for (int i = 0; i < 5; i++) mma16816(acc[i], a2[i], b0, b1);
            if (live && j4 == 0) {
#pragma unroll
                for (int i = 0; i < 5; i++) { stage[(wid * 5 + i) * 16 + g4] = acc[i][0]; stage[(wid * 5 + i) * 16 + 8 + g4] = acc[i][2]; }
            }
            if (live) bar_cons();
            const float* sp = stage + o * 5 + k * 3;
            float v0 = sp[0], v1 = sp[1], v2 = k ? 0.f : sp[2];
            if (live) st_pk16(&g_h3[o][cta][k], __float_as_uint(v0), __float_as_uint(v1), __float_as_uint(v2), tag);
            }
        }
        if (wid == 0 || !live) {
            const uint4* p = &g_h3[cta][0][0] + lane;
            const float gx = own[8 + (lane & 7)], xx = x2s[lane & 7];
            uint4 v[6];
            uint32_t it = 0;
            if (live && cta < 96) spin(POLL_DELAY);
            while (true) {
                bool ok = true;
                LoadN<6, 32>::run(v, p, live, 0, 0, 1);
#pragma unroll
                for (int j = 0; j < 6; j++) ok = ok && v[j].w == tag;
                if (__all_sync(0xffffffffu, ok) || !live) break;
                if (++it > SPIN_LIMIT) __trap();
            }
            float a0 = ((__uint_as_float(v[0].x) + __uint_as_float(v[1].x)) + (__uint_as_float(v[2].x) + __uint_as_float(v[3].x))) + (__uint_as_float(v[4].x) + __uint_as_float(v[5].x));
            float a1 = ((__uint_as_float(v[0].y) + __uint_as_float(v[1].y)) + (__uint_as_float(v[2].y) + __uint_as_float(v[3].y))) + (__uint_as_float(v[4].y) + __uint_as_float(v[5].y));
            float a2 = ((__uint_as_float(v[0].z) + __uint_as_float(v[1].z)) + (__uint_as_float(v[2].z) + __uint_as_float(v[3].z))) + (__uint_as_float(v[4].z) + __uint_as_float(v[5].z));
#pragma unroll
            for (int o = 2; o <= 16; o <<= 1) {
                a0 += __shfl_xor_sync(0xffffffffu, a0, o);
                a1 += __shfl_xor_sync(0xffffffffu, a1, o);
                a2 += __shfl_xor_sync(0xffffffffu, a2, o);
            }
            const float t0 = __shfl_sync(0xffffffffu, a0, lane >= 3), t1 = __shfl_sync(0xffffffffu, a1, lane >= 3);
            const float sum = (lane == 0 || lane == 3) ? t0 : (lane == 2 ? a2 : t1);
            const float y = xx + bfr(gx * bfr(sum));
            if (live && lane < 5) reinterpret_cast<uint16_t*>(out)[cta * 5 + lane] = (uint16_t)(__float_as_uint(bfr(y)) >> 16);
            if (live && cta == 0 && lane == 0) g_epoch = tag;
        }
        if (live) break;
        live = true;
    }
    }
}

typedef CUresult (*EncodeFn)(CUtensorMap*, CUtensorMapDataType, cuuint32_t, void*, const cuuint64_t*, const cuuint64_t*,
                             const cuuint32_t*, const cuuint32_t*, CUtensorMapInterleave, CUtensorMapSwizzle,
                             CUtensorMapL2promotion, CUtensorMapFloatOOBfill);

void make_map(EncodeFn enc, CUtensorMap* tm, const void* ptr, uint64_t cols, uint64_t rows, uint32_t box_c, uint32_t box_r,
              CUtensorMapSwizzle sw, CUtensorMapL2promotion prom) {
    cuuint64_t dims[2] = {cols, rows};
    cuuint64_t strides[1] = {cols * 2};
    cuuint32_t box[2] = {box_c, box_r};
    cuuint32_t es[2] = {1, 1};
    enc(tm, CU_TENSOR_MAP_DATA_TYPE_BFLOAT16, 2, const_cast<void*>(ptr), dims, strides, box, es,
        CU_TENSOR_MAP_INTERLEAVE_NONE, sw, prom, CU_TENSOR_MAP_FLOAT_OOB_FILL_NONE);
}

}

extern "C" void kernel_launch(void* const* d_in, const int* in_sizes, int n_in, void* d_out, int out_size) {
    (void)in_sizes; (void)n_in; (void)out_size;
    static EncodeFn enc = nullptr;
    static int num_sms = 0;
    if (!enc) {
        void* fn = nullptr;
        cudaDriverEntryPointQueryResult qr;
        cudaGetDriverEntryPoint("cuTensorMapEncodeTiled", &fn, cudaEnableDefault, &qr);
        enc = (EncodeFn)fn;
        cudaDeviceGetAttribute(&num_sms, cudaDevAttrMultiProcessorCount, 0);
        cudaFuncSetAttribute(fused_decode_kernel, cudaFuncAttributeMaxDynamicSharedMemorySize, SM_TOTAL);
    }
    CUtensorMap tmK, tmV, tmMod, tmWq, tmWo, tmW1, tmW3, tmW2;
    const uint64_t kv_lines = (uint64_t)NH * SK * 3;
    make_map(enc, &tmK, d_in[1], 64, kv_lines, 64, 96, CU_TENSOR_MAP_SWIZZLE_128B, CU_TENSOR_MAP_L2_PROMOTION_L2_128B);
    make_map(enc, &tmV, d_in[2], 64, kv_lines, 64, 96, CU_TENSOR_MAP_SWIZZLE_128B, CU_TENSOR_MAP_L2_PROMOTION_L2_128B);
    make_map(enc, &tmWq, d_in[3], NH * DH, D, 48, 128, CU_TENSOR_MAP_SWIZZLE_NONE, CU_TENSOR_MAP_L2_PROMOTION_L2_128B);
    make_map(enc, &tmWo, d_in[4], D, NH * DH, 64, 48, CU_TENSOR_MAP_SWIZZLE_128B, CU_TENSOR_MAP_L2_PROMOTION_L2_128B);
    make_map(enc, &tmW1, d_in[6], FF, D, 16, 160, CU_TENSOR_MAP_SWIZZLE_32B, CU_TENSOR_MAP_L2_PROMOTION_L2_128B);
    make_map(enc, &tmW3, d_in[7], FF, D, 16, 160, CU_TENSOR_MAP_SWIZZLE_32B, CU_TENSOR_MAP_L2_PROMOTION_L2_128B);
    make_map(enc, &tmW2, d_in[8], D, FF, 64, 16, CU_TENSOR_MAP_SWIZZLE_128B, CU_TENSOR_MAP_L2_PROMOTION_L2_128B);
    make_map(enc, &tmMod, d_in[10], 6 * D, D, 32, 160, CU_TENSOR_MAP_SWIZZLE_64B, CU_TENSOR_MAP_L2_PROMOTION_L2_128B);
    int grid = num_sms < MAXG ? num_sms : MAXG;
    fused_decode_kernel<<<grid, NTHREADS, SM_TOTAL, cudaStreamPerThread>>>(
        tmK, tmV, tmMod, tmWq, tmWo, tmW1, tmW3, tmW2, (const __nv_bfloat16*)d_in[0], (const __nv_bfloat16*)d_in[9],
        (__nv_bfloat16*)d_out);
}
```

```cpp
#include <cuda_runtime.h>
#include <cuda_bf16.h>
#include <cuda.h>
#include <stdint.h>

namespace {

constexpr int D = 640, NH = 32, SK = 8192, DH = 192, FF = 1536;
constexpr int NG = 4;
constexpr int GH = 7;
constexpr int NGLOB = NH - NG * GH;
constexpr int NQH = GH + NGLOB;
constexpr int TILE = 32;
constexpr int TPH = SK / TILE;
constexpr int GT = GH * TPH;
constexpr int PT = NGLOB * TPH;
constexpr int CHUNK = TILE * DH * 2;
constexpr int NSLOT = 8;
constexpr int WIN = 3;
constexpr int WPRO = 4;
constexpr int POLL_DELAY = 450;
constexpr int NBUF = 2;
constexpr int NLATE = 4;
constexpr int MAXG = 132;
constexpr int NTHREADS = 288;
constexpr float NEG_BIG = -3.402823466e38f;

constexpr int SM_WMOD = 0;
constexpr int SM_WQ = 40960;
constexpr int SM_WO = 0;
constexpr int SM_W1 = 61440;
constexpr int SM_W3 = 81920;
constexpr int SM_RING = 102400;
constexpr int SM_MISC = SM_RING + NSLOT * CHUNK;
constexpr int SM_BARS = SM_MISC;
constexpr int SM_META = SM_BARS + 512;
constexpr int SM_Q = SM_META + 128;
constexpr int SM_SC = SM_Q + NQH * DH * 2;
constexpr int SM_H = SM_SC + 1280;
constexpr int SM_X = SM_H + 1280;
constexpr int SM_CB = SM_X + 1280;
constexpr int SM_SB = SM_CB + 1280;
constexpr int SM_GA = SM_SB + 1280;
constexpr int SM_OWN = SM_GA + 1280;
constexpr int SM_RED = SM_OWN + 128;
constexpr int SM_MERGE = SM_RED + 2048;
constexpr int SM_STAGE = SM_MERGE + NBUF * 3200;
constexpr int SM_X2 = SM_STAGE + 2560;
constexpr int SM_FIN = SM_X2 + 2560;
constexpr int SM_TOTAL = SM_FIN + 512;
static_assert(SM_TOTAL <= 232448, "shared memory budget");

constexpr int B_FULL = 0;
constexpr int B_EMPTY = 8;
constexpr int B_MOD = 16;
constexpr int B_WQ = 20;
constexpr int B_WO = 25;
constexpr int B_W1 = 30;
constexpr int B_W3 = 32;
constexpr int B_W2 = 34;
constexpr int B_PRO = 36, B_DUMMY = 37, B_CLR = 38;
constexpr int B_FLF = 40, B_FLE = 44;
constexpr int B_LAST = 48;
static_assert(NSLOT == 8 && NSLOT >= 6 && WIN <= WPRO && WIN <= NSLOT - 3 && NBUF <= 4, "barrier map / end markers vs window");
constexpr uint32_t META_END = 0x10000u;

__device__ unsigned g_epoch;
__device__ unsigned g_ctr[2][(NG + 1) * 32];
__device__ __align__(128) unsigned long long g_mod[1920];
__device__ __align__(128) unsigned long long g_q[3072];
__device__ __align__(128) uint4 g_hdr[NH][MAXG];
__device__ __align__(128) uint4 g_dat[NH][MAXG][64];
__device__ __align__(128) uint4 g_h1[128][128][2];
__device__ __align__(128) uint4 g_es[128][2];
__device__ __align__(128) uint4 g_late[NLATE][128][2];
__device__ __align__(128) uint4 g_h3[128][96][2];


__device__ __forceinline__ uint32_t smem_u32(const void* p) { return (uint32_t)__cvta_generic_to_shared(p); }
__device__ __forceinline__ void mbar_init(uint32_t bar, uint32_t cnt) {
    asm volatile("mbarrier.init.shared::cta.b64 [%0], %1;" ::"r"(bar), "r"(cnt) : "memory");
}
__device__ __forceinline__ void mbar_expect_tx(uint32_t bar, uint32_t bytes) {
    asm volatile("mbarrier.arrive.expect_tx.shared::cta.b64 _, [%0], %1;" ::"r"(bar), "r"(bytes) : "memory");
}
__device__ __forceinline__ void mbar_arrive(uint32_t bar) {
    asm volatile("mbarrier.arrive.shared::cta.b64 _, [%0];" ::"r"(bar) : "memory");
}
constexpr uint32_t SPIN_LIMIT = 1u << 22;
__device__ __forceinline__ void mbar_wait(uint32_t bar, uint32_t parity) {
    asm volatile(
        "{\n.reg .pred p;\n.reg .u32 c;\nmov.u32 c, 0;\n"
        "LW:\nmbarrier.try_wait.parity.shared::cta.b64 p, [%0], %1;\n@p bra LD;\n"
        "add.u32 c, c, 1;\nsetp.lt.u32 p, c, 0x400000;\n@p bra LW;\ntrap;\nLD:\n}" ::"r"(bar), "r"(parity)
        : "memory");
}
__device__ __forceinline__ uint32_t mbar_try(uint32_t bar, uint32_t parity) {
    uint32_t ok;
    asm volatile("{\n.reg .pred p;\nmbarrier.try_wait.parity.shared::cta.b64 p, [%1], %2;\nselp.u32 %0, 1, 0, p;\n}"
                 : "=r"(ok) : "r"(bar), "r"(parity) : "memory");
    return ok;
}
__device__ __forceinline__ void mbar_wait3(uint32_t b0, uint32_t b1, uint32_t b2) {
    asm volatile(
        "{\n.reg .pred p, q, r;\n.reg .u32 c;\nmov.u32 c, 0;\n"
        "LW:\nmbarrier.try_wait.parity.shared::cta.b64 p, [%0], 0;\n"
        "mbarrier.try_wait.parity.shared::cta.b64 q, [%1], 0;\n"
        "mbarrier.try_wait.parity.shared::cta.b64 r, [%2], 0;\n"
        "and.pred p, p, q;\nand.pred p, p, r;\n@p bra LD;\n"
        "add.u32 c, c, 1;\nsetp.lt.u32 p, c, 0x400000;\n@p bra LW;\ntrap;\nLD:\n}" ::"r"(b0), "r"(b1), "r"(b2)
        : "memory");
}
__device__ __forceinline__ void tma2d(uint32_t dst, const CUtensorMap* tm, int c0, int c1, uint32_t bar) {
    asm volatile(
        "cp.async.bulk.tensor.2d.shared::cluster.global.mbarrier::complete_tx::bytes [%0], [%1, {%3, %4}], [%2];" ::"r"(dst),
        "l"(tm), "r"(bar), "r"(c0), "r"(c1)
        : "memory");
}
__device__ __forceinline__ void tma2d_hint(uint32_t dst, const CUtensorMap* tm, int c0, int c1, uint32_t bar, uint64_t pol) {
    asm volatile(
        "cp.async.bulk.tensor.2d.shared::cluster.global.mbarrier::complete_tx::bytes.L2::cache_hint [%0], [%1, {%3, %4}], [%2], %5;" ::"r"(dst),
        "l"(tm), "r"(bar), "r"(c0), "r"(c1), "l"(pol)
        : "memory");
}
__device__ __forceinline__ void prefetch_tm(const CUtensorMap* tm) {
    asm volatile("prefetch.tensormap [%0];" ::"l"(tm) : "memory");
}
__device__ __forceinline__ void ldsm4(uint32_t (&r)[4], uint32_t addr) {
    asm volatile("ldmatrix.sync.aligned.m8n8.x4.shared.b16 {%0,%1,%2,%3}, [%4];"
                 : "=r"(r[0]), "=r"(r[1]), "=r"(r[2]), "=r"(r[3])
                 : "r"(addr));
}
__device__ __forceinline__ void ldsm4t(uint32_t (&r)[4], uint32_t addr) {
    asm volatile("ldmatrix.sync.aligned.m8n8.x4.trans.shared.b16 {%0,%1,%2,%3}, [%4];"
                 : "=r"(r[0]), "=r"(r[1]), "=r"(r[2]), "=r"(r[3])
                 : "r"(addr));
}
__device__ __forceinline__ void mma16816(float (&d)[4], const uint32_t (&a)[4], uint32_t b0, uint32_t b1) {
    asm volatile(
        "mma.sync.aligned.m16n8k16.row.col.f32.bf16.bf16.f32 {%0,%1,%2,%3}, {%4,%5,%6,%7}, {%8,%9}, {%0,%1,%2,%3};"
        : "+f"(d[0]), "+f"(d[1]), "+f"(d[2]), "+f"(d[3])
        : "r"(a[0]), "r"(a[1]), "r"(a[2]), "r"(a[3]), "r"(b0), "r"(b1));
}
__device__ __forceinline__ void bar_cons() { asm volatile("bar.sync 1, 256;" ::: "memory"); }
__device__ __forceinline__ void spin(int cycles) {
    long long t0 = clock64();
    while (clock64() - t0 < cycles) {}
}

__device__ __forceinline__ float bfr(float x) {
    uint32_t r;
    asm("cvt.rn.bf16x2.f32 %0, %1, %2;" : "=r"(r) : "f"(x), "f"(0.0f));
    return __uint_as_float(r);
}
__device__ __forceinline__ uint32_t pack_bf(float lo, float hi) {
    __nv_bfloat162 t = __floats2bfloat162_rn(lo, hi);
    return *reinterpret_cast<uint32_t*>(&t);
}
__device__ __forceinline__ float bf_lo(uint32_t v) { return __uint_as_float(v << 16); }
__device__ __forceinline__ float bf_hi(uint32_t v) { return __uint_as_float(v & 0xffff0000u); }

__device__ __forceinline__ void st_pk8(unsigned long long* p, uint32_t v, uint32_t tag) {
    unsigned long long w = ((unsigned long long)tag << 32) | v;
    asm volatile("st.relaxed.gpu.global.b64 [%0], %1;" ::"l"(p), "l"(w) : "memory");
}
template <int N>
__device__ __forceinline__ void poll8(const unsigned long long* base, const int (&off)[N], uint32_t (&val)[N], uint32_t tag) {
    uint32_t tg[N];
#pragma unroll
    for (int i = 0; i < N; i++) { val[i] = 0; tg[i] = 0; }
    uint32_t it = 0;
    while (true) {
#pragma unroll
        for (int i = 0; i < N; i++) {
            asm volatile("{\n.reg .pred q;\n.reg .b64 t;\nsetp.ne.u32 q, %1, %3;\nmov.b64 t, {%0, %1};\n"
                             "@q ld.relaxed.gpu.global.b64 t, [%2];\nmov.b64 {%0, %1}, t;\n}"
                             : "+r"(val[i]), "+r"(tg[i]) : "l"(base + off[i]), "r"(tag) : "memory");
        }
        bool ok = true;
#pragma unroll
        for (int i = 0; i < N; i++) ok = ok && tg[i] == tag;
        if (__all_sync(0xffffffffu, ok)) break;
        if (++it > SPIN_LIMIT) __trap();
        __nanosleep(100);
    }
}
__device__ __forceinline__ void st_pk16(uint4* p, uint32_t a, uint32_t b, uint32_t c, uint32_t tag) {
    asm volatile(
        "{\n.reg .b128 t;\n.reg .b64 lo, hi;\nmov.b64 lo, {%1, %2};\nmov.b64 hi, {%3, %4};\nmov.b128 t, {lo, hi};\n"
        "st.relaxed.gpu.global.b128 [%0], t;\n}" ::"l"(p), "r"(a), "r"(b), "r"(c), "r"(tag)
        : "memory");
}
template <int OFF = 0>
__device__ __forceinline__ uint4 ld_raw16p(const uint4* p, uint32_t on) {
    uint4 v;
    asm volatile(
        "{\n.reg .b128 t;\n.reg .b64 lo, hi;\n.reg .pred q;\nsetp.ne.u32 q, %5, 0;\n"
        "mov.b64 lo, 0;\nmov.b128 t, {lo, lo};\n"
        "@q ld.relaxed.gpu.global.b128 t, [%4 + %6];\nmov.b128 {lo, hi}, t;\n"
        "mov.b64 {%0, %1}, lo;\nmov.b64 {%2, %3}, hi;\n}"
        : "=r"(v.x), "=r"(v.y), "=r"(v.z), "=r"(v.w)
        : "l"(p), "r"(on), "n"(OFF * 16)
        : "memory");
    return v;
}
template <int OFF>
__device__ __forceinline__ void ld_fresh16(uint4& v, const uint4* p, uint32_t tag, uint32_t on) {
    asm volatile(
        "{\n.reg .b128 t;\n.reg .b64 lo, hi;\n.reg .pred q;\nsetp.ne.u32 q, %3, %5;\nsetp.ne.and.u32 q, %6, 0, q;\n"
        "mov.b64 lo, {%0, %1};\nmov.b64 hi, {%2, %3};\nmov.b128 t, {lo, hi};\n"
        "@q ld.relaxed.gpu.global.b128 t, [%4 + %7];\nmov.b128 {lo, hi}, t;\n"
        "mov.b64 {%0, %1}, lo;\nmov.b64 {%2, %3}, hi;\n}"
        : "+r"(v.x), "+r"(v.y), "+r"(v.z), "+r"(v.w)
        : "l"(p), "r"(tag), "r"(on), "n"(OFF * 16)
        : "memory");
}
template <int N, int STRIDE, int I = 0>
struct FreshN {
    static __device__ __forceinline__ void run(uint4* v, const uint4* p, uint32_t tag, bool live, int base, int step, int lim) {
        ld_fresh16<I * STRIDE>(v[I], p, tag, live && base + step * I < lim);
        FreshN<N, STRIDE, I + 1>::run(v, p, tag, live, base, step, lim);
    }
};
template <int N, int STRIDE>
struct FreshN<N, STRIDE, N> {
    static __device__ __forceinline__ void run(uint4*, const uint4*, uint32_t, bool, int, int, int) {}
};
template <int N, int STRIDE, int I = 0>
struct LoadN {
    static __device__ __forceinline__ void run(uint4* v, const uint4* p, bool live, int base, int step, int lim) {
        v[I] = ld_raw16p<I * STRIDE>(p, live && base + step * I < lim);
        LoadN<N, STRIDE, I + 1>::run(v, p, live, base, step, lim);
    }
};
template <int N, int STRIDE>
struct LoadN<N, STRIDE, N> {
    static __device__ __forceinline__ void run(uint4*, const uint4*, bool, int, int, int) {}
};
__device__ __forceinline__ void st_zero16(void* p) {
    asm volatile("st.relaxed.gpu.global.v4.u32 [%0], {%1, %1, %1, %1};" ::"l"(p), "r"(0u) : "memory");
}
__device__ __forceinline__ float ex2(float x) {
    float y;
    asm("ex2.approx.ftz.f32 %0, %1;" : "=f"(y) : "f"(x));
    return y;
}
__device__ __forceinline__ float fsqrt(float x) {
    float y;
    asm("sqrt.approx.ftz.f32 %0, %1;" : "=f"(y) : "f"(x));
    return y;
}
__device__ __forceinline__ float frcp(float x) {
    float y;
    asm("rcp.approx.ftz.f32 %0, %1;" : "=f"(y) : "f"(x));
    return y;
}
constexpr float LOG2E = 1.4426950408889634f;
__device__ __forceinline__ float silu(float a) { return a * frcp(1.0f + ex2(-a * LOG2E)); }
__device__ __forceinline__ float warp_max(float v) {
    int k = __float_as_int(v);
    k ^= (k >> 31) & 0x7fffffff;
    k = __reduce_max_sync(0xffffffffu, k);
    k ^= (k >> 31) & 0x7fffffff;
    return __int_as_float(k);
}
__device__ __forceinline__ float warp_sum(float v) {
#pragma unroll
    for (int o = 16; o > 0; o >>= 1) v += __shfl_xor_sync(0xffffffffu, v, o);
    return v;
}

__device__ __forceinline__ void ln_stats(const float (&v)[20], float& mean_b, float& den_b) {
    float s = 0.f;
#pragma unroll
    for (int i = 0; i < 20; i++) s += v[i];
    s = warp_sum(s);
    float mean = s * (1.0f / 640.0f);
    float q = 0.f;
#pragma unroll
    for (int i = 0; i < 20; i++) { float d = v[i] - mean; q += d * d; }
    q = warp_sum(q);
    float var_b = bfr(q * (1.0f / 640.0f));
    mean_b = bfr(mean);
    den_b = bfr(fsqrt(bfr(var_b + 1e-5f)));
}

struct Window {
    uint32_t bar[WPRO];
    uint32_t par[WPRO];
    __device__ __forceinline__ void init(uint32_t dummy) {
#pragma unroll
        for (int i = 0; i < WPRO; i++) { bar[i] = dummy; par[i] = 1; }
    }
    __device__ __forceinline__ void push(uint32_t b, uint32_t p, bool wait = true, bool deep = false) {
        if (wait) mbar_wait(deep ? bar[0] : bar[WPRO - WIN], deep ? par[0] : par[WPRO - WIN]);
#pragma unroll
        for (int i = 0; i + 1 < WPRO; i++) { bar[i] = bar[i + 1]; par[i] = par[i + 1]; }
        bar[WPRO - 1] = b; par[WPRO - 1] = p;
    }
};

__global__ void __launch_bounds__(NTHREADS, 1)
fused_decode_kernel(const __grid_constant__ CUtensorMap tmK, const __grid_constant__ CUtensorMap tmV,
                    const __grid_constant__ CUtensorMap tmMod, const __grid_constant__ CUtensorMap tmWq,
                    const __grid_constant__ CUtensorMap tmWo, const __grid_constant__ CUtensorMap tmW1,
                    const __grid_constant__ CUtensorMap tmW3, const __grid_constant__ CUtensorMap tmW2,
                    const __nv_bfloat16* __restrict__ x_in, const __nv_bfloat16* __restrict__ c_in,
                    __nv_bfloat16* __restrict__ out) {
    extern __shared__ __align__(1024) uint8_t smem[];
    const uint32_t sb = smem_u32(smem);
    const int tid = threadIdx.x, wid = tid >> 5, lane = tid & 31;
    const int cta = blockIdx.x, G = gridDim.x;
    const int grp = cta % NG, rank = cta / NG;
    const uint32_t bars = sb + SM_BARS;
    auto BAR = [&](int i) { return bars + 8u * i; };
    volatile uint32_t* meta = reinterpret_cast<volatile uint32_t*>(smem + SM_META);

    uint32_t in_c0 = 0, in_x0 = 0, in_c1 = 0, in_x1 = 0, in_epoch = 0;
    {
        const bool mf = cta < 40;
        const int b0 = mf ? B_MOD : B_WQ;
        if (wid == 8) {
            if (lane == 0) {
                const CUtensorMap* tm = mf ? &tmMod : &tmWq;
                prefetch_tm(tm);
#pragma unroll 1
                for (int i = 0; i < 4; i++) mbar_init(BAR(b0 + i), 1);
                asm volatile("fence.mbarrier_init.release.cluster;" ::: "memory");
                asm volatile("fence.proxy.async.shared::cta;" ::: "memory");
                if (cta < 128) {
#pragma unroll 1
                    for (int i = 0; i < 4; i++) {
                        const uint32_t bar = BAR(b0 + i);
                        mbar_expect_tx(bar, mf ? 10240 : 12288);
                        tma2d(sb + (mf ? SM_WMOD + i * 10240 : SM_WQ + i * 12288), tm, cta * (mf ? 32 : 48), i * (mf ? 160 : 128), bar);
                    }
                }
                asm volatile("ld.relaxed.gpu.global.u32 %0, [%1];" : "=r"(in_epoch) : "l"(&g_epoch) : "memory");
            }
        } else {
            const uint32_t* cg = reinterpret_cast<const uint32_t*>(c_in);
            const uint32_t* xg = reinterpret_cast<const uint32_t*>(x_in);
            in_c0 = __ldg(cg + tid); in_x0 = __ldg(xg + tid);
            if (tid < 64) { in_c1 = __ldg(cg + 256 + tid); in_x1 = __ldg(xg + 256 + tid); }
            if (tid == 0) asm volatile("ld.relaxed.gpu.global.u32 %0, [%1];" : "=r"(in_epoch) : "l"(&g_epoch) : "memory");
            if (lane == 0) {
#pragma unroll 1
                for (int i = wid; i < B_LAST; i += 8) {
                    if (i >= b0 && i < b0 + 4) continue;
                    mbar_init(BAR(i), (i >= B_EMPTY && i < B_MOD) ? 2 : ((i >= B_FLF && i < B_FLE) ? 4 : 1));
                }
                asm volatile("fence.mbarrier_init.release.cluster;" ::: "memory");
                asm volatile("fence.proxy.async.shared::cta;" ::: "memory");
            }
        }
    }
    __syncwarp();
    __syncthreads();
    if (sb & 1023u) __trap();

    if (wid == 8) {
        if (tid == 256) {
            Window win;
            const unsigned epoch = in_epoch;
            prefetch_tm(&tmWq); prefetch_tm(&tmMod); prefetch_tm(&tmK); prefetch_tm(&tmV);
            const int nmod = cta < 120 ? 4 : 0, nwq = cta < 128 ? 5 : 0;
            win.init(BAR(B_DUMMY));
            prefetch_tm(&tmWo); prefetch_tm(&tmW1); prefetch_tm(&tmW3); prefetch_tm(&tmW2);
            unsigned* ctr = &g_ctr[epoch & 1][grp * 32];
            unsigned* gctr = &g_ctr[epoch & 1][NG * 32];
            if (cta == 0) {
                for (int g = 0; g <= NG; g++) g_ctr[(epoch + 1) & 1][g * 32] = 0;
            }
            unsigned pend = atomicAdd(ctr, 1);
#pragma unroll 1
            for (int i = 0; i < nmod + nwq; i++) {
                const bool is_mod = cta < 40 ? i < nmod : i >= nwq;
                const int j = cta < 40 ? (is_mod ? i : i - nmod) : (is_mod ? i - nwq : i);
                const uint32_t bar = BAR((is_mod ? B_MOD : B_WQ) + j);
                win.push(bar, 0, i >= 4, true);
                if (i >= 4) {
                    mbar_expect_tx(bar, is_mod ? 10240 : 12288);
                    if (is_mod) tma2d(sb + SM_WMOD + j * 10240, &tmMod, cta * 32, j * 160, bar);
                    else tma2d(sb + SM_WQ + j * 12288, &tmWq, cta * 48, j * 128, bar);
                }
            }
            uint64_t pol;
            asm volatile("createpolicy.fractional.L2::evict_first.b64 %0, 1.0;" : "=l"(pol));
            int s = 0; uint32_t par = 0;
            int run = -1, last_head = -1;
            bool glob = false;
#pragma unroll 1
            while (true) {
                unsigned t = pend;
                if (!glob && t >= (unsigned)GT) { glob = true; t = atomicAdd(gctr, 1); }
                if (glob && t >= (unsigned)PT) break;
                pend = atomicAdd(glob ? gctr : ctr, 1);
                const int hl = t / TPH, tile = t % TPH;
                const int head = glob ? NG * GH + hl : grp * GH + hl;
                const int qidx = glob ? GH + hl : hl;
                if (head != last_head) { last_head = head; run++; meta[16 + run] = head; }
                const int line0 = (head * SK + tile * TILE) * 3;
#pragma unroll 1
                for (int kv = 0; kv < 2; kv++) {
                    win.push(BAR(B_FULL + s), par);
                    mbar_wait(BAR(B_EMPTY + s), par ^ 1);
                    meta[s] = run | (qidx << 8);
                    mbar_expect_tx(BAR(B_FULL + s), CHUNK);
                    tma2d_hint(sb + SM_RING + s * CHUNK, kv ? &tmV : &tmK, 0, line0, BAR(B_FULL + s), pol);
                    if (++s == NSLOT) { s = 0; par ^= 1; }
                }
            }
            meta[16 + run + 1] = 0xFFu;
#pragma unroll 1
            for (int e = 0; e < 2; e++) {
                mbar_wait(BAR(B_EMPTY + s), par ^ 1);
                meta[s] = (run + 1) | META_END;
                mbar_arrive(BAR(B_FULL + s));
                if (++s == NSLOT) { s = 0; par ^= 1; }
                if (++s == NSLOT) { s = 0; par ^= 1; }
            }
            if (cta < 128) {
                mbar_wait(BAR(B_PRO), 0);
#pragma unroll 1
                for (int i = 0; i < 5; i++) {
                    win.push(BAR(B_WO + i), 0);
                    mbar_expect_tx(BAR(B_WO + i), 12288);
                    tma2d(sb + SM_WO + (2 * i) * 6144, &tmWo, (2 * i) * 64, cta * 48, BAR(B_WO + i));
                    tma2d(sb + SM_WO + (2 * i + 1) * 6144, &tmWo, (2 * i + 1) * 64, cta * 48, BAR(B_WO + i));
                }
                if (cta < 96) {
#pragma unroll 1
                    for (int i = 0; i < 4; i++) {
                        const int m = i & 1, hf = i >> 1;
                        const uint32_t bar = BAR((m ? B_W3 : B_W1) + hf);
                        const uint32_t dst = sb + (m ? SM_W3 : SM_W1) + hf * 10240;
                        const CUtensorMap* tm = m ? &tmW3 : &tmW1;
                        win.push(bar, 0);
                        mbar_expect_tx(bar, 10240);
                        tma2d(dst, tm, cta * 16, hf * 320, bar);
                        tma2d(dst + 5120, tm, cta * 16, hf * 320 + 160, bar);
                    }
#pragma unroll 1
                    for (int i = 0; i < 2; i++) {
                        win.push(BAR(B_W2 + i), 0);
                        mbar_wait(BAR(B_EMPTY + s), par ^ 1);
                        meta[10 + i] = s;
                        mbar_expect_tx(BAR(B_W2 + i), 10240);
#pragma unroll 1
                        for (int b = 0; b < 5; b++)
                            tma2d(sb + SM_RING + s * CHUNK + b * 2048, &tmW2, (5 * i + b) * 64, cta * 16, BAR(B_W2 + i));
                        if (++s == NSLOT) { s = 0; par ^= 1; }
                    }
                }
            }
        }
    } else {
    const int g4 = lane >> 2, j4 = lane & 3, mi = lane >> 3, l8 = lane & 7;
    uint32_t* sc32 = reinterpret_cast<uint32_t*>(smem + SM_SC);
    uint32_t* h32 = reinterpret_cast<uint32_t*>(smem + SM_H);
    uint32_t* x32 = reinterpret_cast<uint32_t*>(smem + SM_X);
    uint32_t* q32 = reinterpret_cast<uint32_t*>(smem + SM_Q);
    float* red = reinterpret_cast<float*>(smem + SM_RED);
    float* stage = reinterpret_cast<float*>(smem + SM_STAGE);
    float* own = reinterpret_cast<float*>(smem + SM_OWN);

    uint32_t tag;
    bool live = true;
    {
        const uint32_t c0 = in_c0, x0 = in_x0, c1 = in_c1, x1 = in_x1, epoch = in_epoch;
        if (cta < 120 && tid >= 128 && tid < 136) st_zero16(reinterpret_cast<uint4*>(&g_mod[cta * 16]) + (tid - 128));
        if (cta < 128 && tid >= 32 && tid < 44) st_zero16(reinterpret_cast<uint4*>(&g_q[cta * 24]) + (tid - 32));
        sc32[tid] = pack_bf(silu(bf_lo(c0)), silu(bf_hi(c0))); x32[tid] = x0;
        if (tid < 64) { sc32[256 + tid] = pack_bf(silu(bf_lo(c1)), silu(bf_hi(c1))); x32[256 + tid] = x1; }
        if (tid == 0) meta[8] = epoch + 1;
    }
    bar_cons();
    tag = meta[8];
    float mean_x = 0.f, rden_x = 1.f;
    if (cta < 128) {
        float xv[20];
#pragma unroll
        for (int i = 0; i < 10; i++) { uint32_t v = x32[lane + 32 * i]; xv[2 * i] = bf_lo(v); xv[2 * i + 1] = bf_hi(v); }
        float den;
        ln_stats(xv, mean_x, den);
        rden_x = frcp(den);
    }

#pragma unroll 1
    for (int step = 0; step < 2; step++) {
    if (wid >= 4 && (step == 0 ? cta < 40 : (cta >= 40 && cta < 120))) {
        const int w4 = wid - 4;
        float acc[2][4] = {};
        const uint32_t base = sb + SM_WMOD + w4 * 10240;
        mbar_wait(BAR(B_MOD + w4), 0);
#pragma unroll
        for (int hf = 0; hf < 2; hf++) {
            uint32_t a[5][2][4], bb[5][2];
#pragma unroll
            for (int ks = 0; ks < 5; ks++) {
                const int r0 = w4 * 160 + hf * 80 + ks * 16;
                bb[ks][0] = sc32[(r0 >> 1) + j4]; bb[ks][1] = sc32[(r0 >> 1) + 4 + j4];
                const int r = hf * 80 + ks * 16 + l8 + 8 * (mi >> 1);
#pragma unroll
                for (int mt = 0; mt < 2; mt++) ldsm4t(a[ks][mt], base + r * 64 + (((2 * mt + (mi & 1)) ^ ((r >> 1) & 3)) << 4));
            }
#pragma unroll
            for (int ks = 0; ks < 5; ks++) { mma16816(acc[0], a[ks][0], bb[ks][0], bb[ks][1]); mma16816(acc[1], a[ks][1], bb[ks][0], bb[ks][1]); }
        }
        float* red2 = reinterpret_cast<float*>(smem + SM_FIN);
        if (j4 == 0) {
#pragma unroll
            for (int mt = 0; mt < 2; mt++) { red2[w4 * 32 + mt * 16 + g4] = acc[mt][0]; red2[w4 * 32 + mt * 16 + 8 + g4] = acc[mt][2]; }
        }
        asm volatile("bar.sync 3, 128;" ::: "memory");
        if (wid == 4) {
            float v = (red2[lane] + red2[32 + lane]) + (red2[64 + lane] + red2[96 + lane]);
            float o = __shfl_down_sync(0xffffffffu, v, 1);
            if (!(lane & 1)) st_pk8(&g_mod[cta * 16 + (lane >> 1)], pack_bf(v, o), tag);
            if (step == 1 && lane == 0) mbar_arrive(BAR(B_PRO));
        }
    }
    if (step == 1) break;
    if (cta < 128) {
        {
            const int off[4] = {tid, 320 + tid, tid < 64 ? 256 + tid : tid, tid < 64 ? 576 + tid : 320 + tid};
            uint32_t val[4];
            poll8<4>(g_mod, off, val, tag);
#pragma unroll
            for (int rep = 0; rep < 2; rep++) {
                int p = tid + rep * 256;
                if (p < 320) {
                    uint32_t sa = val[2 * rep], ca = val[2 * rep + 1];
                    uint32_t xx = x32[p];
                    float n0 = bfr(bfr(bf_lo(xx) - mean_x) * rden_x), n1 = bfr(bfr(bf_hi(xx) - mean_x) * rden_x);
                    float h0 = bfr(n0 * bfr(1.0f + bf_lo(ca))) + bf_lo(sa);
                    float h1 = bfr(n1 * bfr(1.0f + bf_hi(ca))) + bf_hi(sa);
                    h32[p] = pack_bf(h0, h1);
                }
            }
        }
        bar_cons();
        float acc[3][4] = {};
        uint32_t a[5][3][4], bb[5][2];
#pragma unroll
        for (int ks = 0; ks < 5; ks++) {
            const int r0 = wid * 80 + ks * 16;
            bb[ks][0] = h32[(r0 >> 1) + j4]; bb[ks][1] = h32[(r0 >> 1) + 4 + j4];
        }
        mbar_wait(BAR(B_WQ + ((wid * 80) >> 7)), 0);
        mbar_wait(BAR(B_WQ + ((wid * 80 + 79) >> 7)), 0);
#pragma unroll
        for (int ks = 0; ks < 5; ks++) {
            const int r = wid * 80 + ks * 16 + l8 + 8 * (mi >> 1);
#pragma unroll
            for (int mt = 0; mt < 3; mt++) ldsm4t(a[ks][mt], sb + SM_WQ + r * 96 + ((2 * mt + (mi & 1)) << 4));
        }
#pragma unroll
        for (int ks = 0; ks < 5; ks++) {
#pragma unroll
            for (int mt = 0; mt < 3; mt++) mma16816(acc[mt], a[ks][mt], bb[ks][0], bb[ks][1]);
        }
        if (j4 == 0) {
#pragma unroll
            for (int mt = 0; mt < 3; mt++) { red[wid * 64 + mt * 16 + g4] = acc[mt][0]; red[wid * 64 + mt * 16 + 8 + g4] = acc[mt][2]; }
        }
        bar_cons();
        if (tid < 64) {
            float v = 0.f;
            if (tid < 48) {
#pragma unroll
                for (int w = 0; w < 8; w++) v += red[w * 64 + tid];
            }
            float o = __shfl_down_sync(0xffffffffu, v, 1);
            if (tid < 48 && !(tid & 1)) st_pk8(&g_q[cta * 24 + (tid >> 1)], pack_bf(v, o), tag);
        }
    }
    {
        int off[5];
#pragma unroll
        for (int j = 0; j < 5; j++) {
            int p = tid + 256 * j;
            if (p >= NQH * 96) p = tid;
            off[j] = p < GH * 96 ? grp * GH * 96 + p : NG * GH * 96 + (p - GH * 96);
        }
        uint32_t val[5];
        poll8<5>(g_q, off, val, tag);
#pragma unroll
        for (int j = 0; j < 5; j++)
            if (tid + 256 * j < NQH * 96) q32[tid + 256 * j] = val[j];
    }
    bar_cons();
    if (tid == 0 && !(cta >= 40 && cta < 120)) mbar_arrive(BAR(B_PRO));
    }

    if (wid < 4) {
        const int pair = wid >> 1, half = wid & 1;
        uint32_t offK[3], offV[3];
        {
            const int rowK = half * 16 + l8 + 8 * (mi & 1), hiK = mi >> 1;
            const int rowV = half * 16 + l8 + 8 * (mi >> 1), hiV = mi & 1;
#pragma unroll
            for (int t = 0; t < 3; t++) {
                offK[t] = (rowK * 3 + t) * 128 + ((hiK ^ ((rowK * 3 + t) & 7)) << 4);
                offV[t] = (rowV * 3 + t) * 128 + ((hiV ^ ((rowV * 3 + t) & 7)) << 4);
                asm volatile("" : "+r"(offK[t]), "+r"(offV[t]));
            }
        }
        float acc[12][4];
#pragma unroll
        for (int i = 0; i < 12; i++) { acc[i][0] = acc[i][1] = acc[i][2] = acc[i][3] = 0.f; }
        float m_run = NEG_BIG, l_run = 0.f;
        uint32_t qf[12][2];
#pragma unroll
        for (int i = 0; i < 12; i++) { qf[i][0] = qf[i][1] = 0; }
        int cur = -1, flushed = 0, cnt = 0;
        int s = 2 * pair; uint32_t par = 0;
        int fb = 0; uint32_t fpar = 1;
        uint32_t ready = 0;
#pragma unroll 1
        while (true) {
            if (!ready) mbar_wait(BAR(B_FULL + s), par);
            const uint32_t mt_ = meta[s];
            const int run = mt_ & 0xff;
            if (run != cur) {
#pragma unroll 1
                while (flushed < run) {
                    const uint32_t fle = mbar_try(BAR(B_FLE + fb), fpar);
                    float* mb = reinterpret_cast<float*>(smem + SM_MERGE) + (fb * 4 + wid) * 200;
                    if (flushed != cur) {
#pragma unroll
                        for (int i = 0; i < 12; i++) { acc[i][0] = acc[i][2] = 0.f; }
                        m_run = NEG_BIG; l_run = 0.f; cnt = 0;
                    }
                    float l = l_run;
                    l += __shfl_xor_sync(0xffffffffu, l, 4);
                    l += __shfl_xor_sync(0xffffffffu, l, 8);
                    l += __shfl_xor_sync(0xffffffffu, l, 16);
                    if (!fle) mbar_wait(BAR(B_FLE + fb), fpar);
                    if (j4 == 0) {
#pragma unroll
                        for (int i = 0; i < 12; i++) { mb[4 + 16 * i + g4] = acc[i][0]; mb[4 + 16 * i + 8 + g4] = acc[i][2]; }
                    }
                    if (lane == 0) { mb[0] = m_run; mb[1] = l; mb[2] = __int_as_float(cnt); }
                    __syncwarp();
                    if (lane == 0) mbar_arrive(BAR(B_FLF + fb));
                    if (++fb == NBUF) { fb = 0; fpar ^= 1; }
                    flushed++;
                    cur = -1;
                }
                if (mt_ & META_END) {
                    if (flushed == 0 && lane == 0) mbar_arrive(BAR(B_FLF));
                    break;
                }
                cur = run;
                const int qi = (mt_ >> 8) & 0xff;
#pragma unroll
                for (int i = 0; i < 12; i++) { acc[i][0] = acc[i][1] = acc[i][2] = acc[i][3] = 0.f; }
                m_run = NEG_BIG; l_run = 0.f; cnt = 0;
#pragma unroll
                for (int ks = 0; ks < 12; ks++) {
                    qf[ks][0] = q32[qi * 96 + ks * 8 + j4];
                    qf[ks][1] = q32[qi * 96 + ks * 8 + 4 + j4];
                }
            }
            cnt++;
            const uint32_t kb = sb + SM_RING + s * CHUNK;
            int sv = s + 1; uint32_t parv = par;
            if (sv == NSLOT) { sv = 0; parv ^= 1; }
            float sc[6][4] = {};
            uint32_t vready;
            {
                uint32_t a[12][4];
#pragma unroll
                for (int t = 0; t < 3; t++) {
                    const uint32_t bt = kb + offK[t];
#pragma unroll
                    for (int kk = 0; kk < 4; kk++) ldsm4(a[t * 4 + kk], bt ^ (kk << 5));
                }
                vready = mbar_try(BAR(B_FULL + sv), parv);
#pragma unroll
                for (int i = 0; i < 12; i++) mma16816(sc[i % 6], a[i], qf[i][0], qf[i][1]);
            }
            __syncwarp();
            if (lane == 0) mbar_arrive(BAR(B_EMPTY + s));
            const float scale = 0.07216878364870322f;
            float s0 = bfr(bfr(((sc[0][0] + sc[1][0]) + (sc[2][0] + sc[3][0])) + (sc[4][0] + sc[5][0])) * scale);
            float s1 = bfr(bfr(((sc[0][2] + sc[1][2]) + (sc[2][2] + sc[3][2])) + (sc[4][2] + sc[5][2])) * scale);
            const float tm = warp_max(fmaxf(s0, s1));
            if (tm > m_run) {
                float alpha = ex2((m_run - tm) * LOG2E);
                l_run *= alpha;
#pragma unroll
                for (int i = 0; i < 12; i++) { acc[i][0] *= alpha; acc[i][1] *= alpha; acc[i][2] *= alpha; acc[i][3] *= alpha; }
                m_run = tm;
            }
            float p0 = ex2((s0 - m_run) * LOG2E);
            float p1 = ex2((s1 - m_run) * LOG2E);
            l_run += p0 + p1;
            const uint32_t pw = pack_bf(p0, p1);
            const uint32_t pa = __shfl_sync(0xffffffffu, pw, 8 * j4), pb = __shfl_sync(0xffffffffu, pw, 8 * j4 + 4);
            const uint32_t b0 = __byte_perm(pa, pb, 0x5410), b1 = __byte_perm(pa, pb, 0x7632);
            if (!vready) mbar_wait(BAR(B_FULL + sv), parv);
            s += 4;
            if (s >= NSLOT) { s -= NSLOT; par ^= 1; }
            ready = mbar_try(BAR(B_FULL + s), par);
            const uint32_t vb = sb + SM_RING + sv * CHUNK;
            {
                uint32_t a[12][4];
#pragma unroll
                for (int t = 0; t < 3; t++) {
                    const uint32_t bt = vb + offV[t];
#pragma unroll
                    for (int kk = 0; kk < 4; kk++) ldsm4t(a[t * 4 + kk], bt ^ (kk << 5));
                }
#pragma unroll
                for (int i = 0; i < 12; i++) mma16816(acc[i], a[i], b0, b1);
            }
            __syncwarp();
            if (lane == 0) mbar_arrive(BAR(B_EMPTY + sv));
        }
    } else if (wid == 4) {
        int fb = 0; uint32_t fpar = 0;
        mbar_wait(BAR(B_CLR), 0);
#pragma unroll 1
        for (int f = 0;; f++) {
            const float* mb = reinterpret_cast<const float*>(smem + SM_MERGE) + fb * 800;
            mbar_wait(BAR(B_FLF + fb), fpar);
            const int head = (int)meta[16 + f];
            if (head == 0xFF) break;
            float m0 = mb[0], m1 = mb[200], m2 = mb[400], m3 = mb[600];
            float M = fmaxf(fmaxf(m0, m1), fmaxf(m2, m3));
            float w0 = ex2((m0 - M) * LOG2E), w1 = ex2((m1 - M) * LOG2E);
            float w2 = ex2((m2 - M) * LOG2E), w3 = ex2((m3 - M) * LOG2E);
            const int idx = head < NG * GH ? rank : cta;
            uint4* dst = &g_dat[head][idx][0];
            float o[6];
#pragma unroll
            for (int i = 0; i < 6; i++) {
                int d = 4 + (i < 3 ? 3 * lane + i : 96 + 3 * lane + (i - 3));
                o[i] = w0 * mb[d] + w1 * mb[200 + d] + w2 * mb[400 + d] + w3 * mb[600 + d];
            }
            float L = w0 * mb[1] + w1 * mb[201] + w2 * mb[401] + w3 * mb[601];
            const uint32_t tiles = __float_as_int(mb[2]) + __float_as_int(mb[402]);
            st_pk16(dst + lane, __float_as_uint(o[0]), __float_as_uint(o[1]), __float_as_uint(o[2]), tag);
            st_pk16(dst + 32 + lane, __float_as_uint(o[3]), __float_as_uint(o[4]), __float_as_uint(o[5]), tag);
            if (lane == 0) st_pk16(&g_hdr[head][idx], __float_as_uint(M), __float_as_uint(L), tiles, tag);
            __syncwarp();
            if (lane == 0) mbar_arrive(BAR(B_FLE + fb));
            if (++fb == NBUF) { fb = 0; fpar ^= 1; }
            if (meta[16 + f + 1] == 0xFFu) break;
        }
    } else if (wid == 5) {
        if (cta < 128) {
            if (lane < 2) st_zero16(&g_es[cta][lane]);
#pragma unroll 1
            for (int i = lane; i < 256; i += 32) {
                st_zero16(cta >= 128 - NLATE ? &g_late[cta - (128 - NLATE)][i >> 1][i & 1] : &g_h1[i >> 1][cta][i & 1]);
                if (cta < 96) st_zero16(&g_h3[i >> 1][cta][i & 1]);
            }
        }
#pragma unroll 1
        for (int f = 0; f < NQH; f++) {
            const int head = f < GH ? grp * GH + f : NG * GH + (f - GH);
            const int idx = f < GH ? rank : cta;
            st_zero16(&g_dat[head][idx][lane]);
            st_zero16(&g_dat[head][idx][32 + lane]);
            if (lane == 0) st_zero16(&g_hdr[head][idx]);
        }
        __syncwarp();
        if (lane == 0) mbar_arrive(BAR(B_CLR));
    } else {
        if (cta < 128) {
            const int t = tid - 192;
            uint32_t* cb32 = reinterpret_cast<uint32_t*>(smem + SM_CB);
            uint32_t* sb32 = reinterpret_cast<uint32_t*>(smem + SM_SB);
            uint32_t* ga32 = reinterpret_cast<uint32_t*>(smem + SM_GA);
            const int col = cta * 5 + t;
            int off[16];
            uint32_t val[16];
#pragma unroll
            for (int rep = 0; rep < 5; rep++) { off[3 * rep] = 960 + t + 64 * rep; off[3 * rep + 1] = 1280 + t + 64 * rep; off[3 * rep + 2] = 640 + t + 64 * rep; }
            off[15] = t < 5 ? (3200 + col) >> 1 : 960;
            poll8<16>(g_mod, off, val, tag);
#pragma unroll
            for (int rep = 0; rep < 5; rep++) {
                sb32[t + 64 * rep] = val[3 * rep];
                cb32[t + 64 * rep] = pack_bf(1.0f + bf_lo(val[3 * rep + 1]), 1.0f + bf_hi(val[3 * rep + 1]));
                ga32[t + 64 * rep] = val[3 * rep + 2];
            }
            if (t < 5) own[8 + t] = (col & 1) ? bf_hi(val[15]) : bf_lo(val[15]);
        }
        live = false;
    }
    const uint32_t sb0 = sb;
    const int tid0 = tid;
#pragma unroll 1
    while (cta < 128) {
        uint32_t sb = sb0; int tid = tid0;
        asm volatile("" : "+r"(sb), "+r"(tid));
        const int wid = tid >> 5, lane = tid & 31;
        const int g4 = lane >> 2, j4 = lane & 3, mi = lane >> 3, l8 = lane & 7;
        if (wid >= 5) {
            const int h = cta >> 2, js = cta & 3;
            const bool gl = h >= NG * GH;
            const int ncand = gl ? G : (G - h / GH + NG - 1) / NG;
            const int k = lane & 15, rr = (wid - 5) * 2 + (lane >> 4);
            if (live) {
                const unsigned* cp = &g_ctr[(tag - 1) & 1][(gl ? NG : h / GH) * 32];
                const unsigned thr = ((gl ? h - NG * GH : h % GH) + 1) * TPH;
                uint32_t it = 0;
                while (true) {
                    unsigned v;
                    asm volatile("ld.relaxed.gpu.global.u32 %0, [%1];" : "=r"(v) : "l"(cp) : "memory");
                    if (v >= thr) break;
                    __nanosleep(300);
                    if (++it > SPIN_LIMIT) __trap();
                }
            }
            const uint4* hdr = &g_hdr[h][lane];
            const uint4* dat = &g_dat[h][rr][16 * js + k];
            float* part = stage;
            float L, a0, a1, a2;
            uint32_t it = 0;
            uint4 hd[5], dv[MAXG / 6];
#pragma unroll
            for (int i = 0; i < 5; i++) hd[i] = make_uint4(0, 0, 0, 0);
#pragma unroll
            for (int i = 0; i < MAXG / 6; i++) dv[i] = make_uint4(0, 0, 0, 0);
#pragma unroll 1
            while (true) {
                FreshN<5, 32>::run(hd, hdr, tag, live, lane, 32, ncand);
                FreshN<MAXG / 6, 6 * 64>::run(dv, dat, tag, live, rr, 6, ncand);
                float w[5], M = NEG_BIG;
                int c = 0;
#pragma unroll
                for (int i = 0; i < 5; i++) {
                    const bool v = hd[i].w == tag;
                    w[i] = v ? __uint_as_float(hd[i].x) : NEG_BIG;
                    M = fmaxf(M, w[i]);
                    c += v ? (int)hd[i].z : 0;
                }
                c = __reduce_add_sync(0xffffffffu, c);
                if (++it > SPIN_LIMIT) __trap();
                if (live && c != TPH) continue;
                M = warp_max(M);
                float ls = 0.f;
#pragma unroll
                for (int i = 0; i < 5; i++) {
                    const bool v = w[i] != NEG_BIG;
                    const float e = ex2((w[i] - M) * LOG2E);
                    w[i] = v ? e : -0.0f;
                    ls = fmaf(w[i], __uint_as_float(hd[i].y), ls);
                }
                float* wsm = reinterpret_cast<float*>(smem + SM_X2) + (wid - 5) * 160;
                if (live) {
#pragma unroll
                    for (int i = 0; i < 5; i++) wsm[lane + 32 * i] = w[i];
                }
                __syncwarp();
                L = warp_sum(ls);
                uint32_t badm = 0;
                a0 = a1 = a2 = 0.f;
#pragma unroll
                for (int i = 0; i < MAXG / 6; i++) {
                    const float wi = wsm[rr + 6 * i];
                    badm |= (dv[i].w ^ tag) & ~(uint32_t)(__float_as_int(wi) >> 31);
                    a0 = fmaf(wi, __uint_as_float(dv[i].x), a0);
                    a1 = fmaf(wi, __uint_as_float(dv[i].y), a1);
                    a2 = fmaf(wi, __uint_as_float(dv[i].z), a2);
                }
                const bool bad = badm != 0;
                if (!__any_sync(0xffffffffu, bad) || !live) break;
            }
            a0 += __shfl_xor_sync(0xffffffffu, a0, 16);
            a1 += __shfl_xor_sync(0xffffffffu, a1, 16);
            a2 += __shfl_xor_sync(0xffffffffu, a2, 16);
            if (live && lane < 16) { float* pp = part + (wid - 5) * 48 + 3 * k; pp[0] = a0; pp[1] = a1; pp[2] = a2; }
            if (live) asm volatile("bar.sync 2, 96;" ::: "memory");
            if (wid == 5 || !live) {
                uint16_t* osw = reinterpret_cast<uint16_t*>(smem + SM_SC);
                const float inv = frcp(L);
                const float o0 = (part[lane] + part[48 + lane]) + part[96 + lane];
                const float o1 = (part[32 + (lane & 15)] + part[80 + (lane & 15)]) + part[128 + (lane & 15)];
                if (live) { osw[lane] = (uint16_t)(__float_as_uint(bfr(o0 * inv)) >> 16); if (lane < 16) osw[32 + lane] = (uint16_t)(__float_as_uint(bfr(o1 * inv)) >> 16); }
            }
        }
        if (wid < 5 || !live) {
            const int w5 = wid < 5 ? wid : wid - 5;
            uint32_t wa[8][3][4];
            if (live) mbar_wait(BAR(B_WO + w5), 0);
#pragma unroll
            for (int i = 0; i < 8; i++) {
                const int cc = 2 * (i & 3) + (mi & 1);
#pragma unroll
                for (int ks = 0; ks < 3; ks++) {
                    const int r = ks * 16 + l8 + 8 * (mi >> 1);
                    ldsm4t(wa[i][ks], sb + SM_WO + (2 * w5 + (i >> 2)) * 6144 + r * 128 + ((cc ^ (r & 7)) << 4));
                }
            }
            if (live) bar_cons();
            const uint32_t* os32 = reinterpret_cast<const uint32_t*>(smem + SM_SC);
            float acc[8][4] = {};
#pragma unroll
            for (int ks = 0; ks < 3; ks++) {
                const uint32_t b0 = os32[ks * 8 + j4], b1 = os32[ks * 8 + 4 + j4];
#pragma unroll
                for (int i = 0; i < 8; i++) mma16816(acc[i], wa[i][ks], b0, b1);
            }
            if (live && j4 == 0) {
#pragma unroll
                for (int i = 0; i < 8; i++) { stage[(w5 * 8 + i) * 16 + g4] = acc[i][0]; stage[(w5 * 8 + i) * 16 + 8 + g4] = acc[i][2]; }
            }
        } else {
            bar_cons();
        }
        if (live) bar_cons();
        {
            const int o = tid >> 1, kk = tid & 1;
            const float* sp = stage + o * 5 + kk * 3;
            float v0 = sp[0], v1 = sp[1], v2 = kk ? 0.f : sp[2];
            uint4* dst = cta >= 128 - NLATE ? &g_late[cta - (128 - NLATE)][o][kk] : &g_h1[o][cta][kk];
            if (live) st_pk16(dst, __float_as_uint(v0), __float_as_uint(v1), __float_as_uint(v2), tag);
        }
        if (wid == 0 || !live) {
            const uint4* p = &g_h1[cta][0][0] + lane;
            uint4 v[8];
#pragma unroll
            for (int j = 0; j < 8; j++) v[j] = make_uint4(0, 0, 0, 0);
            if (lane >= 32 - 2 * NLATE) v[7].w = tag;
            uint32_t it = 0;
            while (true) {
                FreshN<8, 32>::run(v, p, tag, live, 0, 0, 1);
                bool ok = true;
#pragma unroll
                for (int j = 0; j < 8; j++) ok = ok && v[j].w == tag;
                if (__all_sync(0xffffffffu, ok) || !live) break;
                if (++it > SPIN_LIMIT) __trap();
            }
            float a0, a1, a2;
            a0 = ((__uint_as_float(v[0].x) + __uint_as_float(v[1].x)) + (__uint_as_float(v[2].x) + __uint_as_float(v[3].x))) +
                 ((__uint_as_float(v[4].x) + __uint_as_float(v[5].x)) + (__uint_as_float(v[6].x) + __uint_as_float(v[7].x)));
            a1 = ((__uint_as_float(v[0].y) + __uint_as_float(v[1].y)) + (__uint_as_float(v[2].y) + __uint_as_float(v[3].y))) +
                 ((__uint_as_float(v[4].y) + __uint_as_float(v[5].y)) + (__uint_as_float(v[6].y) + __uint_as_float(v[7].y)));
            a2 = ((__uint_as_float(v[0].z) + __uint_as_float(v[1].z)) + (__uint_as_float(v[2].z) + __uint_as_float(v[3].z))) +
                 ((__uint_as_float(v[4].z) + __uint_as_float(v[5].z)) + (__uint_as_float(v[6].z) + __uint_as_float(v[7].z)));
#pragma unroll
            for (int o = 2; o <= 16; o <<= 1) {
                a0 += __shfl_xor_sync(0xffffffffu, a0, o);
                a1 += __shfl_xor_sync(0xffffffffu, a1, o);
                a2 += __shfl_xor_sync(0xffffffffu, a2, o);
            }
            if (live && lane < 2) st_pk16(&g_es[cta][lane], __float_as_uint(a0), __float_as_uint(a1), __float_as_uint(a2), tag);
        }
        float* x2s = reinterpret_cast<float*>(smem + SM_X2);
        {
            uint32_t a1[5][4], a3[5][4];
            if (live && cta < 96) mbar_wait3(BAR(B_W1 + (wid >> 2)), BAR(B_W3 + (wid >> 2)), BAR(B_W1 + (wid >> 2)));
#pragma unroll
            for (int ks = 0; ks < 5; ks++) {
                const int r = wid * 80 + ks * 16 + l8 + 8 * (mi >> 1);
                const uint32_t off = r * 32 + (((mi & 1) ^ ((r >> 2) & 1)) << 4);
                ldsm4t(a1[ks], sb + SM_W1 + off);
                ldsm4t(a3[ks], sb + SM_W3 + off);
            }
            const int o = tid >> 1, k = tid & 1, c0 = 5 * o + 3 * k;
            const uint16_t* x16 = reinterpret_cast<const uint16_t*>(smem + SM_X);
            const uint16_t* ga16 = reinterpret_cast<const uint16_t*>(smem + SM_GA);
            const uint16_t* cb16 = reinterpret_cast<const uint16_t*>(smem + SM_CB);
            const uint16_t* sb16 = reinterpret_cast<const uint16_t*>(smem + SM_SB);
            float xin[3], gin[3], cin[3], sin_[3];
#pragma unroll
            for (int e = 0; e < 3; e++) {
                const int c = c0 + ((e == 2 && k) ? 1 : e);
                xin[e] = __uint_as_float((uint32_t)x16[c] << 16); gin[e] = __uint_as_float((uint32_t)ga16[c] << 16);
                cin[e] = __uint_as_float((uint32_t)cb16[c] << 16); sin_[e] = __uint_as_float((uint32_t)sb16[c] << 16);
            }
            uint32_t w2o[5];
#pragma unroll
            for (int i = 0; i < 5; i++) {
                const int mt = (wid & 3) * 5 + i;
                const int cc = 2 * (mt & 3) + (mi & 1);
                const int r = l8 + 8 * (mi >> 1);
                w2o[i] = sb + SM_RING + (mt >> 2) * 2048 + r * 128 + ((cc ^ (r & 7)) << 4);
                asm volatile("" : "+r"(w2o[i]));
            }
            const uint32_t* hw = h32 + wid * 40 + j4;
            uint4 v[1 + NLATE];
#pragma unroll
            for (int j = 0; j <= NLATE; j++) v[j] = make_uint4(0, 0, 0, 0);
            const uint4* pe = &g_es[o][k];
            const uint4* pl = &g_late[0][o][k];
            uint32_t it = 0;
            while (true) {
                FreshN<1, 1>::run(v, pe, tag, live, 0, 0, 1);
                FreshN<NLATE, 256>::run(v + 1, pl, tag, live, 0, 0, 1);
                bool ok = true;
#pragma unroll
                for (int j = 0; j <= NLATE; j++) ok = ok && v[j].w == tag;
                if (__all_sync(0xffffffffu, ok) || !live) break;
                if (++it > SPIN_LIMIT) __trap();
            }
            float x2[3];
            x2[0] = (__uint_as_float(v[0].x) + (__uint_as_float(v[1].x) + __uint_as_float(v[2].x))) + (__uint_as_float(v[3].x) + __uint_as_float(v[4].x));
            x2[1] = (__uint_as_float(v[0].y) + (__uint_as_float(v[1].y) + __uint_as_float(v[2].y))) + (__uint_as_float(v[3].y) + __uint_as_float(v[4].y));
            x2[2] = (__uint_as_float(v[0].z) + (__uint_as_float(v[1].z) + __uint_as_float(v[2].z))) + (__uint_as_float(v[3].z) + __uint_as_float(v[4].z));
#pragma unroll
            for (int e = 0; e < 3; e++) x2[e] = bfr(xin[e] + bfr(gin[e] * bfr(x2[e])));
            if (live && o == cta) { x2s[3 * k] = x2[0]; x2s[3 * k + 1] = x2[1]; if (!k) x2s[2] = x2[2]; }
            float* st8 = red + 256;
            {
                const float pv = __shfl_sync(0xffffffffu, x2[0], 0);
                const float d0 = x2[0] - pv, d1 = x2[1] - pv, d2 = k ? 0.f : x2[2] - pv;
                float s1 = (d0 + d1) + d2;
                float s2 = fmaf(d0, d0, fmaf(d1, d1, d2 * d2));
#pragma unroll
                for (int q = 16; q > 0; q >>= 1) { s1 += __shfl_xor_sync(0xffffffffu, s1, q); s2 += __shfl_xor_sync(0xffffffffu, s2, q); }
                if (live && lane == 0) { st8[wid] = pv + s1 * (1.0f / 80.0f); st8[8 + wid] = s2 - s1 * s1 * (1.0f / 80.0f); }
            }
            if (live) bar_cons();
            if (cta < 96) {
            const float4 mA = *reinterpret_cast<const float4*>(st8), mB = *reinterpret_cast<const float4*>(st8 + 4);
            const float4 qA = *reinterpret_cast<const float4*>(st8 + 8), qB = *reinterpret_cast<const float4*>(st8 + 12);
            const float mean = (((mA.x + mA.y) + (mA.z + mA.w)) + ((mB.x + mB.y) + (mB.z + mB.w))) * 0.125f;
            const float u0 = mA.x - mean, u1 = mA.y - mean, u2 = mA.z - mean, u3 = mA.w - mean;
            const float u4 = mB.x - mean, u5 = mB.y - mean, u6 = mB.z - mean, u7 = mB.w - mean;
            const float m2 = (((qA.x + qA.y) + (qA.z + qA.w)) + ((qB.x + qB.y) + (qB.z + qB.w))) +
                             80.0f * (((u0 * u0 + u1 * u1) + (u2 * u2 + u3 * u3)) + ((u4 * u4 + u5 * u5) + (u6 * u6 + u7 * u7)));
            const float mean_b = bfr(mean);
            const float rden = frcp(bfr(fsqrt(bfr(bfr(m2 * (1.0f / 640.0f)) + 1e-5f))));
            {
                uint16_t* h16 = reinterpret_cast<uint16_t*>(smem + SM_H);
#pragma unroll
                for (int e = 0; e < 3; e++) {
                    const float n = bfr(bfr(x2[e] - mean_b) * rden);
                    const float hv = bfr(bfr(n * cin[e]) + sin_[e]);
                    if (live && !(e == 2 && k)) h16[c0 + e] = (uint16_t)(__float_as_uint(hv) >> 16);
                }
            }
            __syncwarp();
            const uint32_t w2ready = mbar_try(BAR(B_W2 + (wid >> 2)), 0);
            float ag[2][4] = {}, au[2][4] = {};
#pragma unroll
            for (int ks = 0; ks < 5; ks++) {
                const uint32_t b0 = hw[8 * ks], b1 = hw[8 * ks + 4];
                mma16816(ag[ks & 1], a1[ks], b0, b1);
                mma16816(au[ks & 1], a3[ks], b0, b1);
            }
            if (live && j4 == 0) {
                red[wid * 32 + g4] = ag[0][0] + ag[1][0]; red[wid * 32 + 8 + g4] = ag[0][2] + ag[1][2];
                red[wid * 32 + 16 + g4] = au[0][0] + au[1][0]; red[wid * 32 + 24 + g4] = au[0][2] + au[1][2];
            }
            uint32_t a2[5][4];
            if (live && !w2ready) mbar_wait(BAR(B_W2 + (wid >> 2)), 0);
            const uint32_t w2b = (meta[10 + (wid >> 2)] & (NSLOT - 1)) * CHUNK;
#pragma unroll
            for (int i = 0; i < 5; i++) ldsm4t(a2[i], w2o[i] + w2b);
            if (live) bar_cons();
            float v = ((red[lane] + red[32 + lane]) + (red[64 + lane] + red[96 + lane])) + ((red[128 + lane] + red[160 + lane]) + (red[192 + lane] + red[224 + lane]));
            v = bfr(v);
            float up = __shfl_down_sync(0xffffffffu, v, 16);
            float hact = bfr(bfr(silu(v)) * up);
            float e0 = __shfl_sync(0xffffffffu, hact, 2 * j4), e1 = __shfl_sync(0xffffffffu, hact, 2 * j4 + 1);
            float e2 = __shfl_sync(0xffffffffu, hact, 2 * j4 + 8), e3 = __shfl_sync(0xffffffffu, hact, 2 * j4 + 9);
            const uint32_t b0 = pack_bf(e0, e1), b1 = pack_bf(e2, e3);
            float acc[5][4] = {};
#pragma unroll
            for (int i = 0; i < 5; i++) mma16816(acc[i], a2[i], b0, b1);
            if (live && j4 == 0) {
#pragma unroll
                for (int i = 0; i < 5; i++) { stage[(wid * 5 + i) * 16 + g4] = acc[i][0]; stage[(wid * 5 + i) * 16 + 8 + g4] = acc[i][2]; }
            }
            if (live) bar_cons();
            const float* sp = stage + o * 5 + k * 3;
            float v0 = sp[0], v1 = sp[1], v2 = k ? 0.f : sp[2];
            if (live) st_pk16(&g_h3[o][cta][k], __float_as_uint(v0), __float_as_uint(v1), __float_as_uint(v2), tag);
            }
        }
        if (wid == 0 || !live) {
            const uint4* p = &g_h3[cta][0][0] + lane;
            const float gx = own[8 + (lane & 7)], xx = x2s[lane & 7];
            uint4 v[6];
            uint32_t it = 0;
            if (live && cta < 96) spin(POLL_DELAY);
            while (true) {
                bool ok = true;
                LoadN<6, 32>::run(v, p, live, 0, 0, 1);
#pragma unroll
                for (int j = 0; j < 6; j++) ok = ok && v[j].w == tag;
                if (__all_sync(0xffffffffu, ok) || !live) break;
                if (++it > SPIN_LIMIT) __trap();
            }
            float a0 = ((__uint_as_float(v[0].x) + __uint_as_float(v[1].x)) + (__uint_as_float(v[2].x) + __uint_as_float(v[3].x))) + (__uint_as_float(v[4].x) + __uint_as_float(v[5].x));
            float a1 = ((__uint_as_float(v[0].y) + __uint_as_float(v[1].y)) + (__uint_as_float(v[2].y) + __uint_as_float(v[3].y))) + (__uint_as_float(v[4].y) + __uint_as_float(v[5].y));
            float a2 = ((__uint_as_float(v[0].z) + __uint_as_float(v[1].z)) + (__uint_as_float(v[2].z) + __uint_as_float(v[3].z))) + (__uint_as_float(v[4].z) + __uint_as_float(v[5].z));
#pragma unroll
            for (int o = 2; o <= 16; o <<= 1) {
                a0 += __shfl_xor_sync(0xffffffffu, a0, o);
                a1 += __shfl_xor_sync(0xffffffffu, a1, o);
                a2 += __shfl_xor_sync(0xffffffffu, a2, o);
            }
            const float t0 = __shfl_sync(0xffffffffu, a0, lane >= 3), t1 = __shfl_sync(0xffffffffu, a1, lane >= 3);
            const float sum = (lane == 0 || lane == 3) ? t0 : (lane == 2 ? a2 : t1);
            const float y = xx + bfr(gx * bfr(sum));
            if (live && lane < 5) reinterpret_cast<uint16_t*>(out)[cta * 5 + lane] = (uint16_t)(__float_as_uint(bfr(y)) >> 16);
            if (live && cta == 0 && lane == 0) g_epoch = tag;
        }
        if (live) break;
        live = true;
    }
    }
}

typedef CUresult (*EncodeFn)(CUtensorMap*, CUtensorMapDataType, cuuint32_t, void*, const cuuint64_t*, const cuuint64_t*,
                             const cuuint32_t*, const cuuint32_t*, CUtensorMapInterleave, CUtensorMapSwizzle,
                             CUtensorMapL2promotion, CUtensorMapFloatOOBfill);

void make_map(EncodeFn enc, CUtensorMap* tm, const void* ptr, uint64_t cols, uint64_t rows, uint32_t box_c, uint32_t box_r,
              CUtensorMapSwizzle sw, CUtensorMapL2promotion prom) {
    cuuint64_t dims[2] = {cols, rows};
    cuuint64_t strides[1] = {cols * 2};
    cuuint32_t box[2] = {box_c, box_r};
    cuuint32_t es[2] = {1, 1};
    enc(tm, CU_TENSOR_MAP_DATA_TYPE_BFLOAT16, 2, const_cast<void*>(ptr), dims, strides, box, es,
        CU_TENSOR_MAP_INTERLEAVE_NONE, sw, prom, CU_TENSOR_MAP_FLOAT_OOB_FILL_NONE);
}

}

extern "C" void kernel_launch(void* const* d_in, const int* in_sizes, int n_in, void* d_out, int out_size) {
    (void)in_sizes; (void)n_in; (void)out_size;
    static EncodeFn enc = nullptr;
    static int num_sms = 0;
    if (!enc) {
        void* fn = nullptr;
        cudaDriverEntryPointQueryResult qr;
        cudaGetDriverEntryPoint("cuTensorMapEncodeTiled", &fn, cudaEnableDefault, &qr);
        enc = (EncodeFn)fn;
        cudaDeviceGetAttribute(&num_sms, cudaDevAttrMultiProcessorCount, 0);
        cudaFuncSetAttribute(fused_decode_kernel, cudaFuncAttributeMaxDynamicSharedMemorySize, SM_TOTAL);
    }
    CUtensorMap tmK, tmV, tmMod, tmWq, tmWo, tmW1, tmW3, tmW2;
    const uint64_t kv_lines = (uint64_t)NH * SK * 3;
    make_map(enc, &tmK, d_in[1], 64, kv_lines, 64, 96, CU_TENSOR_MAP_SWIZZLE_128B, CU_TENSOR_MAP_L2_PROMOTION_L2_128B);
    make_map(enc, &tmV, d_in[2], 64, kv_lines, 64, 96, CU_TENSOR_MAP_SWIZZLE_128B, CU_TENSOR_MAP_L2_PROMOTION_L2_128B);
    make_map(enc, &tmWq, d_in[3], NH * DH, D, 48, 128, CU_TENSOR_MAP_SWIZZLE_NONE, CU_TENSOR_MAP_L2_PROMOTION_L2_128B);
    make_map(enc, &tmWo, d_in[4], D, NH * DH, 64, 48, CU_TENSOR_MAP_SWIZZLE_128B, CU_TENSOR_MAP_L2_PROMOTION_L2_128B);
    make_map(enc, &tmW1, d_in[6], FF, D, 16, 160, CU_TENSOR_MAP_SWIZZLE_32B, CU_TENSOR_MAP_L2_PROMOTION_L2_128B);
    make_map(enc, &tmW3, d_in[7], FF, D, 16, 160, CU_TENSOR_MAP_SWIZZLE_32B, CU_TENSOR_MAP_L2_PROMOTION_L2_128B);
    make_map(enc, &tmW2, d_in[8], D, FF, 64, 16, CU_TENSOR_MAP_SWIZZLE_128B, CU_TENSOR_MAP_L2_PROMOTION_L2_128B);
    make_map(enc, &tmMod, d_in[10], 6 * D, D, 32, 160, CU_TENSOR_MAP_SWIZZLE_64B, CU_TENSOR_MAP_L2_PROMOTION_L2_128B);
    int grid = num_sms < MAXG ? num_sms : MAXG;
    fused_decode_kernel<<<grid, NTHREADS, SM_TOTAL, cudaStreamPerThread>>>(
        tmK, tmV, tmMod, tmWq, tmWo, tmW1, tmW3, tmW2, (const __nv_bfloat16*)d_in[0], (const __nv_bfloat16*)d_in[9],
        (__nv_bfloat16*)d_out);
}
```

```cpp
#include <cuda_runtime.h>
#include <cuda_bf16.h>
#include <cuda.h>
#include <stdint.h>

namespace {

constexpr int D = 640, NH = 32, SK = 8192, DH = 192, FF = 1536;
constexpr int NG = 4;
constexpr int GH = 7;
constexpr int NGLOB = NH - NG * GH;
constexpr int NQH = GH + NGLOB;
constexpr int TILE = 32;
constexpr int TPH = SK / TILE;
constexpr int GT = GH * TPH;
constexpr int PT = NGLOB * TPH;
constexpr int CHUNK = TILE * DH * 2;
constexpr int NSLOT = 8;
constexpr int WIN = 3;
constexpr int WPRO = 4;
constexpr int POLL_DELAY = 450;
constexpr int NBUF = 2;
constexpr int NLATE = 4;
constexpr int MAXG = 132;
constexpr int NTHREADS = 288;
constexpr float NEG_BIG = -3.402823466e38f;

constexpr int SM_WMOD = 0;
constexpr int SM_WQ = 40960;
constexpr int SM_WO = 0;
constexpr int SM_W1 = 61440;
constexpr int SM_W3 = 81920;
constexpr int SM_RING = 102400;
constexpr int SM_MISC = SM_RING + NSLOT * CHUNK;
constexpr int SM_BARS = SM_MISC;
constexpr int SM_META = SM_BARS + 512;
constexpr int SM_Q = SM_META + 128;
constexpr int SM_SC = SM_Q + NQH * DH * 2;
constexpr int SM_H = SM_SC + 1280;
constexpr int SM_X = SM_H + 1280;
constexpr int SM_CB = SM_X + 1280;
constexpr int SM_SB = SM_CB + 1280;
constexpr int SM_GA = SM_SB + 1280;
constexpr int SM_OWN = SM_GA + 1280;
constexpr int SM_RED = SM_OWN + 128;
constexpr int SM_MERGE = SM_RED + 2048;
constexpr int SM_STAGE = SM_MERGE + NBUF * 3200;
constexpr int SM_X2 = SM_STAGE + 2560;
constexpr int SM_FIN = SM_X2 + 2560;
constexpr int SM_TOTAL = SM_FIN + 512;
static_assert(SM_TOTAL <= 232448, "shared memory budget");

constexpr int B_FULL = 0;
constexpr int B_EMPTY = 8;
constexpr int B_MOD = 16;
constexpr int B_WQ = 20;
constexpr int B_WO = 25;
constexpr int B_W1 = 30;
constexpr int B_W3 = 32;
constexpr int B_W2 = 34;
constexpr int B_PRO = 36, B_DUMMY = 37, B_CLR = 38, B_QALL = 39;
constexpr int B_FLF = 40, B_FLE = 44;
constexpr int B_LAST = 48;
static_assert(NSLOT == 8 && NSLOT >= 6 && WIN <= WPRO && WIN <= NSLOT - 3 && NBUF <= 4, "barrier map / end markers vs window");
constexpr uint32_t META_END = 0x10000u;

__device__ unsigned g_epoch;
__device__ unsigned g_ctr[2][(NG + 1) * 32];
__device__ __align__(128) unsigned long long g_mod[1920];
__device__ __align__(128) unsigned long long g_q[3072];
__device__ __align__(128) uint4 g_hdr[NH][MAXG];
__device__ __align__(128) uint4 g_dat[NH][MAXG][64];
__device__ __align__(128) uint4 g_h1[128][128][2];
__device__ __align__(128) uint4 g_es[128][2];
__device__ __align__(128) uint4 g_late[NLATE][128][2];
__device__ __align__(128) uint4 g_h3[128][96][2];


__device__ __forceinline__ uint32_t smem_u32(const void* p) { return (uint32_t)__cvta_generic_to_shared(p); }
__device__ __forceinline__ void mbar_init(uint32_t bar, uint32_t cnt) {
    asm volatile("mbarrier.init.shared::cta.b64 [%0], %1;" ::"r"(bar), "r"(cnt) : "memory");
}
__device__ __forceinline__ void mbar_expect_tx(uint32_t bar, uint32_t bytes) {
    asm volatile("mbarrier.arrive.expect_tx.shared::cta.b64 _, [%0], %1;" ::"r"(bar), "r"(bytes) : "memory");
}
__device__ __forceinline__ void mbar_arrive(uint32_t bar) {
    asm volatile("mbarrier.arrive.shared::cta.b64 _, [%0];" ::"r"(bar) : "memory");
}
constexpr uint32_t SPIN_LIMIT = 1u << 22;
__device__ __forceinline__ void mbar_wait(uint32_t bar, uint32_t parity) {
    asm volatile(
        "{\n.reg .pred p;\n.reg .u32 c;\nmov.u32 c, 0;\n"
        "LW:\nmbarrier.try_wait.parity.shared::cta.b64 p, [%0], %1;\n@p bra LD;\n"
        "add.u32 c, c, 1;\nsetp.lt.u32 p, c, 0x400000;\n@p bra LW;\ntrap;\nLD:\n}" ::"r"(bar), "r"(parity)
        : "memory");
}
__device__ __forceinline__ uint32_t mbar_try(uint32_t bar, uint32_t parity) {
    uint32_t ok;
    asm volatile("{\n.reg .pred p;\nmbarrier.try_wait.parity.shared::cta.b64 p, [%1], %2;\nselp.u32 %0, 1, 0, p;\n}"
                 : "=r"(ok) : "r"(bar), "r"(parity) : "memory");
    return ok;
}
__device__ __forceinline__ void mbar_wait3(uint32_t b0, uint32_t b1, uint32_t b2) {
    asm volatile(
        "{\n.reg .pred p, q, r;\n.reg .u32 c;\nmov.u32 c, 0;\n"
        "LW:\nmbarrier.try_wait.parity.shared::cta.b64 p, [%0], 0;\n"
        "mbarrier.try_wait.parity.shared::cta.b64 q, [%1], 0;\n"
        "mbarrier.try_wait.parity.shared::cta.b64 r, [%2], 0;\n"
        "and.pred p, p, q;\nand.pred p, p, r;\n@p bra LD;\n"
        "add.u32 c, c, 1;\nsetp.lt.u32 p, c, 0x400000;\n@p bra LW;\ntrap;\nLD:\n}" ::"r"(b0), "r"(b1), "r"(b2)
        : "memory");
}
__device__ __forceinline__ void tma2d(uint32_t dst, const CUtensorMap* tm, int c0, int c1, uint32_t bar) {
    asm volatile(
        "cp.async.bulk.tensor.2d.shared::cluster.global.mbarrier::complete_tx::bytes [%0], [%1, {%3, %4}], [%2];" ::"r"(dst),
        "l"(tm), "r"(bar), "r"(c0), "r"(c1)
        : "memory");
}
__device__ __forceinline__ void tma2d_hint(uint32_t dst, const CUtensorMap* tm, int c0, int c1, uint32_t bar, uint64_t pol) {
    asm volatile(
        "cp.async.bulk.tensor.2d.shared::cluster.global.mbarrier::complete_tx::bytes.L2::cache_hint [%0], [%1, {%3, %4}], [%2], %5;" ::"r"(dst),
        "l"(tm), "r"(bar), "r"(c0), "r"(c1), "l"(pol)
        : "memory");
}
__device__ __forceinline__ void prefetch_tm(const CUtensorMap* tm) {
    asm volatile("prefetch.tensormap [%0];" ::"l"(tm) : "memory");
}
__device__ __forceinline__ void ldsm4(uint32_t (&r)[4], uint32_t addr) {
    asm volatile("ldmatrix.sync.aligned.m8n8.x4.shared.b16 {%0,%1,%2,%3}, [%4];"
                 : "=r"(r[0]), "=r"(r[1]), "=r"(r[2]), "=r"(r[3])
                 : "r"(addr));
}
__device__ __forceinline__ void ldsm4t(uint32_t (&r)[4], uint32_t addr) {
    asm volatile("ldmatrix.sync.aligned.m8n8.x4.trans.shared.b16 {%0,%1,%2,%3}, [%4];"
                 : "=r"(r[0]), "=r"(r[1]), "=r"(r[2]), "=r"(r[3])
                 : "r"(addr));
}
__device__ __forceinline__ void mma16816(float (&d)[4], const uint32_t (&a)[4], uint32_t b0, uint32_t b1) {
    asm volatile(
        "mma.sync.aligned.m16n8k16.row.col.f32.bf16.bf16.f32 {%0,%1,%2,%3}, {%4,%5,%6,%7}, {%8,%9}, {%0,%1,%2,%3};"
        : "+f"(d[0]), "+f"(d[1]), "+f"(d[2]), "+f"(d[3])
        : "r"(a[0]), "r"(a[1]), "r"(a[2]), "r"(a[3]), "r"(b0), "r"(b1));
}
__device__ __forceinline__ void bar_cons() { asm volatile("bar.sync 1, 256;" ::: "memory"); }
__device__ __forceinline__ void spin(int cycles) {
    long long t0 = clock64();
    while (clock64() - t0 < cycles) {}
}

__device__ __forceinline__ float bfr(float x) {
    uint32_t r;
    asm("cvt.rn.bf16x2.f32 %0, %1, %2;" : "=r"(r) : "f"(x), "f"(0.0f));
    return __uint_as_float(r);
}
__device__ __forceinline__ uint32_t pack_bf(float lo, float hi) {
    __nv_bfloat162 t = __floats2bfloat162_rn(lo, hi);
    return *reinterpret_cast<uint32_t*>(&t);
}
__device__ __forceinline__ float bf_lo(uint32_t v) { return __uint_as_float(v << 16); }
__device__ __forceinline__ float bf_hi(uint32_t v) { return __uint_as_float(v & 0xffff0000u); }

__device__ __forceinline__ void st_pk8(unsigned long long* p, uint32_t v, uint32_t tag) {
    unsigned long long w = ((unsigned long long)tag << 32) | v;
    asm volatile("st.relaxed.gpu.global.b64 [%0], %1;" ::"l"(p), "l"(w) : "memory");
}
template <int N>
__device__ __forceinline__ void poll8(const unsigned long long* base, const int (&off)[N], uint32_t (&val)[N], uint32_t tag, bool live = true) {
    uint32_t tg[N];
#pragma unroll
    for (int i = 0; i < N; i++) { val[i] = 0; tg[i] = 0; }
    uint32_t it = 0;
    while (true) {
#pragma unroll
        for (int i = 0; i < N; i++) {
            asm volatile("{\n.reg .pred q;\n.reg .b64 t;\nsetp.ne.u32 q, %1, %3;\nsetp.ne.and.u32 q, %4, 0, q;\nmov.b64 t, {%0, %1};\n"
                         "@q ld.relaxed.gpu.global.b64 t, [%2];\nmov.b64 {%0, %1}, t;\n}"
                         : "+r"(val[i]), "+r"(tg[i]) : "l"(base + off[i]), "r"(tag), "r"((uint32_t)live) : "memory");
        }
        bool ok = true;
#pragma unroll
        for (int i = 0; i < N; i++) ok = ok && tg[i] == tag;
        if (__all_sync(0xffffffffu, ok) || !live) break;
        if (++it > SPIN_LIMIT) __trap();
        __nanosleep(100);
    }
}
__device__ __forceinline__ void st_pk16(uint4* p, uint32_t a, uint32_t b, uint32_t c, uint32_t tag) {
    asm volatile(
        "{\n.reg .b128 t;\n.reg .b64 lo, hi;\nmov.b64 lo, {%1, %2};\nmov.b64 hi, {%3, %4};\nmov.b128 t, {lo, hi};\n"
        "st.relaxed.gpu.global.b128 [%0], t;\n}" ::"l"(p), "r"(a), "r"(b), "r"(c), "r"(tag)
        : "memory");
}
template <int OFF = 0>
__device__ __forceinline__ uint4 ld_raw16p(const uint4* p, uint32_t on) {
    uint4 v;
    asm volatile(
        "{\n.reg .b128 t;\n.reg .b64 lo, hi;\n.reg .pred q;\nsetp.ne.u32 q, %5, 0;\n"
        "mov.b64 lo, 0;\nmov.b128 t, {lo, lo};\n"
        "@q ld.relaxed.gpu.global.b128 t, [%4 + %6];\nmov.b128 {lo, hi}, t;\n"
        "mov.b64 {%0, %1}, lo;\nmov.b64 {%2, %3}, hi;\n}"
        : "=r"(v.x), "=r"(v.y), "=r"(v.z), "=r"(v.w)
        : "l"(p), "r"(on), "n"(OFF * 16)
        : "memory");
    return v;
}
template <int OFF>
__device__ __forceinline__ void ld_fresh16(uint4& v, const uint4* p, uint32_t tag, uint32_t on) {
    asm volatile(
        "{\n.reg .b128 t;\n.reg .b64 lo, hi;\n.reg .pred q;\nsetp.ne.u32 q, %3, %5;\nsetp.ne.and.u32 q, %6, 0, q;\n"
        "mov.b64 lo, {%0, %1};\nmov.b64 hi, {%2, %3};\nmov.b128 t, {lo, hi};\n"
        "@q ld.relaxed.gpu.global.b128 t, [%4 + %7];\nmov.b128 {lo, hi}, t;\n"
        "mov.b64 {%0, %1}, lo;\nmov.b64 {%2, %3}, hi;\n}"
        : "+r"(v.x), "+r"(v.y), "+r"(v.z), "+r"(v.w)
        : "l"(p), "r"(tag), "r"(on), "n"(OFF * 16)
        : "memory");
}
template <int N, int STRIDE, int I = 0>
struct FreshN {
    static __device__ __forceinline__ void run(uint4* v, const uint4* p, uint32_t tag, bool live, int base, int step, int lim) {
        ld_fresh16<I * STRIDE>(v[I], p, tag, live && base + step * I < lim);
        FreshN<N, STRIDE, I + 1>::run(v, p, tag, live, base, step, lim);
    }
};
template <int N, int STRIDE>
struct FreshN<N, STRIDE, N> {
    static __device__ __forceinline__ void run(uint4*, const uint4*, uint32_t, bool, int, int, int) {}
};
template <int N, int STRIDE, int I = 0>
struct LoadN {
    static __device__ __forceinline__ void run(uint4* v, const uint4* p, bool live, int base, int step, int lim) {
        v[I] = ld_raw16p<I * STRIDE>(p, live && base + step * I < lim);
        LoadN<N, STRIDE, I + 1>::run(v, p, live, base, step, lim);
    }
};
template <int N, int STRIDE>
struct LoadN<N, STRIDE, N> {
    static __device__ __forceinline__ void run(uint4*, const uint4*, bool, int, int, int) {}
};
__device__ __forceinline__ void st_zero16(void* p) {
    asm volatile("st.relaxed.gpu.global.v4.u32 [%0], {%1, %1, %1, %1};" ::"l"(p), "r"(0u) : "memory");
}
__device__ __forceinline__ float ex2(float x) {
    float y;
    asm("ex2.approx.ftz.f32 %0, %1;" : "=f"(y) : "f"(x));
    return y;
}
__device__ __forceinline__ float fsqrt(float x) {
    float y;
    asm("sqrt.approx.ftz.f32 %0, %1;" : "=f"(y) : "f"(x));
    return y;
}
__device__ __forceinline__ float frcp(float x) {
    float y;
    asm("rcp.approx.ftz.f32 %0, %1;" : "=f"(y) : "f"(x));
    return y;
}
constexpr float LOG2E = 1.4426950408889634f;
__device__ __forceinline__ float silu(float a) { return a * frcp(1.0f + ex2(-a * LOG2E)); }
__device__ __forceinline__ float warp_max(float v) {
    int k = __float_as_int(v);
    k ^= (k >> 31) & 0x7fffffff;
    k = __reduce_max_sync(0xffffffffu, k);
    k ^= (k >> 31) & 0x7fffffff;
    return __int_as_float(k);
}
__device__ __forceinline__ float warp_sum(float v) {
#pragma unroll
    for (int o = 16; o > 0; o >>= 1) v += __shfl_xor_sync(0xffffffffu, v, o);
    return v;
}

__device__ __forceinline__ void ln_stats(const float (&v)[20], float& mean_b, float& den_b) {
    float s = 0.f;
#pragma unroll
    for (int i = 0; i < 20; i++) s += v[i];
    s = warp_sum(s);
    float mean = s * (1.0f / 640.0f);
    float q = 0.f;
#pragma unroll
    for (int i = 0; i < 20; i++) { float d = v[i] - mean; q += d * d; }
    q = warp_sum(q);
    float var_b = bfr(q * (1.0f / 640.0f));
    mean_b = bfr(mean);
    den_b = bfr(fsqrt(bfr(var_b + 1e-5f)));
}

struct Window {
    uint32_t bar[WPRO];
    uint32_t par[WPRO];
    __device__ __forceinline__ void init(uint32_t dummy) {
#pragma unroll
        for (int i = 0; i < WPRO; i++) { bar[i] = dummy; par[i] = 1; }
    }
    __device__ __forceinline__ void push(uint32_t b, uint32_t p, bool wait = true, bool deep = false) {
        if (wait) mbar_wait(deep ? bar[0] : bar[WPRO - WIN], deep ? par[0] : par[WPRO - WIN]);
#pragma unroll
        for (int i = 0; i + 1 < WPRO; i++) { bar[i] = bar[i + 1]; par[i] = par[i + 1]; }
        bar[WPRO - 1] = b; par[WPRO - 1] = p;
    }
};

__global__ void __launch_bounds__(NTHREADS, 1)
fused_decode_kernel(const __grid_constant__ CUtensorMap tmK, const __grid_constant__ CUtensorMap tmV,
                    const __grid_constant__ CUtensorMap tmMod, const __grid_constant__ CUtensorMap tmWq,
                    const __grid_constant__ CUtensorMap tmWo, const __grid_constant__ CUtensorMap tmW1,
                    const __grid_constant__ CUtensorMap tmW3, const __grid_constant__ CUtensorMap tmW2,
                    const __nv_bfloat16* __restrict__ x_in, const __nv_bfloat16* __restrict__ c_in,
                    __nv_bfloat16* __restrict__ out) {
    extern __shared__ __align__(1024) uint8_t smem[];
    const uint32_t sb = smem_u32(smem);
    const int tid = threadIdx.x, wid = tid >> 5, lane = tid & 31;
    const int cta = blockIdx.x, G = gridDim.x;
    const int grp = cta % NG, rank = cta / NG;
    const uint32_t bars = sb + SM_BARS;
    auto BAR = [&](int i) { return bars + 8u * i; };
    volatile uint32_t* meta = reinterpret_cast<volatile uint32_t*>(smem + SM_META);

    uint32_t in_c0 = 0, in_x0 = 0, in_c1 = 0, in_x1 = 0, in_epoch = 0;
    {
        const bool mf = cta < 40;
        const int b0 = mf ? B_MOD : B_WQ;
        if (wid == 8) {
            if (lane == 0) {
                const CUtensorMap* tm = mf ? &tmMod : &tmWq;
                prefetch_tm(tm);
#pragma unroll 1
                for (int i = 0; i < 4; i++) mbar_init(BAR(b0 + i), 1);
                asm volatile("fence.mbarrier_init.release.cluster;" ::: "memory");
                asm volatile("fence.proxy.async.shared::cta;" ::: "memory");
                if (cta < 128) {
#pragma unroll 1
                    for (int i = 0; i < 4; i++) {
                        const uint32_t bar = BAR(b0 + i);
                        mbar_expect_tx(bar, mf ? 10240 : 12288);
                        tma2d(sb + (mf ? SM_WMOD + i * 10240 : SM_WQ + i * 12288), tm, cta * (mf ? 32 : 48), i * (mf ? 160 : 128), bar);
                    }
                }
                asm volatile("ld.relaxed.gpu.global.u32 %0, [%1];" : "=r"(in_epoch) : "l"(&g_epoch) : "memory");
            }
        } else {
            const uint32_t* cg = reinterpret_cast<const uint32_t*>(c_in);
            const uint32_t* xg = reinterpret_cast<const uint32_t*>(x_in);
            in_c0 = __ldg(cg + tid); in_x0 = __ldg(xg + tid);
            if (tid < 64) { in_c1 = __ldg(cg + 256 + tid); in_x1 = __ldg(xg + 256 + tid); }
            if (tid == 0) asm volatile("ld.relaxed.gpu.global.u32 %0, [%1];" : "=r"(in_epoch) : "l"(&g_epoch) : "memory");
            if (lane == 0) {
#pragma unroll 1
                for (int i = wid; i < B_LAST; i += 8) {
                    if (i >= b0 && i < b0 + 4) continue;
                    mbar_init(BAR(i), (i >= B_EMPTY && i < B_MOD) ? 2 : (((i >= B_FLF && i < B_FLE) || i == B_QALL) ? 4 : 1));
                }
                asm volatile("fence.mbarrier_init.release.cluster;" ::: "memory");
                asm volatile("fence.proxy.async.shared::cta;" ::: "memory");
            }
        }
    }
    __syncwarp();
    __syncthreads();
    if (sb & 1023u) __trap();

    if (wid == 8) {
        if (tid == 256) {
            Window win;
            const unsigned epoch = in_epoch;
            prefetch_tm(&tmWq); prefetch_tm(&tmMod); prefetch_tm(&tmK); prefetch_tm(&tmV);
            const int nmod = cta < 120 ? 4 : 0, nwq = cta < 128 ? 5 : 0;
            win.init(BAR(B_DUMMY));
            prefetch_tm(&tmWo); prefetch_tm(&tmW1); prefetch_tm(&tmW3); prefetch_tm(&tmW2);
            unsigned* ctr = &g_ctr[epoch & 1][grp * 32];
            unsigned* gctr = &g_ctr[epoch & 1][NG * 32];
            if (cta == 0) {
                for (int g = 0; g <= NG; g++) g_ctr[(epoch + 1) & 1][g * 32] = 0;
            }
            unsigned pend = atomicAdd(ctr, 1);
#pragma unroll 1
            for (int i = 0; i < nmod + nwq; i++) {
                const bool is_mod = cta < 40 ? i < nmod : i >= nwq;
                const int j = cta < 40 ? (is_mod ? i : i - nmod) : (is_mod ? i - nwq : i);
                const uint32_t bar = BAR((is_mod ? B_MOD : B_WQ) + j);
                win.push(bar, 0, i >= 4, true);
                if (i >= 4) {
                    mbar_expect_tx(bar, is_mod ? 10240 : 12288);
                    if (is_mod) tma2d(sb + SM_WMOD + j * 10240, &tmMod, cta * 32, j * 160, bar);
                    else tma2d(sb + SM_WQ + j * 12288, &tmWq, cta * 48, j * 128, bar);
                }
            }
            uint64_t pol;
            asm volatile("createpolicy.fractional.L2::evict_first.b64 %0, 1.0;" : "=l"(pol));
            int s = 0; uint32_t par = 0;
            int run = -1, last_head = -1;
            bool glob = false;
#pragma unroll 1
            while (true) {
                unsigned t = pend;
                if (!glob && t >= (unsigned)GT) { glob = true; t = atomicAdd(gctr, 1); }
                if (glob && t >= (unsigned)PT) break;
                pend = atomicAdd(glob ? gctr : ctr, 1);
                const int hl = t / TPH, tile = t % TPH;
                const int head = glob ? NG * GH + hl : grp * GH + hl;
                const int qidx = glob ? GH + hl : hl;
                if (head != last_head) { last_head = head; run++; meta[16 + run] = head; }
                const int line0 = (head * SK + tile * TILE) * 3;
#pragma unroll 1
                for (int kv = 0; kv < 2; kv++) {
                    mbar_wait(BAR(B_EMPTY + s), par ^ 1);
                    meta[s] = run | (qidx << 8);
                    mbar_expect_tx(BAR(B_FULL + s), CHUNK);
                    win.push(BAR(B_FULL + s), par);
                    tma2d_hint(sb + SM_RING + s * CHUNK, kv ? &tmV : &tmK, 0, line0, BAR(B_FULL + s), pol);
                    if (++s == NSLOT) { s = 0; par ^= 1; }
                }
            }
            meta[16 + run + 1] = 0xFFu;
#pragma unroll 1
            for (int e = 0; e < 2; e++) {
                mbar_wait(BAR(B_EMPTY + s), par ^ 1);
                meta[s] = (run + 1) | META_END;
                mbar_arrive(BAR(B_FULL + s));
                if (++s == NSLOT) { s = 0; par ^= 1; }
                if (++s == NSLOT) { s = 0; par ^= 1; }
            }
            if (cta < 128) {
                mbar_wait(BAR(B_PRO), 0);
#pragma unroll 1
                for (int i = 0; i < 5; i++) {
                    win.push(BAR(B_WO + i), 0);
                    mbar_expect_tx(BAR(B_WO + i), 12288);
                    tma2d(sb + SM_WO + (2 * i) * 6144, &tmWo, (2 * i) * 64, cta * 48, BAR(B_WO + i));
                    tma2d(sb + SM_WO + (2 * i + 1) * 6144, &tmWo, (2 * i + 1) * 64, cta * 48, BAR(B_WO + i));
                }
                if (cta < 96) {
#pragma unroll 1
                    for (int i = 0; i < 4; i++) {
                        const int m = i & 1, hf = i >> 1;
                        const uint32_t bar = BAR((m ? B_W3 : B_W1) + hf);
                        const uint32_t dst = sb + (m ? SM_W3 : SM_W1) + hf * 10240;
                        const CUtensorMap* tm = m ? &tmW3 : &tmW1;
                        win.push(bar, 0);
                        mbar_expect_tx(bar, 10240);
                        tma2d(dst, tm, cta * 16, hf * 320, bar);
                        tma2d(dst + 5120, tm, cta * 16, hf * 320 + 160, bar);
                    }
#pragma unroll 1
                    for (int i = 0; i < 2; i++) {
                        win.push(BAR(B_W2 + i), 0);
                        mbar_wait(BAR(B_EMPTY + s), par ^ 1);
                        meta[10 + i] = s;
                        mbar_expect_tx(BAR(B_W2 + i), 10240);
#pragma unroll 1
                        for (int b = 0; b < 5; b++)
                            tma2d(sb + SM_RING + s * CHUNK + b * 2048, &tmW2, (5 * i + b) * 64, cta * 16, BAR(B_W2 + i));
                        if (++s == NSLOT) { s = 0; par ^= 1; }
                    }
                }
            }
        }
    } else {
    const int g4 = lane >> 2, j4 = lane & 3, mi = lane >> 3, l8 = lane & 7;
    uint32_t* sc32 = reinterpret_cast<uint32_t*>(smem + SM_SC);
    uint32_t* h32 = reinterpret_cast<uint32_t*>(smem + SM_H);
    uint32_t* x32 = reinterpret_cast<uint32_t*>(smem + SM_X);
    uint32_t* q32 = reinterpret_cast<uint32_t*>(smem + SM_Q);
    float* red = reinterpret_cast<float*>(smem + SM_RED);
    float* stage = reinterpret_cast<float*>(smem + SM_STAGE);
    float* own = reinterpret_cast<float*>(smem + SM_OWN);

    uint32_t tag;
    bool live = true;
    {
        const uint32_t c0 = in_c0, x0 = in_x0, c1 = in_c1, x1 = in_x1, epoch = in_epoch;
        if (cta < 120 && tid >= 128 && tid < 136) st_zero16(reinterpret_cast<uint4*>(&g_mod[cta * 16]) + (tid - 128));
        if (cta < 128 && tid >= 32 && tid < 44) st_zero16(reinterpret_cast<uint4*>(&g_q[cta * 24]) + (tid - 32));
        sc32[tid] = pack_bf(silu(bf_lo(c0)), silu(bf_hi(c0))); x32[tid] = x0;
        if (tid < 64) { sc32[256 + tid] = pack_bf(silu(bf_lo(c1)), silu(bf_hi(c1))); x32[256 + tid] = x1; }
        if (tid == 0) meta[8] = epoch + 1;
    }
    bar_cons();
    tag = meta[8];
    float mean_x = 0.f, rden_x = 1.f;
    if (cta < 128) {
        float xv[20];
#pragma unroll
        for (int i = 0; i < 10; i++) { uint32_t v = x32[lane + 32 * i]; xv[2 * i] = bf_lo(v); xv[2 * i + 1] = bf_hi(v); }
        float den;
        ln_stats(xv, mean_x, den);
        rden_x = frcp(den);
    }

#pragma unroll 1
    for (int step = wid < 4 ? -1 : 0; step < 2; step++) {
    const bool pl = step >= 0;
    if (wid >= 4 && (step == 0 ? cta < 40 : (cta >= 40 && cta < 120))) {
        const int w4 = wid - 4;
        float acc[2][4] = {};
        const uint32_t base = sb + SM_WMOD + w4 * 10240;
        mbar_wait(BAR(B_MOD + w4), 0);
#pragma unroll
        for (int hf = 0; hf < 2; hf++) {
            uint32_t a[5][2][4], bb[5][2];
#pragma unroll
            for (int ks = 0; ks < 5; ks++) {
                const int r0 = w4 * 160 + hf * 80 + ks * 16;
                bb[ks][0] = sc32[(r0 >> 1) + j4]; bb[ks][1] = sc32[(r0 >> 1) + 4 + j4];
                const int r = hf * 80 + ks * 16 + l8 + 8 * (mi >> 1);
#pragma unroll
                for (int mt = 0; mt < 2; mt++) ldsm4t(a[ks][mt], base + r * 64 + (((2 * mt + (mi & 1)) ^ ((r >> 1) & 3)) << 4));
            }
#pragma unroll
            for (int ks = 0; ks < 5; ks++) { mma16816(acc[0], a[ks][0], bb[ks][0], bb[ks][1]); mma16816(acc[1], a[ks][1], bb[ks][0], bb[ks][1]); }
        }
        float* red2 = reinterpret_cast<float*>(smem + SM_FIN);
        if (j4 == 0) {
#pragma unroll
            for (int mt = 0; mt < 2; mt++) { red2[w4 * 32 + mt * 16 + g4] = acc[mt][0]; red2[w4 * 32 + mt * 16 + 8 + g4] = acc[mt][2]; }
        }
        asm volatile("bar.sync 3, 128;" ::: "memory");
        if (wid == 4) {
            float v = (red2[lane] + red2[32 + lane]) + (red2[64 + lane] + red2[96 + lane]);
            float o = __shfl_down_sync(0xffffffffu, v, 1);
            if (!(lane & 1)) st_pk8(&g_mod[cta * 16 + (lane >> 1)], pack_bf(v, o), tag);
            if (step == 1 && lane == 0) mbar_arrive(BAR(B_PRO));
        }
    }
    if (step == 1) break;
    if (cta < 128) {
        {
            const int off[4] = {tid, 320 + tid, tid < 64 ? 256 + tid : tid, tid < 64 ? 576 + tid : 320 + tid};
            uint32_t val[4];
            poll8<4>(g_mod, off, val, tag, pl);
#pragma unroll
            for (int rep = 0; rep < 2; rep++) {
                int p = tid + rep * 256;
                if (p < 320) {
                    uint32_t sa = val[2 * rep], ca = val[2 * rep + 1];
                    uint32_t xx = x32[p];
                    float n0 = bfr(bfr(bf_lo(xx) - mean_x) * rden_x), n1 = bfr(bfr(bf_hi(xx) - mean_x) * rden_x);
                    float h0 = bfr(n0 * bfr(1.0f + bf_lo(ca))) + bf_lo(sa);
                    float h1 = bfr(n1 * bfr(1.0f + bf_hi(ca))) + bf_hi(sa);
                    if (pl) h32[p] = pack_bf(h0, h1);
                }
            }
        }
        if (pl) bar_cons();
        float acc[3][4] = {};
        uint32_t a[5][3][4], bb[5][2];
#pragma unroll
        for (int ks = 0; ks < 5; ks++) {
            const int r0 = wid * 80 + ks * 16;
            bb[ks][0] = h32[(r0 >> 1) + j4]; bb[ks][1] = h32[(r0 >> 1) + 4 + j4];
        }
        if (pl) mbar_wait3(BAR(B_WQ + ((wid * 80) >> 7)), BAR(B_WQ + ((wid * 80 + 79) >> 7)), BAR(B_WQ + ((wid * 80) >> 7)));
#pragma unroll
        for (int ks = 0; ks < 5; ks++) {
            const int r = wid * 80 + ks * 16 + l8 + 8 * (mi >> 1);
#pragma unroll
            for (int mt = 0; mt < 3; mt++) ldsm4t(a[ks][mt], sb + SM_WQ + r * 96 + ((2 * mt + (mi & 1)) << 4));
        }
#pragma unroll
        for (int ks = 0; ks < 5; ks++) {
#pragma unroll
            for (int mt = 0; mt < 3; mt++) mma16816(acc[mt], a[ks][mt], bb[ks][0], bb[ks][1]);
        }
        if (pl && j4 == 0) {
#pragma unroll
            for (int mt = 0; mt < 3; mt++) { red[wid * 64 + mt * 16 + g4] = acc[mt][0]; red[wid * 64 + mt * 16 + 8 + g4] = acc[mt][2]; }
        }
        if (pl) bar_cons();
        if (tid < 64) {
            float v = 0.f;
            if (tid < 48) {
#pragma unroll
                for (int w = 0; w < 8; w++) v += red[w * 64 + tid];
            }
            float o = __shfl_down_sync(0xffffffffu, v, 1);
            if (pl && tid < 48 && !(tid & 1)) st_pk8(&g_q[cta * 24 + (tid >> 1)], pack_bf(v, o), tag);
        }
    }
    if (pl && tid == 0 && !(cta >= 40 && cta < 120)) mbar_arrive(BAR(B_PRO));
    if (wid < 4) {
        const int off[3] = {grp * GH * 96 + lane, grp * GH * 96 + 32 + lane, grp * GH * 96 + 64 + lane};
        uint32_t val[3];
        poll8<3>(g_q, off, val, tag, pl);
        if (pl) { q32[lane] = val[0]; q32[32 + lane] = val[1]; q32[64 + lane] = val[2]; }
        __syncwarp();
    } else {
        constexpr int NQR = ((NQH - 1) * 96 + 127) / 128;
        int off[NQR];
#pragma unroll
        for (int j = 0; j < NQR; j++) {
            int p = 96 + (tid - 128) + 128 * j;
            if (p >= NQH * 96) p = 96 + (tid - 128);
            off[j] = p < GH * 96 ? grp * GH * 96 + p : NG * GH * 96 + (p - GH * 96);
        }
        uint32_t val[NQR];
        poll8<NQR>(g_q, off, val, tag);
#pragma unroll
        for (int j = 0; j < NQR; j++)
            if (96 + (tid - 128) + 128 * j < NQH * 96) q32[96 + (tid - 128) + 128 * j] = val[j];
        __syncwarp();
        if (lane == 0) mbar_arrive(BAR(B_QALL));
    }
    }

    if (wid < 4) {
        const int pair = wid >> 1, half = wid & 1;
        uint32_t offK[3], offV[3];
        {
            const int rowK = half * 16 + l8 + 8 * (mi & 1), hiK = mi >> 1;
            const int rowV = half * 16 + l8 + 8 * (mi >> 1), hiV = mi & 1;
#pragma unroll
            for (int t = 0; t < 3; t++) {
                offK[t] = (rowK * 3 + t) * 128 + ((hiK ^ ((rowK * 3 + t) & 7)) << 4);
                offV[t] = (rowV * 3 + t) * 128 + ((hiV ^ ((rowV * 3 + t) & 7)) << 4);
                asm volatile("" : "+r"(offK[t]), "+r"(offV[t]));
            }
        }
        float acc[12][4];
#pragma unroll
        for (int i = 0; i < 12; i++) { acc[i][0] = acc[i][1] = acc[i][2] = acc[i][3] = 0.f; }
        float m_run = NEG_BIG, l_run = 0.f;
        uint32_t qf[12][2];
#pragma unroll
        for (int i = 0; i < 12; i++) { qf[i][0] = qf[i][1] = 0; }
        int cur = -1, flushed = 0, cnt = 0;
        bool qall = false;
        int s = 2 * pair; uint32_t par = 0;
        int fb = 0; uint32_t fpar = 1;
        uint32_t ready = 0;
#pragma unroll 1
        while (true) {
            if (!ready) mbar_wait(BAR(B_FULL + s), par);
            const uint32_t mt_ = meta[s];
            const int run = mt_ & 0xff;
            if (run != cur) {
#pragma unroll 1
                while (flushed < run) {
                    const uint32_t fle = mbar_try(BAR(B_FLE + fb), fpar);
                    float* mb = reinterpret_cast<float*>(smem + SM_MERGE) + (fb * 4 + wid) * 200;
                    if (flushed != cur) {
#pragma unroll
                        for (int i = 0; i < 12; i++) { acc[i][0] = acc[i][2] = 0.f; }
                        m_run = NEG_BIG; l_run = 0.f; cnt = 0;
                    }
                    float l = l_run;
                    l += __shfl_xor_sync(0xffffffffu, l, 4);
                    l += __shfl_xor_sync(0xffffffffu, l, 8);
                    l += __shfl_xor_sync(0xffffffffu, l, 16);
                    if (!fle) mbar_wait(BAR(B_FLE + fb), fpar);
                    if (j4 == 0) {
#pragma unroll
                        for (int i = 0; i < 12; i++) { mb[4 + 16 * i + g4] = acc[i][0]; mb[4 + 16 * i + 8 + g4] = acc[i][2]; }
                    }
                    if (lane == 0) { mb[0] = m_run; mb[1] = l; mb[2] = __int_as_float(cnt); }
                    __syncwarp();
                    if (lane == 0) mbar_arrive(BAR(B_FLF + fb));
                    if (++fb == NBUF) { fb = 0; fpar ^= 1; }
                    flushed++;
                    cur = -1;
                }
                if (mt_ & META_END) {
                    if (flushed == 0 && lane == 0) mbar_arrive(BAR(B_FLF));
                    break;
                }
                cur = run;
                const int qi = (mt_ >> 8) & 0xff;
                if (qi != 0 && !qall) { mbar_wait(BAR(B_QALL), 0); qall = true; }
#pragma unroll
                for (int i = 0; i < 12; i++) { acc[i][0] = acc[i][1] = acc[i][2] = acc[i][3] = 0.f; }
                m_run = NEG_BIG; l_run = 0.f; cnt = 0;
#pragma unroll
                for (int ks = 0; ks < 12; ks++) {
                    qf[ks][0] = q32[qi * 96 + ks * 8 + j4];
                    qf[ks][1] = q32[qi * 96 + ks * 8 + 4 + j4];
                }
            }
            cnt++;
            const uint32_t kb = sb + SM_RING + s * CHUNK;
            int sv = s + 1; uint32_t parv = par;
            if (sv == NSLOT) { sv = 0; parv ^= 1; }
            float sc[6][4] = {};
            uint32_t vready;
            {
                uint32_t a[12][4];
#pragma unroll
                for (int t = 0; t < 3; t++) {
                    const uint32_t bt = kb + offK[t];
#pragma unroll
                    for (int kk = 0; kk < 4; kk++) ldsm4(a[t * 4 + kk], bt ^ (kk << 5));
                }
                vready = mbar_try(BAR(B_FULL + sv), parv);
#pragma unroll
                for (int i = 0; i < 12; i++) mma16816(sc[i % 6], a[i], qf[i][0], qf[i][1]);
            }
            __syncwarp();
            if (lane == 0) mbar_arrive(BAR(B_EMPTY + s));
            const float scale = 0.07216878364870322f;
            float s0 = bfr(bfr(((sc[0][0] + sc[1][0]) + (sc[2][0] + sc[3][0])) + (sc[4][0] + sc[5][0])) * scale);
            float s1 = bfr(bfr(((sc[0][2] + sc[1][2]) + (sc[2][2] + sc[3][2])) + (sc[4][2] + sc[5][2])) * scale);
            const float tm = warp_max(fmaxf(s0, s1));
            if (tm > m_run) {
                float alpha = ex2((m_run - tm) * LOG2E);
                l_run *= alpha;
#pragma unroll
                for (int i = 0; i < 12; i++) { acc[i][0] *= alpha; acc[i][1] *= alpha; acc[i][2] *= alpha; acc[i][3] *= alpha; }
                m_run = tm;
            }
            float p0 = ex2((s0 - m_run) * LOG2E);
            float p1 = ex2((s1 - m_run) * LOG2E);
            l_run += p0 + p1;
            const uint32_t pw = pack_bf(p0, p1);
            const uint32_t pa = __shfl_sync(0xffffffffu, pw, 8 * j4), pb = __shfl_sync(0xffffffffu, pw, 8 * j4 + 4);
            const uint32_t b0 = __byte_perm(pa, pb, 0x5410), b1 = __byte_perm(pa, pb, 0x7632);
            if (!vready) mbar_wait(BAR(B_FULL + sv), parv);
            s += 4;
            if (s >= NSLOT) { s -= NSLOT; par ^= 1; }
            ready = mbar_try(BAR(B_FULL + s), par);
            const uint32_t vb = sb + SM_RING + sv * CHUNK;
            {
                uint32_t a[12][4];
#pragma unroll
                for (int t = 0; t < 3; t++) {
                    const uint32_t bt = vb + offV[t];
#pragma unroll
                    for (int kk = 0; kk < 4; kk++) ldsm4t(a[t * 4 + kk], bt ^ (kk << 5));
                }
#pragma unroll
                for (int i = 0; i < 12; i++) mma16816(acc[i], a[i], b0, b1);
            }
            __syncwarp();
            if (lane == 0) mbar_arrive(BAR(B_EMPTY + sv));
        }
    } else if (wid == 4) {
        int fb = 0; uint32_t fpar = 0;
        mbar_wait(BAR(B_CLR), 0);
#pragma unroll 1
        for (int f = 0;; f++) {
            const float* mb = reinterpret_cast<const float*>(smem + SM_MERGE) + fb * 800;
            mbar_wait(BAR(B_FLF + fb), fpar);
            const int head = (int)meta[16 + f];
            if (head == 0xFF) break;
            float m0 = mb[0], m1 = mb[200], m2 = mb[400], m3 = mb[600];
            float M = fmaxf(fmaxf(m0, m1), fmaxf(m2, m3));
            float w0 = ex2((m0 - M) * LOG2E), w1 = ex2((m1 - M) * LOG2E);
            float w2 = ex2((m2 - M) * LOG2E), w3 = ex2((m3 - M) * LOG2E);
            const int idx = head < NG * GH ? rank : cta;
            uint4* dst = &g_dat[head][idx][0];
            float o[6];
#pragma unroll
            for (int i = 0; i < 6; i++) {
                int d = 4 + (i < 3 ? 3 * lane + i : 96 + 3 * lane + (i - 3));
                o[i] = w0 * mb[d] + w1 * mb[200 + d] + w2 * mb[400 + d] + w3 * mb[600 + d];
            }
            float L = w0 * mb[1] + w1 * mb[201] + w2 * mb[401] + w3 * mb[601];
            const uint32_t tiles = __float_as_int(mb[2]) + __float_as_int(mb[402]);
            st_pk16(dst + lane, __float_as_uint(o[0]), __float_as_uint(o[1]), __float_as_uint(o[2]), tag);
            st_pk16(dst + 32 + lane, __float_as_uint(o[3]), __float_as_uint(o[4]), __float_as_uint(o[5]), tag);
            if (lane == 0) st_pk16(&g_hdr[head][idx], __float_as_uint(M), __float_as_uint(L), tiles, tag);
            __syncwarp();
            if (lane == 0) mbar_arrive(BAR(B_FLE + fb));
            if (++fb == NBUF) { fb = 0; fpar ^= 1; }
            if (meta[16 + f + 1] == 0xFFu) break;
        }
    } else if (wid == 5) {
        if (cta < 128) {
            if (lane < 2) st_zero16(&g_es[cta][lane]);
#pragma unroll 1
            for (int i = lane; i < 256; i += 32) {
                st_zero16(cta >= 128 - NLATE ? &g_late[cta - (128 - NLATE)][i >> 1][i & 1] : &g_h1[i >> 1][cta][i & 1]);
                if (cta < 96) st_zero16(&g_h3[i >> 1][cta][i & 1]);
            }
        }
#pragma unroll 1
        for (int f = 0; f < NQH; f++) {
            const int head = f < GH ? grp * GH + f : NG * GH + (f - GH);
            const int idx = f < GH ? rank : cta;
            st_zero16(&g_dat[head][idx][lane]);
            st_zero16(&g_dat[head][idx][32 + lane]);
            if (lane == 0) st_zero16(&g_hdr[head][idx]);
        }
        __syncwarp();
        if (lane == 0) mbar_arrive(BAR(B_CLR));
    } else {
        if (cta < 128) {
            const int t = tid - 192;
            uint32_t* cb32 = reinterpret_cast<uint32_t*>(smem + SM_CB);
            uint32_t* sb32 = reinterpret_cast<uint32_t*>(smem + SM_SB);
            uint32_t* ga32 = reinterpret_cast<uint32_t*>(smem + SM_GA);
            const int col = cta * 5 + t;
            int off[16];
            uint32_t val[16];
#pragma unroll
            for (int rep = 0; rep < 5; rep++) { off[3 * rep] = 960 + t + 64 * rep; off[3 * rep + 1] = 1280 + t + 64 * rep; off[3 * rep + 2] = 640 + t + 64 * rep; }
            off[15] = t < 5 ? (3200 + col) >> 1 : 960;
            poll8<16>(g_mod, off, val, tag);
#pragma unroll
            for (int rep = 0; rep < 5; rep++) {
                sb32[t + 64 * rep] = val[3 * rep];
                cb32[t + 64 * rep] = pack_bf(1.0f + bf_lo(val[3 * rep + 1]), 1.0f + bf_hi(val[3 * rep + 1]));
                ga32[t + 64 * rep] = val[3 * rep + 2];
            }
            if (t < 5) own[8 + t] = (col & 1) ? bf_hi(val[15]) : bf_lo(val[15]);
        }
        live = false;
    }
    const uint32_t sb0 = sb;
    const int tid0 = tid;
#pragma unroll 1
    while (cta < 128) {
        uint32_t sb = sb0; int tid = tid0;
        asm volatile("" : "+r"(sb), "+r"(tid));
        const int wid = tid >> 5, lane = tid & 31;
        const int g4 = lane >> 2, j4 = lane & 3, mi = lane >> 3, l8 = lane & 7;
        if (wid >= 5) {
            const int h = cta >> 2, js = cta & 3;
            const bool gl = h >= NG * GH;
            const int ncand = gl ? G : (G - h / GH + NG - 1) / NG;
            const int k = lane & 15, rr = (wid - 5) * 2 + (lane >> 4);
            if (live) {
                const unsigned* cp = &g_ctr[(tag - 1) & 1][(gl ? NG : h / GH) * 32];
                const unsigned thr = ((gl ? h - NG * GH : h % GH) + 1) * TPH;
                uint32_t it = 0;
                while (true) {
                    unsigned v;
                    asm volatile("ld.relaxed.gpu.global.u32 %0, [%1];" : "=r"(v) : "l"(cp) : "memory");
                    if (v >= thr) break;
                    __nanosleep(300);
                    if (++it > SPIN_LIMIT) __trap();
                }
            }
            const uint4* hdr = &g_hdr[h][lane];
            const uint4* dat = &g_dat[h][rr][16 * js + k];
            float* part = stage;
            float L, a0, a1, a2;
            uint32_t it = 0;
            uint4 hd[5], dv[MAXG / 6];
#pragma unroll
            for (int i = 0; i < 5; i++) hd[i] = make_uint4(0, 0, 0, 0);
#pragma unroll
            for (int i = 0; i < MAXG / 6; i++) dv[i] = make_uint4(0, 0, 0, 0);
#pragma unroll 1
            while (true) {
                FreshN<5, 32>::run(hd, hdr, tag, live, lane, 32, ncand);
                FreshN<MAXG / 6, 6 * 64>::run(dv, dat, tag, live, rr, 6, ncand);
                float w[5], M = NEG_BIG;
                int c = 0;
#pragma unroll
                for (int i = 0; i < 5; i++) {
                    const bool v = hd[i].w == tag;
                    w[i] = v ? __uint_as_float(hd[i].x) : NEG_BIG;
                    M = fmaxf(M, w[i]);
                    c += v ? (int)hd[i].z : 0;
                }
                c = __reduce_add_sync(0xffffffffu, c);
                if (++it > SPIN_LIMIT) __trap();
                if (live && c != TPH) continue;
                M = warp_max(M);
                float ls = 0.f;
#pragma unroll
                for (int i = 0; i < 5; i++) {
                    const bool v = w[i] != NEG_BIG;
                    const float e = ex2((w[i] - M) * LOG2E);
                    w[i] = v ? e : -0.0f;
                    ls = fmaf(w[i], __uint_as_float(hd[i].y), ls);
                }
                float* wsm = reinterpret_cast<float*>(smem + SM_X2) + (wid - 5) * 160;
                if (live) {
#pragma unroll
                    for (int i = 0; i < 5; i++) wsm[lane + 32 * i] = w[i];
                }
                __syncwarp();
                L = warp_sum(ls);
                uint32_t badm = 0;
                a0 = a1 = a2 = 0.f;
#pragma unroll
                for (int i = 0; i < MAXG / 6; i++) {
                    const float wi = wsm[rr + 6 * i];
                    badm |= (dv[i].w ^ tag) & ~(uint32_t)(__float_as_int(wi) >> 31);
                    a0 = fmaf(wi, __uint_as_float(dv[i].x), a0);
                    a1 = fmaf(wi, __uint_as_float(dv[i].y), a1);
                    a2 = fmaf(wi, __uint_as_float(dv[i].z), a2);
                }
                const bool bad = badm != 0;
                if (!__any_sync(0xffffffffu, bad) || !live) break;
            }
            a0 += __shfl_xor_sync(0xffffffffu, a0, 16);
            a1 += __shfl_xor_sync(0xffffffffu, a1, 16);
            a2 += __shfl_xor_sync(0xffffffffu, a2, 16);
            if (live && lane < 16) { float* pp = part + (wid - 5) * 48 + 3 * k; pp[0] = a0; pp[1] = a1; pp[2] = a2; }
            if (live) asm volatile("bar.sync 2, 96;" ::: "memory");
            if (wid == 5 || !live) {
                uint16_t* osw = reinterpret_cast<uint16_t*>(smem + SM_SC);
                const float inv = frcp(L);
                const float o0 = (part[lane] + part[48 + lane]) + part[96 + lane];
                const float o1 = (part[32 + (lane & 15)] + part[80 + (lane & 15)]) + part[128 + (lane & 15)];
                if (live) { osw[lane] = (uint16_t)(__float_as_uint(bfr(o0 * inv)) >> 16); if (lane < 16) osw[32 + lane] = (uint16_t)(__float_as_uint(bfr(o1 * inv)) >> 16); }
            }
        }
        if (wid < 5 || !live) {
            const int w5 = wid < 5 ? wid : wid - 5;
            uint32_t wa[8][3][4];
            if (live) mbar_wait(BAR(B_WO + w5), 0);
#pragma unroll
            for (int i = 0; i < 8; i++) {
                const int cc = 2 * (i & 3) + (mi & 1);
#pragma unroll
                for (int ks = 0; ks < 3; ks++) {
                    const int r = ks * 16 + l8 + 8 * (mi >> 1);
                    ldsm4t(wa[i][ks], sb + SM_WO + (2 * w5 + (i >> 2)) * 6144 + r * 128 + ((cc ^ (r & 7)) << 4));
                }
            }
            if (live) bar_cons();
            const uint32_t* os32 = reinterpret_cast<const uint32_t*>(smem + SM_SC);
            float acc[8][4] = {};
#pragma unroll
            for (int ks = 0; ks < 3; ks++) {
                const uint32_t b0 = os32[ks * 8 + j4], b1 = os32[ks * 8 + 4 + j4];
#pragma unroll
                for (int i = 0; i < 8; i++) mma16816(acc[i], wa[i][ks], b0, b1);
            }
            if (live && j4 == 0) {
#pragma unroll
                for (int i = 0; i < 8; i++) { stage[(w5 * 8 + i) * 16 + g4] = acc[i][0]; stage[(w5 * 8 + i) * 16 + 8 + g4] = acc[i][2]; }
            }
        } else {
            bar_cons();
        }
        if (live) bar_cons();
        {
            const int o = tid >> 1, kk = tid & 1;
            const float* sp = stage + o * 5 + kk * 3;
            float v0 = sp[0], v1 = sp[1], v2 = kk ? 0.f : sp[2];
            uint4* dst = cta >= 128 - NLATE ? &g_late[cta - (128 - NLATE)][o][kk] : &g_h1[o][cta][kk];
            if (live) st_pk16(dst, __float_as_uint(v0), __float_as_uint(v1), __float_as_uint(v2), tag);
        }
        if (wid == 0 || !live) {
            const uint4* p = &g_h1[cta][0][0] + lane;
            uint4 v[8];
#pragma unroll
            for (int j = 0; j < 8; j++) v[j] = make_uint4(0, 0, 0, 0);
            if (lane >= 32 - 2 * NLATE) v[7].w = tag;
            uint32_t it = 0;
            while (true) {
                FreshN<8, 32>::run(v, p, tag, live, 0, 0, 1);
                bool ok = true;
#pragma unroll
                for (int j = 0; j < 8; j++) ok = ok && v[j].w == tag;
                if (__all_sync(0xffffffffu, ok) || !live) break;
                if (++it > SPIN_LIMIT) __trap();
            }
            float a0, a1, a2;
            a0 = ((__uint_as_float(v[0].x) + __uint_as_float(v[1].x)) + (__uint_as_float(v[2].x) + __uint_as_float(v[3].x))) +
                 ((__uint_as_float(v[4].x) + __uint_as_float(v[5].x)) + (__uint_as_float(v[6].x) + __uint_as_float(v[7].x)));
            a1 = ((__uint_as_float(v[0].y) + __uint_as_float(v[1].y)) + (__uint_as_float(v[2].y) + __uint_as_float(v[3].y))) +
                 ((__uint_as_float(v[4].y) + __uint_as_float(v[5].y)) + (__uint_as_float(v[6].y) + __uint_as_float(v[7].y)));
            a2 = ((__uint_as_float(v[0].z) + __uint_as_float(v[1].z)) + (__uint_as_float(v[2].z) + __uint_as_float(v[3].z))) +
                 ((__uint_as_float(v[4].z) + __uint_as_float(v[5].z)) + (__uint_as_float(v[6].z) + __uint_as_float(v[7].z)));
#pragma unroll
            for (int o = 2; o <= 16; o <<= 1) {
                a0 += __shfl_xor_sync(0xffffffffu, a0, o);
                a1 += __shfl_xor_sync(0xffffffffu, a1, o);
                a2 += __shfl_xor_sync(0xffffffffu, a2, o);
            }
            if (live && lane < 2) st_pk16(&g_es[cta][lane], __float_as_uint(a0), __float_as_uint(a1), __float_as_uint(a2), tag);
        }
        float* x2s = reinterpret_cast<float*>(smem + SM_X2);
        {
            uint32_t a1[5][4], a3[5][4];
            if (live && cta < 96) mbar_wait3(BAR(B_W1 + (wid >> 2)), BAR(B_W3 + (wid >> 2)), BAR(B_W1 + (wid >> 2)));
#pragma unroll
            for (int ks = 0; ks < 5; ks++) {
                const int r = wid * 80 + ks * 16 + l8 + 8 * (mi >> 1);
                const uint32_t off = r * 32 + (((mi & 1) ^ ((r >> 2) & 1)) << 4);
                ldsm4t(a1[ks], sb + SM_W1 + off);
                ldsm4t(a3[ks], sb + SM_W3 + off);
            }
            const int o = tid >> 1, k = tid & 1, c0 = 5 * o + 3 * k;
            const uint16_t* x16 = reinterpret_cast<const uint16_t*>(smem + SM_X);
            const uint16_t* ga16 = reinterpret_cast<const uint16_t*>(smem + SM_GA);
            const uint16_t* cb16 = reinterpret_cast<const uint16_t*>(smem + SM_CB);
            const uint16_t* sb16 = reinterpret_cast<const uint16_t*>(smem + SM_SB);
            float xin[3], gin[3], cin[3], sin_[3];
#pragma unroll
            for (int e = 0; e < 3; e++) {
                const int c = c0 + ((e == 2 && k) ? 1 : e);
                xin[e] = __uint_as_float((uint32_t)x16[c] << 16); gin[e] = __uint_as_float((uint32_t)ga16[c] << 16);
                cin[e] = __uint_as_float((uint32_t)cb16[c] << 16); sin_[e] = __uint_as_float((uint32_t)sb16[c] << 16);
            }
            uint32_t w2o[5];
#pragma unroll
            for (int i = 0; i < 5; i++) {
                const int mt = (wid & 3) * 5 + i;
                const int cc = 2 * (mt & 3) + (mi & 1);
                const int r = l8 + 8 * (mi >> 1);
                w2o[i] = sb + SM_RING + (mt >> 2) * 2048 + r * 128 + ((cc ^ (r & 7)) << 4);
                asm volatile("" : "+r"(w2o[i]));
            }
            const uint32_t* hw = h32 + wid * 40 + j4;
            uint4 v[1 + NLATE];
#pragma unroll
            for (int j = 0; j <= NLATE; j++) v[j] = make_uint4(0, 0, 0, 0);
            const uint4* pe = &g_es[o][k];
            const uint4* pl = &g_late[0][o][k];
            uint32_t it = 0;
            while (true) {
                FreshN<1, 1>::run(v, pe, tag, live, 0, 0, 1);
                FreshN<NLATE, 256>::run(v + 1, pl, tag, live, 0, 0, 1);
                bool ok = true;
#pragma unroll
                for (int j = 0; j <= NLATE; j++) ok = ok && v[j].w == tag;
                if (__all_sync(0xffffffffu, ok) || !live) break;
                if (++it > SPIN_LIMIT) __trap();
            }
            float x2[3];
            x2[0] = (__uint_as_float(v[0].x) + (__uint_as_float(v[1].x) + __uint_as_float(v[2].x))) + (__uint_as_float(v[3].x) + __uint_as_float(v[4].x));
            x2[1] = (__uint_as_float(v[0].y) + (__uint_as_float(v[1].y) + __uint_as_float(v[2].y))) + (__uint_as_float(v[3].y) + __uint_as_float(v[4].y));
            x2[2] = (__uint_as_float(v[0].z) + (__uint_as_float(v[1].z) + __uint_as_float(v[2].z))) + (__uint_as_float(v[3].z) + __uint_as_float(v[4].z));
#pragma unroll
            for (int e = 0; e < 3; e++) x2[e] = bfr(xin[e] + bfr(gin[e] * bfr(x2[e])));
            if (live && o == cta) { x2s[3 * k] = x2[0]; x2s[3 * k + 1] = x2[1]; if (!k) x2s[2] = x2[2]; }
            float* st8 = red + 256;
            {
                const float pv = __shfl_sync(0xffffffffu, x2[0], 0);
                const float d0 = x2[0] - pv, d1 = x2[1] - pv, d2 = k ? 0.f : x2[2] - pv;
                float s1 = (d0 + d1) + d2;
                float s2 = fmaf(d0, d0, fmaf(d1, d1, d2 * d2));
#pragma unroll
                for (int q = 16; q > 0; q >>= 1) { s1 += __shfl_xor_sync(0xffffffffu, s1, q); s2 += __shfl_xor_sync(0xffffffffu, s2, q); }
                if (live && lane == 0) { st8[wid] = pv + s1 * (1.0f / 80.0f); st8[8 + wid] = s2 - s1 * s1 * (1.0f / 80.0f); }
            }
            if (live) bar_cons();
            if (cta < 96) {
            const float4 mA = *reinterpret_cast<const float4*>(st8), mB = *reinterpret_cast<const float4*>(st8 + 4);
            const float4 qA = *reinterpret_cast<const float4*>(st8 + 8), qB = *reinterpret_cast<const float4*>(st8 + 12);
            const float mean = (((mA.x + mA.y) + (mA.z + mA.w)) + ((mB.x + mB.y) + (mB.z + mB.w))) * 0.125f;
            const float u0 = mA.x - mean, u1 = mA.y - mean, u2 = mA.z - mean, u3 = mA.w - mean;
            const float u4 = mB.x - mean, u5 = mB.y - mean, u6 = mB.z - mean, u7 = mB.w - mean;
            const float m2 = (((qA.x + qA.y) + (qA.z + qA.w)) + ((qB.x + qB.y) + (qB.z + qB.w))) +
                             80.0f * (((u0 * u0 + u1 * u1) + (u2 * u2 + u3 * u3)) + ((u4 * u4 + u5 * u5) + (u6 * u6 + u7 * u7)));
            const float mean_b = bfr(mean);
            const float rden = frcp(bfr(fsqrt(bfr(bfr(m2 * (1.0f / 640.0f)) + 1e-5f))));
            {
                uint16_t* h16 = reinterpret_cast<uint16_t*>(smem + SM_H);
#pragma unroll
                for (int e = 0; e < 3; e++) {
                    const float n = bfr(bfr(x2[e] - mean_b) * rden);
                    const float hv = bfr(bfr(n * cin[e]) + sin_[e]);
                    if (live && !(e == 2 && k)) h16[c0 + e] = (uint16_t)(__float_as_uint(hv) >> 16);
                }
            }
            __syncwarp();
            const uint32_t w2ready = mbar_try(BAR(B_W2 + (wid >> 2)), 0);
            float ag[2][4] = {}, au[2][4] = {};
#pragma unroll
            for (int ks = 0; ks < 5; ks++) {
                const uint32_t b0 = hw[8 * ks], b1 = hw[8 * ks + 4];
                mma16816(ag[ks & 1], a1[ks], b0, b1);
                mma16816(au[ks & 1], a3[ks], b0, b1);
            }
            if (live && j4 == 0) {
                red[wid * 32 + g4] = ag[0][0] + ag[1][0]; red[wid * 32 + 8 + g4] = ag[0][2] + ag[1][2];
                red[wid * 32 + 16 + g4] = au[0][0] + au[1][0]; red[wid * 32 + 24 + g4] = au[0][2] + au[1][2];
            }
            uint32_t a2[5][4];
            if (live && !w2ready) mbar_wait(BAR(B_W2 + (wid >> 2)), 0);
            const uint32_t w2b = (meta[10 + (wid >> 2)] & (NSLOT - 1)) * CHUNK;
#pragma unroll
            for (int i = 0; i < 5; i++) ldsm4t(a2[i], w2o[i] + w2b);
            if (live) bar_cons();
            float v = ((red[lane] + red[32 + lane]) + (red[64 + lane] + red[96 + lane])) + ((red[128 + lane] + red[160 + lane]) + (red[192 + lane] + red[224 + lane]));
            v = bfr(v);
            float up = __shfl_down_sync(0xffffffffu, v, 16);
            float hact = bfr(bfr(silu(v)) * up);
            float e0 = __shfl_sync(0xffffffffu, hact, 2 * j4), e1 = __shfl_sync(0xffffffffu, hact, 2 * j4 + 1);
            float e2 = __shfl_sync(0xffffffffu, hact, 2 * j4 + 8), e3 = __shfl_sync(0xffffffffu, hact, 2 * j4 + 9);
            const uint32_t b0 = pack_bf(e0, e1), b1 = pack_bf(e2, e3);
            float acc[5][4] = {};
#pragma unroll
            for (int i = 0; i < 5; i++) mma16816(acc[i], a2[i], b0, b1);
            if (live && j4 == 0) {
#pragma unroll
                for (int i = 0; i < 5; i++) { stage[(wid * 5 + i) * 16 + g4] = acc[i][0]; stage[(wid * 5 + i) * 16 + 8 + g4] = acc[i][2]; }
            }
            if (live) bar_cons();
            const float* sp = stage + o * 5 + k * 3;
            float v0 = sp[0], v1 = sp[1], v2 = k ? 0.f : sp[2];
            if (live) st_pk16(&g_h3[o][cta][k], __float_as_uint(v0), __float_as_uint(v1), __float_as_uint(v2), tag);
            }
        }
        if (wid == 0 || !live) {
            const uint4* p = &g_h3[cta][0][0] + lane;
            const float gx = own[8 + (lane & 7)], xx = x2s[lane & 7];
            uint4 v[6];
            uint32_t it = 0;
            if (live && cta < 96) spin(POLL_DELAY);
            while (true) {
                bool ok = true;
                LoadN<6, 32>::run(v, p, live, 0, 0, 1);
#pragma unroll
                for (int j = 0; j < 6; j++) ok = ok && v[j].w == tag;
                if (__all_sync(0xffffffffu, ok) || !live) break;
                if (++it > SPIN_LIMIT) __trap();
            }
            float a0 = ((__uint_as_float(v[0].x) + __uint_as_float(v[1].x)) + (__uint_as_float(v[2].x) + __uint_as_float(v[3].x))) + (__uint_as_float(v[4].x) + __uint_as_float(v[5].x));
            float a1 = ((__uint_as_float(v[0].y) + __uint_as_float(v[1].y)) + (__uint_as_float(v[2].y) + __uint_as_float(v[3].y))) + (__uint_as_float(v[4].y) + __uint_as_float(v[5].y));
            float a2 = ((__uint_as_float(v[0].z) + __uint_as_float(v[1].z)) + (__uint_as_float(v[2].z) + __uint_as_float(v[3].z))) + (__uint_as_float(v[4].z) + __uint_as_float(v[5].z));
#pragma unroll
            for (int o = 2; o <= 16; o <<= 1) {
                a0 += __shfl_xor_sync(0xffffffffu, a0, o);
                a1 += __shfl_xor_sync(0xffffffffu, a1, o);
                a2 += __shfl_xor_sync(0xffffffffu, a2, o);
            }
            const float t0 = __shfl_sync(0xffffffffu, a0, lane >= 3), t1 = __shfl_sync(0xffffffffu, a1, lane >= 3);
            const float sum = (lane == 0 || lane == 3) ? t0 : (lane == 2 ? a2 : t1);
            const float y = xx + bfr(gx * bfr(sum));
            if (live && lane < 5) reinterpret_cast<uint16_t*>(out)[cta * 5 + lane] = (uint16_t)(__float_as_uint(bfr(y)) >> 16);
            if (live && cta == 0 && lane == 0) g_epoch = tag;
        }
        if (live) break;
        live = true;
    }
    }
}

typedef CUresult (*EncodeFn)(CUtensorMap*, CUtensorMapDataType, cuuint32_t, void*, const cuuint64_t*, const cuuint64_t*,
                             const cuuint32_t*, const cuuint32_t*, CUtensorMapInterleave, CUtensorMapSwizzle,
                             CUtensorMapL2promotion, CUtensorMapFloatOOBfill);

void make_map(EncodeFn enc, CUtensorMap* tm, const void* ptr, uint64_t cols, uint64_t rows, uint32_t box_c, uint32_t box_r,
              CUtensorMapSwizzle sw, CUtensorMapL2promotion prom) {
    cuuint64_t dims[2] = {cols, rows};
    cuuint64_t strides[1] = {cols * 2};
    cuuint32_t box[2] = {box_c, box_r};
    cuuint32_t es[2] = {1, 1};
    enc(tm, CU_TENSOR_MAP_DATA_TYPE_BFLOAT16, 2, const_cast<void*>(ptr), dims, strides, box, es,
        CU_TENSOR_MAP_INTERLEAVE_NONE, sw, prom, CU_TENSOR_MAP_FLOAT_OOB_FILL_NONE);
}

}

extern "C" void kernel_launch(void* const* d_in, const int* in_sizes, int n_in, void* d_out, int out_size) {
    (void)in_sizes; (void)n_in; (void)out_size;
    static EncodeFn enc = nullptr;
    static int num_sms = 0;
    if (!enc) {
        void* fn = nullptr;
        cudaDriverEntryPointQueryResult qr;
        cudaGetDriverEntryPoint("cuTensorMapEncodeTiled", &fn, cudaEnableDefault, &qr);
        enc = (EncodeFn)fn;
        cudaDeviceGetAttribute(&num_sms, cudaDevAttrMultiProcessorCount, 0);
        cudaFuncSetAttribute(fused_decode_kernel, cudaFuncAttributeMaxDynamicSharedMemorySize, SM_TOTAL);
    }
    CUtensorMap tmK, tmV, tmMod, tmWq, tmWo, tmW1, tmW3, tmW2;
    const uint64_t kv_lines = (uint64_t)NH * SK * 3;
    make_map(enc, &tmK, d_in[1], 64, kv_lines, 64, 96, CU_TENSOR_MAP_SWIZZLE_128B, CU_TENSOR_MAP_L2_PROMOTION_L2_128B);
    make_map(enc, &tmV, d_in[2], 64, kv_lines, 64, 96, CU_TENSOR_MAP_SWIZZLE_128B, CU_TENSOR_MAP_L2_PROMOTION_L2_128B);
    make_map(enc, &tmWq, d_in[3], NH * DH, D, 48, 128, CU_TENSOR_MAP_SWIZZLE_NONE, CU_TENSOR_MAP_L2_PROMOTION_L2_128B);
    make_map(enc, &tmWo, d_in[4], D, NH * DH, 64, 48, CU_TENSOR_MAP_SWIZZLE_128B, CU_TENSOR_MAP_L2_PROMOTION_L2_128B);
    make_map(enc, &tmW1, d_in[6], FF, D, 16, 160, CU_TENSOR_MAP_SWIZZLE_32B, CU_TENSOR_MAP_L2_PROMOTION_L2_128B);
    make_map(enc, &tmW3, d_in[7], FF, D, 16, 160, CU_TENSOR_MAP_SWIZZLE_32B, CU_TENSOR_MAP_L2_PROMOTION_L2_128B);
    make_map(enc, &tmW2, d_in[8], D, FF, 64, 16, CU_TENSOR_MAP_SWIZZLE_128B, CU_TENSOR_MAP_L2_PROMOTION_L2_128B);
    make_map(enc, &tmMod, d_in[10], 6 * D, D, 32, 160, CU_TENSOR_MAP_SWIZZLE_64B, CU_TENSOR_MAP_L2_PROMOTION_L2_128B);
    int grid = num_sms < MAXG ? num_sms : MAXG;
    fused_decode_kernel<<<grid, NTHREADS, SM_TOTAL, cudaStreamPerThread>>>(
        tmK, tmV, tmMod, tmWq, tmWo, tmW1, tmW3, tmW2, (const __nv_bfloat16*)d_in[0], (const __nv_bfloat16*)d_in[9],
        (__nv_bfloat16*)d_out);
}
```

```cpp
#include <cuda_runtime.h>
#include <cuda_bf16.h>
#include <cuda.h>
#include <stdint.h>

namespace {

constexpr int D = 640, NH = 32, SK = 8192, DH = 192, FF = 1536;
constexpr int NG = 4;
constexpr int GH = 7;
constexpr int NGLOB = NH - NG * GH;
constexpr int NQH = GH + NGLOB;
constexpr int TILE = 32;
constexpr int TPH = SK / TILE;
constexpr int GT = GH * TPH;
constexpr int PT = NGLOB * TPH;
constexpr int CHUNK = TILE * DH * 2;
constexpr int NSLOT = 9;
constexpr int WIN = 3;
constexpr int WPRO = 4;
constexpr int POLL_DELAY = 450;
constexpr int NBUF = 1;
constexpr int NLATE = 4;
constexpr int MAXG = 132;
constexpr int NTHREADS = 288;
constexpr float NEG_BIG = -3.402823466e38f;

constexpr int SM_WMOD = 0;
constexpr int SM_WQ = 40960;
constexpr int SM_WO = 0;
constexpr int SM_W1 = 61440;
constexpr int SM_W3 = 81920;
constexpr int SM_RING = 102400;
constexpr int SM_MISC = SM_RING + NSLOT * CHUNK;
constexpr int SM_BARS = SM_MISC;
constexpr int SM_META = SM_BARS + 512;
constexpr int SM_Q = SM_META + 128;
constexpr int SM_SC = SM_Q + NQH * DH * 2;
constexpr int SM_H = SM_SC + 1280;
constexpr int SM_GA = SM_H;
constexpr int SM_X = SM_H + 1280;
constexpr int SM_CB = SM_X + 1280;
constexpr int SM_SB = SM_CB + 1280;
constexpr int SM_OWN = SM_SB + 1280;
constexpr int SM_RED = SM_OWN + 128;
constexpr int SM_MERGE = SM_RED + 2048;
constexpr int SM_STAGE = SM_MERGE + NBUF * 3200;
constexpr int SM_TOTAL = SM_STAGE + 2560;
static_assert(SM_TOTAL <= 232448, "shared memory budget");

constexpr int B_FULL = 0;
constexpr int B_EMPTY = 10;
constexpr int B_MOD = 20;
constexpr int B_WQ = 24;
constexpr int B_WO = 29;
constexpr int B_W1 = 34;
constexpr int B_W3 = 36;
constexpr int B_W2 = 38;
constexpr int B_PRO = 40, B_DUMMY = 41, B_CLR = 42, B_QALL = 43;
constexpr int B_FLF = 44, B_FLE = 48;
constexpr int B_LAST = 52;
static_assert(NSLOT <= 10 && NSLOT >= 6 && WIN <= WPRO && WIN <= NSLOT - 3 && NBUF <= 4, "barrier map / end markers vs window");
constexpr uint32_t META_END = 0x10000u;

__device__ unsigned g_epoch;
__device__ unsigned g_ctr[2][(NG + 1) * 32];
__device__ __align__(128) unsigned long long g_mod[1920];
__device__ __align__(128) unsigned long long g_q[3072];
__device__ __align__(128) uint4 g_hdr[NH][MAXG];
__device__ __align__(128) uint4 g_dat[NH][MAXG][64];
__device__ __align__(128) uint4 g_h1[128][128][2];
__device__ __align__(128) uint4 g_es[128][2];
__device__ __align__(128) uint4 g_late[NLATE][128][2];
__device__ __align__(128) uint4 g_h3[128][96][2];


__device__ __forceinline__ uint32_t smem_u32(const void* p) { return (uint32_t)__cvta_generic_to_shared(p); }
__device__ __forceinline__ void mbar_init(uint32_t bar, uint32_t cnt) {
    asm volatile("mbarrier.init.shared::cta.b64 [%0], %1;" ::"r"(bar), "r"(cnt) : "memory");
}
__device__ __forceinline__ void mbar_expect_tx(uint32_t bar, uint32_t bytes) {
    asm volatile("mbarrier.arrive.expect_tx.shared::cta.b64 _, [%0], %1;" ::"r"(bar), "r"(bytes) : "memory");
}
__device__ __forceinline__ void mbar_arrive(uint32_t bar) {
    asm volatile("mbarrier.arrive.shared::cta.b64 _, [%0];" ::"r"(bar) : "memory");
}
constexpr uint32_t SPIN_LIMIT = 1u << 22;
__device__ __forceinline__ void mbar_wait(uint32_t bar, uint32_t parity) {
    asm volatile(
        "{\n.reg .pred p;\n.reg .u32 c;\nmov.u32 c, 0;\n"
        "LW:\nmbarrier.try_wait.parity.shared::cta.b64 p, [%0], %1;\n@p bra LD;\n"
        "add.u32 c, c, 1;\nsetp.lt.u32 p, c, 0x400000;\n@p bra LW;\ntrap;\nLD:\n}" ::"r"(bar), "r"(parity)
        : "memory");
}
__device__ __forceinline__ uint32_t mbar_try(uint32_t bar, uint32_t parity) {
    uint32_t ok;
    asm volatile("{\n.reg .pred p;\nmbarrier.try_wait.parity.shared::cta.b64 p, [%1], %2;\nselp.u32 %0, 1, 0, p;\n}"
                 : "=r"(ok) : "r"(bar), "r"(parity) : "memory");
    return ok;
}
__device__ __forceinline__ void mbar_wait3(uint32_t b0, uint32_t b1, uint32_t b2) {
    asm volatile(
        "{\n.reg .pred p, q, r;\n.reg .u32 c;\nmov.u32 c, 0;\n"
        "LW:\nmbarrier.try_wait.parity.shared::cta.b64 p, [%0], 0;\n"
        "mbarrier.try_wait.parity.shared::cta.b64 q, [%1], 0;\n"
        "mbarrier.try_wait.parity.shared::cta.b64 r, [%2], 0;\n"
        "and.pred p, p, q;\nand.pred p, p, r;\n@p bra LD;\n"
        "add.u32 c, c, 1;\nsetp.lt.u32 p, c, 0x400000;\n@p bra LW;\ntrap;\nLD:\n}" ::"r"(b0), "r"(b1), "r"(b2)
        : "memory");
}
__device__ __forceinline__ void tma2d(uint32_t dst, const CUtensorMap* tm, int c0, int c1, uint32_t bar) {
    asm volatile(
        "cp.async.bulk.tensor.2d.shared::cluster.global.mbarrier::complete_tx::bytes [%0], [%1, {%3, %4}], [%2];" ::"r"(dst),
        "l"(tm), "r"(bar), "r"(c0), "r"(c1)
        : "memory");
}
__device__ __forceinline__ void tma2d_hint(uint32_t dst, const CUtensorMap* tm, int c0, int c1, uint32_t bar, uint64_t pol) {
    asm volatile(
        "cp.async.bulk.tensor.2d.shared::cluster.global.mbarrier::complete_tx::bytes.L2::cache_hint [%0], [%1, {%3, %4}], [%2], %5;" ::"r"(dst),
        "l"(tm), "r"(bar), "r"(c0), "r"(c1), "l"(pol)
        : "memory");
}
__device__ __forceinline__ void prefetch_tm(const CUtensorMap* tm) {
    asm volatile("prefetch.tensormap [%0];" ::"l"(tm) : "memory");
}
__device__ __forceinline__ void ldsm4(uint32_t (&r)[4], uint32_t addr) {
    asm volatile("ldmatrix.sync.aligned.m8n8.x4.shared.b16 {%0,%1,%2,%3}, [%4];"
                 : "=r"(r[0]), "=r"(r[1]), "=r"(r[2]), "=r"(r[3])
                 : "r"(addr));
}
__device__ __forceinline__ void ldsm4t(uint32_t (&r)[4], uint32_t addr) {
    asm volatile("ldmatrix.sync.aligned.m8n8.x4.trans.shared.b16 {%0,%1,%2,%3}, [%4];"
                 : "=r"(r[0]), "=r"(r[1]), "=r"(r[2]), "=r"(r[3])
                 : "r"(addr));
}
__device__ __forceinline__ void mma16816(float (&d)[4], const uint32_t (&a)[4], uint32_t b0, uint32_t b1) {
    asm volatile(
        "mma.sync.aligned.m16n8k16.row.col.f32.bf16.bf16.f32 {%0,%1,%2,%3}, {%4,%5,%6,%7}, {%8,%9}, {%0,%1,%2,%3};"
        : "+f"(d[0]), "+f"(d[1]), "+f"(d[2]), "+f"(d[3])
        : "r"(a[0]), "r"(a[1]), "r"(a[2]), "r"(a[3]), "r"(b0), "r"(b1));
}
__device__ __forceinline__ void bar_cons() { asm volatile("bar.sync 1, 256;" ::: "memory"); }
__device__ __forceinline__ void spin(int cycles) {
    long long t0 = clock64();
    while (clock64() - t0 < cycles) {}
}

__device__ __forceinline__ float bfr(float x) {
    uint32_t r;
    asm("cvt.rn.bf16x2.f32 %0, %1, %2;" : "=r"(r) : "f"(x), "f"(0.0f));
    return __uint_as_float(r);
}
__device__ __forceinline__ uint32_t pack_bf(float lo, float hi) {
    __nv_bfloat162 t = __floats2bfloat162_rn(lo, hi);
    return *reinterpret_cast<uint32_t*>(&t);
}
__device__ __forceinline__ float bf_lo(uint32_t v) { return __uint_as_float(v << 16); }
__device__ __forceinline__ float bf_hi(uint32_t v) { return __uint_as_float(v & 0xffff0000u); }

__device__ __forceinline__ void st_pk8(unsigned long long* p, uint32_t v, uint32_t tag) {
    unsigned long long w = ((unsigned long long)tag << 32) | v;
    asm volatile("st.relaxed.gpu.global.b64 [%0], %1;" ::"l"(p), "l"(w) : "memory");
}
template <int N>
__device__ __forceinline__ void poll8(const unsigned long long* base, const int (&off)[N], uint32_t (&val)[N], uint32_t tag, bool live = true) {
    uint32_t tg[N];
#pragma unroll
    for (int i = 0; i < N; i++) { val[i] = 0; tg[i] = 0; }
    uint32_t it = 0;
    while (true) {
#pragma unroll
        for (int i = 0; i < N; i++) {
            asm volatile("{\n.reg .pred q;\n.reg .b64 t;\nsetp.ne.u32 q, %1, %3;\nsetp.ne.and.u32 q, %4, 0, q;\nmov.b64 t, {%0, %1};\n"
                         "@q ld.relaxed.gpu.global.b64 t, [%2];\nmov.b64 {%0, %1}, t;\n}"
                         : "+r"(val[i]), "+r"(tg[i]) : "l"(base + off[i]), "r"(tag), "r"((uint32_t)live) : "memory");
        }
        bool ok = true;
#pragma unroll
        for (int i = 0; i < N; i++) ok = ok && tg[i] == tag;
        if (__all_sync(0xffffffffu, ok) || !live) break;
        if (++it > SPIN_LIMIT) __trap();
        __nanosleep(100);
    }
}
__device__ __forceinline__ void st_pk16(uint4* p, uint32_t a, uint32_t b, uint32_t c, uint32_t tag) {
    asm volatile(
        "{\n.reg .b128 t;\n.reg .b64 lo, hi;\nmov.b64 lo, {%1, %2};\nmov.b64 hi, {%3, %4};\nmov.b128 t, {lo, hi};\n"
        "st.relaxed.gpu.global.b128 [%0], t;\n}" ::"l"(p), "r"(a), "r"(b), "r"(c), "r"(tag)
        : "memory");
}
template <int OFF = 0>
__device__ __forceinline__ uint4 ld_raw16p(const uint4* p, uint32_t on) {
    uint4 v;
    asm volatile(
        "{\n.reg .b128 t;\n.reg .b64 lo, hi;\n.reg .pred q;\nsetp.ne.u32 q, %5, 0;\n"
        "mov.b64 lo, 0;\nmov.b128 t, {lo, lo};\n"
        "@q ld.relaxed.gpu.global.b128 t, [%4 + %6];\nmov.b128 {lo, hi}, t;\n"
        "mov.b64 {%0, %1}, lo;\nmov.b64 {%2, %3}, hi;\n}"
        : "=r"(v.x), "=r"(v.y), "=r"(v.z), "=r"(v.w)
        : "l"(p), "r"(on), "n"(OFF * 16)
        : "memory");
    return v;
}
template <int OFF>
__device__ __forceinline__ void ld_fresh16(uint4& v, const uint4* p, uint32_t tag, uint32_t on) {
    asm volatile(
        "{\n.reg .b128 t;\n.reg .b64 lo, hi;\n.reg .pred q;\nsetp.ne.u32 q, %3, %5;\nsetp.ne.and.u32 q, %6, 0, q;\n"
        "mov.b64 lo, {%0, %1};\nmov.b64 hi, {%2, %3};\nmov.b128 t, {lo, hi};\n"
        "@q ld.relaxed.gpu.global.b128 t, [%4 + %7];\nmov.b128 {lo, hi}, t;\n"
        "mov.b64 {%0, %1}, lo;\nmov.b64 {%2, %3}, hi;\n}"
        : "+r"(v.x), "+r"(v.y), "+r"(v.z), "+r"(v.w)
        : "l"(p), "r"(tag), "r"(on), "n"(OFF * 16)
        : "memory");
}
template <int N, int STRIDE, int I = 0>
struct FreshN {
    static __device__ __forceinline__ void run(uint4* v, const uint4* p, uint32_t tag, bool live, int base, int step, int lim) {
        ld_fresh16<I * STRIDE>(v[I], p, tag, live && base + step * I < lim);
        FreshN<N, STRIDE, I + 1>::run(v, p, tag, live, base, step, lim);
    }
};
template <int N, int STRIDE>
struct FreshN<N, STRIDE, N> {
    static __device__ __forceinline__ void run(uint4*, const uint4*, uint32_t, bool, int, int, int) {}
};
template <int N, int STRIDE, int I = 0>
struct LoadN {
    static __device__ __forceinline__ void run(uint4* v, const uint4* p, bool live, int base, int step, int lim) {
        v[I] = ld_raw16p<I * STRIDE>(p, live && base + step * I < lim);
        LoadN<N, STRIDE, I + 1>::run(v, p, live, base, step, lim);
    }
};
template <int N, int STRIDE>
struct LoadN<N, STRIDE, N> {
    static __device__ __forceinline__ void run(uint4*, const uint4*, bool, int, int, int) {}
};
__device__ __forceinline__ void st_zero16(void* p) {
    asm volatile("st.relaxed.gpu.global.v4.u32 [%0], {%1, %1, %1, %1};" ::"l"(p), "r"(0u) : "memory");
}
__device__ __forceinline__ float ex2(float x) {
    float y;
    asm("ex2.approx.ftz.f32 %0, %1;" : "=f"(y) : "f"(x));
    return y;
}
__device__ __forceinline__ float fsqrt(float x) {
    float y;
    asm("sqrt.approx.ftz.f32 %0, %1;" : "=f"(y) : "f"(x));
    return y;
}
__device__ __forceinline__ float frcp(float x) {
    float y;
    asm("rcp.approx.ftz.f32 %0, %1;" : "=f"(y) : "f"(x));
    return y;
}
constexpr float LOG2E = 1.4426950408889634f;
__device__ __forceinline__ float silu(float a) { return a * frcp(1.0f + ex2(-a * LOG2E)); }
__device__ __forceinline__ float warp_max(float v) {
    int k = __float_as_int(v);
    k ^= (k >> 31) & 0x7fffffff;
    k = __reduce_max_sync(0xffffffffu, k);
    k ^= (k >> 31) & 0x7fffffff;
    return __int_as_float(k);
}
__device__ __forceinline__ float warp_sum(float v) {
#pragma unroll
    for (int o = 16; o > 0; o >>= 1) v += __shfl_xor_sync(0xffffffffu, v, o);
    return v;
}

__device__ __forceinline__ void ln_stats(const float (&v)[20], float& mean_b, float& den_b) {
    float s = 0.f;
#pragma unroll
    for (int i = 0; i < 20; i++) s += v[i];
    s = warp_sum(s);
    float mean = s * (1.0f / 640.0f);
    float q = 0.f;
#pragma unroll
    for (int i = 0; i < 20; i++) { float d = v[i] - mean; q += d * d; }
    q = warp_sum(q);
    float var_b = bfr(q * (1.0f / 640.0f));
    mean_b = bfr(mean);
    den_b = bfr(fsqrt(bfr(var_b + 1e-5f)));
}

struct Window {
    uint32_t bar[WPRO];
    uint32_t par[WPRO];
    __device__ __forceinline__ void init(uint32_t dummy) {
#pragma unroll
        for (int i = 0; i < WPRO; i++) { bar[i] = dummy; par[i] = 1; }
    }
    __device__ __forceinline__ void push(uint32_t b, uint32_t p, bool wait = true, bool deep = false) {
        if (wait) mbar_wait(deep ? bar[0] : bar[WPRO - WIN], deep ? par[0] : par[WPRO - WIN]);
#pragma unroll
        for (int i = 0; i + 1 < WPRO; i++) { bar[i] = bar[i + 1]; par[i] = par[i + 1]; }
        bar[WPRO - 1] = b; par[WPRO - 1] = p;
    }
};

__global__ void __launch_bounds__(NTHREADS, 1)
fused_decode_kernel(const __grid_constant__ CUtensorMap tmK, const __grid_constant__ CUtensorMap tmV,
                    const __grid_constant__ CUtensorMap tmMod, const __grid_constant__ CUtensorMap tmWq,
                    const __grid_constant__ CUtensorMap tmWo, const __grid_constant__ CUtensorMap tmW1,
                    const __grid_constant__ CUtensorMap tmW3, const __grid_constant__ CUtensorMap tmW2,
                    const __nv_bfloat16* __restrict__ x_in, const __nv_bfloat16* __restrict__ c_in,
                    __nv_bfloat16* __restrict__ out) {
    extern __shared__ __align__(1024) uint8_t smem[];
    const uint32_t sb = smem_u32(smem);
    const int tid = threadIdx.x, wid = tid >> 5, lane = tid & 31;
    const int cta = blockIdx.x, G = gridDim.x;
    const int grp = cta % NG, rank = cta / NG;
    const uint32_t bars = sb + SM_BARS;
    auto BAR = [&](int i) { return bars + 8u * i; };
    volatile uint32_t* meta = reinterpret_cast<volatile uint32_t*>(smem + SM_META);

    uint32_t in_c0 = 0, in_x0 = 0, in_c1 = 0, in_x1 = 0, in_epoch = 0;
    {
        const bool mf = cta < 40;
        const int b0 = mf ? B_MOD : B_WQ;
        if (wid == 8) {
            if (lane == 0) {
                const CUtensorMap* tm = mf ? &tmMod : &tmWq;
                prefetch_tm(tm);
#pragma unroll 1
                for (int i = 0; i < 4; i++) mbar_init(BAR(b0 + i), 1);
                asm volatile("fence.mbarrier_init.release.cluster;" ::: "memory");
                asm volatile("fence.proxy.async.shared::cta;" ::: "memory");
                if (cta < 128) {
#pragma unroll 1
                    for (int i = 0; i < 4; i++) {
                        const uint32_t bar = BAR(b0 + i);
                        mbar_expect_tx(bar, mf ? 10240 : 12288);
                        tma2d(sb + (mf ? SM_WMOD + i * 10240 : SM_WQ + i * 12288), tm, cta * (mf ? 32 : 48), i * (mf ? 160 : 128), bar);
                    }
                }
                asm volatile("ld.relaxed.gpu.global.u32 %0, [%1];" : "=r"(in_epoch) : "l"(&g_epoch) : "memory");
            }
        } else {
            const uint32_t* cg = reinterpret_cast<const uint32_t*>(c_in);
            const uint32_t* xg = reinterpret_cast<const uint32_t*>(x_in);
            in_c0 = __ldg(cg + tid); in_x0 = __ldg(xg + tid);
            if (tid < 64) { in_c1 = __ldg(cg + 256 + tid); in_x1 = __ldg(xg + 256 + tid); }
            if (tid == 0) asm volatile("ld.relaxed.gpu.global.u32 %0, [%1];" : "=r"(in_epoch) : "l"(&g_epoch) : "memory");
            if (lane == 0) {
#pragma unroll 1
                for (int i = wid; i < B_LAST; i += 8) {
                    if (i >= b0 && i < b0 + 4) continue;
                    mbar_init(BAR(i), (i >= B_EMPTY && i < B_MOD) ? 2 : (((i >= B_FLF && i < B_FLE) || i == B_QALL) ? 4 : 1));
                }
                asm volatile("fence.mbarrier_init.release.cluster;" ::: "memory");
                asm volatile("fence.proxy.async.shared::cta;" ::: "memory");
            }
        }
    }
    __syncwarp();
    __syncthreads();
    if (sb & 1023u) __trap();

    if (wid == 8) {
        if (tid == 256) {
            Window win;
            const unsigned epoch = in_epoch;
            prefetch_tm(&tmWq); prefetch_tm(&tmMod); prefetch_tm(&tmK); prefetch_tm(&tmV);
            const int nmod = cta < 120 ? 4 : 0, nwq = cta < 128 ? 5 : 0;
            win.init(BAR(B_DUMMY));
            prefetch_tm(&tmWo); prefetch_tm(&tmW1); prefetch_tm(&tmW3); prefetch_tm(&tmW2);
            unsigned* ctr = &g_ctr[epoch & 1][grp * 32];
            unsigned* gctr = &g_ctr[epoch & 1][NG * 32];
            if (cta == 0) {
                for (int g = 0; g <= NG; g++) g_ctr[(epoch + 1) & 1][g * 32] = 0;
            }
            unsigned pend = atomicAdd(ctr, 1);
#pragma unroll 1
            for (int i = 0; i < nmod + nwq; i++) {
                const bool is_mod = cta < 40 ? i < nmod : i >= nwq;
                const int j = cta < 40 ? (is_mod ? i : i - nmod) : (is_mod ? i - nwq : i);
                const uint32_t bar = BAR((is_mod ? B_MOD : B_WQ) + j);
                win.push(bar, 0, i >= 4, true);
                if (i >= 4) {
                    mbar_expect_tx(bar, is_mod ? 10240 : 12288);
                    if (is_mod) tma2d(sb + SM_WMOD + j * 10240, &tmMod, cta * 32, j * 160, bar);
                    else tma2d(sb + SM_WQ + j * 12288, &tmWq, cta * 48, j * 128, bar);
                }
            }
            uint64_t pol;
            asm volatile("createpolicy.fractional.L2::evict_first.b64 %0, 1.0;" : "=l"(pol));
            int s = 0; uint32_t par = 0;
            int run = -1, last_head = -1;
            bool glob = false;
#pragma unroll 1
            while (true) {
                unsigned t = pend;
                if (!glob && t >= (unsigned)GT) { glob = true; t = atomicAdd(gctr, 1); }
                if (glob && t >= (unsigned)PT) break;
                pend = atomicAdd(glob ? gctr : ctr, 1);
                const int hl = t / TPH, tile = t % TPH;
                const int head = glob ? NG * GH + hl : grp * GH + hl;
                const int qidx = glob ? GH + hl : hl;
                if (head != last_head) { last_head = head; run++; meta[16 + run] = head; }
                const int line0 = (head * SK + tile * TILE) * 3;
#pragma unroll 1
                for (int kv = 0; kv < 2; kv++) {
                    mbar_wait(BAR(B_EMPTY + s), par ^ 1);
                    meta[s] = run | (qidx << 8);
                    mbar_expect_tx(BAR(B_FULL + s), CHUNK);
                    win.push(BAR(B_FULL + s), par);
                    tma2d_hint(sb + SM_RING + s * CHUNK, kv ? &tmV : &tmK, 0, line0, BAR(B_FULL + s), pol);
                    if (++s == NSLOT) { s = 0; par ^= 1; }
                }
            }
            meta[16 + run + 1] = 0xFFu;
#pragma unroll 1
            for (int e = 0; e < 2; e++) {
                mbar_wait(BAR(B_EMPTY + s), par ^ 1);
                meta[s] = (run + 1) | META_END;
                mbar_arrive(BAR(B_FULL + s));
                if (++s == NSLOT) { s = 0; par ^= 1; }
                if (++s == NSLOT) { s = 0; par ^= 1; }
            }
            if (cta < 128) {
                mbar_wait(BAR(B_PRO), 0);
#pragma unroll 1
                for (int i = 0; i < 5; i++) {
                    win.push(BAR(B_WO + i), 0);
                    mbar_expect_tx(BAR(B_WO + i), 12288);
                    tma2d(sb + SM_WO + (2 * i) * 6144, &tmWo, (2 * i) * 64, cta * 48, BAR(B_WO + i));
                    tma2d(sb + SM_WO + (2 * i + 1) * 6144, &tmWo, (2 * i + 1) * 64, cta * 48, BAR(B_WO + i));
                }
                if (cta < 96) {
#pragma unroll 1
                    for (int i = 0; i < 4; i++) {
                        const int m = i & 1, hf = i >> 1;
                        const uint32_t bar = BAR((m ? B_W3 : B_W1) + hf);
                        const uint32_t dst = sb + (m ? SM_W3 : SM_W1) + hf * 10240;
                        const CUtensorMap* tm = m ? &tmW3 : &tmW1;
                        win.push(bar, 0);
                        mbar_expect_tx(bar, 10240);
                        tma2d(dst, tm, cta * 16, hf * 320, bar);
                        tma2d(dst + 5120, tm, cta * 16, hf * 320 + 160, bar);
                    }
#pragma unroll 1
                    for (int i = 0; i < 2; i++) {
                        win.push(BAR(B_W2 + i), 0);
                        mbar_wait(BAR(B_EMPTY + s), par ^ 1);
                        meta[10 + i] = s;
                        mbar_expect_tx(BAR(B_W2 + i), 10240);
#pragma unroll 1
                        for (int b = 0; b < 5; b++)
                            tma2d(sb + SM_RING + s * CHUNK + b * 2048, &tmW2, (5 * i + b) * 64, cta * 16, BAR(B_W2 + i));
                        if (++s == NSLOT) { s = 0; par ^= 1; }
                    }
                }
            }
        }
    } else {
    const int g4 = lane >> 2, j4 = lane & 3, mi = lane >> 3, l8 = lane & 7;
    uint32_t* sc32 = reinterpret_cast<uint32_t*>(smem + SM_SC);
    uint32_t* h32 = reinterpret_cast<uint32_t*>(smem + SM_H);
    uint32_t* x32 = reinterpret_cast<uint32_t*>(smem + SM_X);
    uint32_t* q32 = reinterpret_cast<uint32_t*>(smem + SM_Q);
    float* red = reinterpret_cast<float*>(smem + SM_RED);
    float* stage = reinterpret_cast<float*>(smem + SM_STAGE);
    float* own = reinterpret_cast<float*>(smem + SM_OWN);

    uint32_t tag;
    bool live = true;
    {
        const uint32_t c0 = in_c0, x0 = in_x0, c1 = in_c1, x1 = in_x1, epoch = in_epoch;
        if (cta < 120 && tid >= 128 && tid < 136) st_zero16(reinterpret_cast<uint4*>(&g_mod[cta * 16]) + (tid - 128));
        if (cta < 128 && tid >= 32 && tid < 44) st_zero16(reinterpret_cast<uint4*>(&g_q[cta * 24]) + (tid - 32));
        sc32[tid] = pack_bf(silu(bf_lo(c0)), silu(bf_hi(c0))); x32[tid] = x0;
        if (tid < 64) { sc32[256 + tid] = pack_bf(silu(bf_lo(c1)), silu(bf_hi(c1))); x32[256 + tid] = x1; }
        if (tid == 0) meta[12] = epoch + 1;
    }
    bar_cons();
    tag = meta[12];
    float mean_x = 0.f, rden_x = 1.f;
    if (cta < 128) {
        float xv[20];
#pragma unroll
        for (int i = 0; i < 10; i++) { uint32_t v = x32[lane + 32 * i]; xv[2 * i] = bf_lo(v); xv[2 * i + 1] = bf_hi(v); }
        float den;
        ln_stats(xv, mean_x, den);
        rden_x = frcp(den);
    }

#pragma unroll 1
    for (int step = wid < 4 ? -1 : 0; step < 2; step++) {
    const bool pl = step >= 0;
    if (wid >= 4 && (step == 0 ? cta < 40 : (cta >= 40 && cta < 120))) {
        const int w4 = wid - 4;
        float acc[2][4] = {};
        const uint32_t base = sb + SM_WMOD + w4 * 10240;
        mbar_wait(BAR(B_MOD + w4), 0);
#pragma unroll
        for (int hf = 0; hf < 2; hf++) {
            uint32_t a[5][2][4], bb[5][2];
#pragma unroll
            for (int ks = 0; ks < 5; ks++) {
                const int r0 = w4 * 160 + hf * 80 + ks * 16;
                bb[ks][0] = sc32[(r0 >> 1) + j4]; bb[ks][1] = sc32[(r0 >> 1) + 4 + j4];
                const int r = hf * 80 + ks * 16 + l8 + 8 * (mi >> 1);
#pragma unroll
                for (int mt = 0; mt < 2; mt++) ldsm4t(a[ks][mt], base + r * 64 + (((2 * mt + (mi & 1)) ^ ((r >> 1) & 3)) << 4));
            }
#pragma unroll
            for (int ks = 0; ks < 5; ks++) { mma16816(acc[0], a[ks][0], bb[ks][0], bb[ks][1]); mma16816(acc[1], a[ks][1], bb[ks][0], bb[ks][1]); }
        }
        float* red2 = stage;
        if (j4 == 0) {
#pragma unroll
            for (int mt = 0; mt < 2; mt++) { red2[w4 * 32 + mt * 16 + g4] = acc[mt][0]; red2[w4 * 32 + mt * 16 + 8 + g4] = acc[mt][2]; }
        }
        asm volatile("bar.sync 3, 128;" ::: "memory");
        if (wid == 4) {
            float v = (red2[lane] + red2[32 + lane]) + (red2[64 + lane] + red2[96 + lane]);
            float o = __shfl_down_sync(0xffffffffu, v, 1);
            if (!(lane & 1)) st_pk8(&g_mod[cta * 16 + (lane >> 1)], pack_bf(v, o), tag);
            if (step == 1 && lane == 0) mbar_arrive(BAR(B_PRO));
        }
    }
    if (step == 1) break;
    if (cta < 128) {
        {
            const int off[4] = {tid, 320 + tid, tid < 64 ? 256 + tid : tid, tid < 64 ? 576 + tid : 320 + tid};
            uint32_t val[4];
            poll8<4>(g_mod, off, val, tag, pl);
#pragma unroll
            for (int rep = 0; rep < 2; rep++) {
                int p = tid + rep * 256;
                if (p < 320) {
                    uint32_t sa = val[2 * rep], ca = val[2 * rep + 1];
                    uint32_t xx = x32[p];
                    float n0 = bfr(bfr(bf_lo(xx) - mean_x) * rden_x), n1 = bfr(bfr(bf_hi(xx) - mean_x) * rden_x);
                    float h0 = bfr(n0 * bfr(1.0f + bf_lo(ca))) + bf_lo(sa);
                    float h1 = bfr(n1 * bfr(1.0f + bf_hi(ca))) + bf_hi(sa);
                    if (pl) h32[p] = pack_bf(h0, h1);
                }
            }
        }
        if (pl) bar_cons();
        float acc[3][4] = {};
        uint32_t a[5][3][4], bb[5][2];
#pragma unroll
        for (int ks = 0; ks < 5; ks++) {
            const int r0 = wid * 80 + ks * 16;
            bb[ks][0] = h32[(r0 >> 1) + j4]; bb[ks][1] = h32[(r0 >> 1) + 4 + j4];
        }
        if (pl) mbar_wait3(BAR(B_WQ + ((wid * 80) >> 7)), BAR(B_WQ + ((wid * 80 + 79) >> 7)), BAR(B_WQ + ((wid * 80) >> 7)));
#pragma unroll
        for (int ks = 0; ks < 5; ks++) {
            const int r = wid * 80 + ks * 16 + l8 + 8 * (mi >> 1);
#pragma unroll
            for (int mt = 0; mt < 3; mt++) ldsm4t(a[ks][mt], sb + SM_WQ + r * 96 + ((2 * mt + (mi & 1)) << 4));
        }
#pragma unroll
        for (int ks = 0; ks < 5; ks++) {
#pragma unroll
            for (int mt = 0; mt < 3; mt++) mma16816(acc[mt], a[ks][mt], bb[ks][0], bb[ks][1]);
        }
        if (pl && j4 == 0) {
#pragma unroll
            for (int mt = 0; mt < 3; mt++) { red[wid * 64 + mt * 16 + g4] = acc[mt][0]; red[wid * 64 + mt * 16 + 8 + g4] = acc[mt][2]; }
        }
        if (pl) bar_cons();
        if (tid < 64) {
            float v = 0.f;
            if (tid < 48) {
#pragma unroll
                for (int w = 0; w < 8; w++) v += red[w * 64 + tid];
            }
            float o = __shfl_down_sync(0xffffffffu, v, 1);
            if (pl && tid < 48 && !(tid & 1)) st_pk8(&g_q[cta * 24 + (tid >> 1)], pack_bf(v, o), tag);
        }
    }
    if (pl && tid == 0 && !(cta >= 40 && cta < 120)) mbar_arrive(BAR(B_PRO));
    if (wid < 4) {
        const int off[3] = {grp * GH * 96 + lane, grp * GH * 96 + 32 + lane, grp * GH * 96 + 64 + lane};
        uint32_t val[3];
        poll8<3>(g_q, off, val, tag, pl);
        if (pl) { q32[lane] = val[0]; q32[32 + lane] = val[1]; q32[64 + lane] = val[2]; }
        __syncwarp();
    } else {
        constexpr int NQR = ((NQH - 1) * 96 + 127) / 128;
        int off[NQR];
#pragma unroll
        for (int j = 0; j < NQR; j++) {
            int p = 96 + (tid - 128) + 128 * j;
            if (p >= NQH * 96) p = 96 + (tid - 128);
            off[j] = p < GH * 96 ? grp * GH * 96 + p : NG * GH * 96 + (p - GH * 96);
        }
        uint32_t val[NQR];
        poll8<NQR>(g_q, off, val, tag);
#pragma unroll
        for (int j = 0; j < NQR; j++)
            if (96 + (tid - 128) + 128 * j < NQH * 96) q32[96 + (tid - 128) + 128 * j] = val[j];
        __syncwarp();
        if (lane == 0) mbar_arrive(BAR(B_QALL));
    }
    }

    if (wid < 4) {
        const int pair = wid >> 1, half = wid & 1;
        uint32_t offK[3], offV[3];
        {
            const int rowK = half * 16 + l8 + 8 * (mi & 1), hiK = mi >> 1;
            const int rowV = half * 16 + l8 + 8 * (mi >> 1), hiV = mi & 1;
#pragma unroll
            for (int t = 0; t < 3; t++) {
                offK[t] = (rowK * 3 + t) * 128 + ((hiK ^ ((rowK * 3 + t) & 7)) << 4);
                offV[t] = (rowV * 3 + t) * 128 + ((hiV ^ ((rowV * 3 + t) & 7)) << 4);
                asm volatile("" : "+r"(offK[t]), "+r"(offV[t]));
            }
        }
        float acc[12][4];
#pragma unroll
        for (int i = 0; i < 12; i++) { acc[i][0] = acc[i][1] = acc[i][2] = acc[i][3] = 0.f; }
        float m_run = NEG_BIG, l_run = 0.f;
        uint32_t qf[12][2];
#pragma unroll
        for (int i = 0; i < 12; i++) { qf[i][0] = qf[i][1] = 0; }
        int cur = -1, flushed = 0, cnt = 0;
        bool qall = false;
        int s = 2 * pair; uint32_t par = 0;
        int fb = 0; uint32_t fpar = 1;
        uint32_t ready = 0;
#pragma unroll 1
        while (true) {
            if (!ready) mbar_wait(BAR(B_FULL + s), par);
            const uint32_t mt_ = meta[s];
            const int run = mt_ & 0xff;
            if (run != cur) {
#pragma unroll 1
                while (flushed < run) {
                    const uint32_t fle = mbar_try(BAR(B_FLE + fb), fpar);
                    float* mb = reinterpret_cast<float*>(smem + SM_MERGE) + (fb * 4 + wid) * 200;
                    if (flushed != cur) {
#pragma unroll
                        for (int i = 0; i < 12; i++) { acc[i][0] = acc[i][2] = 0.f; }
                        m_run = NEG_BIG; l_run = 0.f; cnt = 0;
                    }
                    float l = l_run;
                    l += __shfl_xor_sync(0xffffffffu, l, 4);
                    l += __shfl_xor_sync(0xffffffffu, l, 8);
                    l += __shfl_xor_sync(0xffffffffu, l, 16);
                    if (!fle) mbar_wait(BAR(B_FLE + fb), fpar);
                    if (j4 == 0) {
#pragma unroll
                        for (int i = 0; i < 12; i++) { mb[4 + 16 * i + g4] = acc[i][0]; mb[4 + 16 * i + 8 + g4] = acc[i][2]; }
                    }
                    if (lane == 0) { mb[0] = m_run; mb[1] = l; mb[2] = __int_as_float(cnt); }
                    __syncwarp();
                    if (lane == 0) mbar_arrive(BAR(B_FLF + fb));
                    if (++fb == NBUF) { fb = 0; fpar ^= 1; }
                    flushed++;
                    cur = -1;
                }
                if (mt_ & META_END) {
                    if (flushed == 0 && lane == 0) mbar_arrive(BAR(B_FLF));
                    break;
                }
                cur = run;
                const int qi = (mt_ >> 8) & 0xff;
                if (qi != 0 && !qall) { mbar_wait(BAR(B_QALL), 0); qall = true; }
#pragma unroll
                for (int i = 0; i < 12; i++) { acc[i][0] = acc[i][1] = acc[i][2] = acc[i][3] = 0.f; }
                m_run = NEG_BIG; l_run = 0.f; cnt = 0;
#pragma unroll
                for (int ks = 0; ks < 12; ks++) {
                    qf[ks][0] = q32[qi * 96 + ks * 8 + j4];
                    qf[ks][1] = q32[qi * 96 + ks * 8 + 4 + j4];
                }
            }
            cnt++;
            const uint32_t kb = sb + SM_RING + s * CHUNK;
            int sv = s + 1; uint32_t parv = par;
            if (sv == NSLOT) { sv = 0; parv ^= 1; }
            float sc[6][4] = {};
            uint32_t vready;
            {
                uint32_t a[12][4];
#pragma unroll
                for (int t = 0; t < 3; t++) {
                    const uint32_t bt = kb + offK[t];
#pragma unroll
                    for (int kk = 0; kk < 4; kk++) ldsm4(a[t * 4 + kk], bt ^ (kk << 5));
                }
                vready = mbar_try(BAR(B_FULL + sv), parv);
#pragma unroll
                for (int i = 0; i < 12; i++) mma16816(sc[i % 6], a[i], qf[i][0], qf[i][1]);
            }
            __syncwarp();
            if (lane == 0) mbar_arrive(BAR(B_EMPTY + s));
            const float scale = 0.07216878364870322f;
            float s0 = bfr(bfr(((sc[0][0] + sc[1][0]) + (sc[2][0] + sc[3][0])) + (sc[4][0] + sc[5][0])) * scale);
            float s1 = bfr(bfr(((sc[0][2] + sc[1][2]) + (sc[2][2] + sc[3][2])) + (sc[4][2] + sc[5][2])) * scale);
            const float tm = warp_max(fmaxf(s0, s1));
            if (tm > m_run) {
                float alpha = ex2((m_run - tm) * LOG2E);
                l_run *= alpha;
#pragma unroll
                for (int i = 0; i < 12; i++) { acc[i][0] *= alpha; acc[i][1] *= alpha; acc[i][2] *= alpha; acc[i][3] *= alpha; }
                m_run = tm;
            }
            float p0 = ex2((s0 - m_run) * LOG2E);
            float p1 = ex2((s1 - m_run) * LOG2E);
            l_run += p0 + p1;
            const uint32_t pw = pack_bf(p0, p1);
            const uint32_t pa = __shfl_sync(0xffffffffu, pw, 8 * j4), pb = __shfl_sync(0xffffffffu, pw, 8 * j4 + 4);
            const uint32_t b0 = __byte_perm(pa, pb, 0x5410), b1 = __byte_perm(pa, pb, 0x7632);
            if (!vready) mbar_wait(BAR(B_FULL + sv), parv);
            s += 4;
            if (s >= NSLOT) { s -= NSLOT; par ^= 1; }
            ready = mbar_try(BAR(B_FULL + s), par);
            const uint32_t vb = sb + SM_RING + sv * CHUNK;
            {
                uint32_t a[12][4];
#pragma unroll
                for (int t = 0; t < 3; t++) {
                    const uint32_t bt = vb + offV[t];
#pragma unroll
                    for (int kk = 0; kk < 4; kk++) ldsm4t(a[t * 4 + kk], bt ^ (kk << 5));
                }
#pragma unroll
                for (int i = 0; i < 12; i++) mma16816(acc[i], a[i], b0, b1);
            }
            __syncwarp();
            if (lane == 0) mbar_arrive(BAR(B_EMPTY + sv));
        }
    } else if (wid == 4) {
        int fb = 0; uint32_t fpar = 0;
        mbar_wait(BAR(B_CLR), 0);
#pragma unroll 1
        for (int f = 0;; f++) {
            const float* mb = reinterpret_cast<const float*>(smem + SM_MERGE) + fb * 800;
            mbar_wait(BAR(B_FLF + fb), fpar);
            const int head = (int)meta[16 + f];
            if (head == 0xFF) break;
            float m0 = mb[0], m1 = mb[200], m2 = mb[400], m3 = mb[600];
            float M = fmaxf(fmaxf(m0, m1), fmaxf(m2, m3));
            float w0 = ex2((m0 - M) * LOG2E), w1 = ex2((m1 - M) * LOG2E);
            float w2 = ex2((m2 - M) * LOG2E), w3 = ex2((m3 - M) * LOG2E);
            const int idx = head < NG * GH ? rank : cta;
            uint4* dst = &g_dat[head][idx][0];
            float o[6];
#pragma unroll
            for (int i = 0; i < 6; i++) {
                int d = 4 + (i < 3 ? 3 * lane + i : 96 + 3 * lane + (i - 3));
                o[i] = w0 * mb[d] + w1 * mb[200 + d] + w2 * mb[400 + d] + w3 * mb[600 + d];
            }
            float L = w0 * mb[1] + w1 * mb[201] + w2 * mb[401] + w3 * mb[601];
            const uint32_t tiles = __float_as_int(mb[2]) + __float_as_int(mb[402]);
            st_pk16(dst + lane, __float_as_uint(o[0]), __float_as_uint(o[1]), __float_as_uint(o[2]), tag);
            st_pk16(dst + 32 + lane, __float_as_uint(o[3]), __float_as_uint(o[4]), __float_as_uint(o[5]), tag);
            if (lane == 0) st_pk16(&g_hdr[head][idx], __float_as_uint(M), __float_as_uint(L), tiles, tag);
            __syncwarp();
            if (lane == 0) mbar_arrive(BAR(B_FLE + fb));
            if (++fb == NBUF) { fb = 0; fpar ^= 1; }
            if (meta[16 + f + 1] == 0xFFu) break;
        }
    } else if (wid == 5) {
        if (cta < 128) {
            if (lane < 2) st_zero16(&g_es[cta][lane]);
#pragma unroll 1
            for (int i = lane; i < 256; i += 32) {
                st_zero16(cta >= 128 - NLATE ? &g_late[cta - (128 - NLATE)][i >> 1][i & 1] : &g_h1[i >> 1][cta][i & 1]);
                if (cta < 96) st_zero16(&g_h3[i >> 1][cta][i & 1]);
            }
        }
#pragma unroll 1
        for (int f = 0; f < NQH; f++) {
            const int head = f < GH ? grp * GH + f : NG * GH + (f - GH);
            const int idx = f < GH ? rank : cta;
            st_zero16(&g_dat[head][idx][lane]);
            st_zero16(&g_dat[head][idx][32 + lane]);
            if (lane == 0) st_zero16(&g_hdr[head][idx]);
        }
        __syncwarp();
        if (lane == 0) mbar_arrive(BAR(B_CLR));
    } else {
        if (cta < 128) {
            const int t = tid - 192;
            uint32_t* cb32 = reinterpret_cast<uint32_t*>(smem + SM_CB);
            uint32_t* sb32 = reinterpret_cast<uint32_t*>(smem + SM_SB);
            uint32_t* ga32 = reinterpret_cast<uint32_t*>(smem + SM_GA);
            const int col = cta * 5 + t;
            int off[16];
            uint32_t val[16];
#pragma unroll
            for (int rep = 0; rep < 5; rep++) { off[3 * rep] = 960 + t + 64 * rep; off[3 * rep + 1] = 1280 + t + 64 * rep; off[3 * rep + 2] = 640 + t + 64 * rep; }
            off[15] = t < 5 ? (3200 + col) >> 1 : 960;
            poll8<16>(g_mod, off, val, tag);
#pragma unroll
            for (int rep = 0; rep < 5; rep++) {
                sb32[t + 64 * rep] = val[3 * rep];
                cb32[t + 64 * rep] = pack_bf(1.0f + bf_lo(val[3 * rep + 1]), 1.0f + bf_hi(val[3 * rep + 1]));
                ga32[t + 64 * rep] = val[3 * rep + 2];
            }
            if (t < 5) own[8 + t] = (col & 1) ? bf_hi(val[15]) : bf_lo(val[15]);
        }
        live = false;
    }
    const uint32_t sb0 = sb;
    const int tid0 = tid;
#pragma unroll 1
    while (cta < 128) {
        uint32_t sb = sb0; int tid = tid0;
        asm volatile("" : "+r"(sb), "+r"(tid));
        const int wid = tid >> 5, lane = tid & 31;
        const int g4 = lane >> 2, j4 = lane & 3, mi = lane >> 3, l8 = lane & 7;
        if (wid >= 5) {
            const int h = cta >> 2, js = cta & 3;
            const bool gl = h >= NG * GH;
            const int ncand = gl ? G : (G - h / GH + NG - 1) / NG;
            const int k = lane & 15, rr = (wid - 5) * 2 + (lane >> 4);
            if (live) {
                const unsigned* cp = &g_ctr[(tag - 1) & 1][(gl ? NG : h / GH) * 32];
                const unsigned thr = ((gl ? h - NG * GH : h % GH) + 1) * TPH;
                uint32_t it = 0;
                while (true) {
                    unsigned v;
                    asm volatile("ld.relaxed.gpu.global.u32 %0, [%1];" : "=r"(v) : "l"(cp) : "memory");
                    if (v >= thr) break;
                    __nanosleep(300);
                    if (++it > SPIN_LIMIT) __trap();
                }
            }
            const uint4* hdr = &g_hdr[h][lane];
            const uint4* dat = &g_dat[h][rr][16 * js + k];
            float* part = stage;
            float L, a0, a1, a2;
            uint32_t it = 0;
            uint4 hd[5], dv[MAXG / 6];
#pragma unroll
            for (int i = 0; i < 5; i++) hd[i] = make_uint4(0, 0, 0, 0);
#pragma unroll
            for (int i = 0; i < MAXG / 6; i++) dv[i] = make_uint4(0, 0, 0, 0);
#pragma unroll 1
            while (true) {
                FreshN<5, 32>::run(hd, hdr, tag, live, lane, 32, ncand);
                FreshN<MAXG / 6, 6 * 64>::run(dv, dat, tag, live, rr, 6, ncand);
                float w[5], M = NEG_BIG;
                int c = 0;
#pragma unroll
                for (int i = 0; i < 5; i++) {
                    const bool v = hd[i].w == tag;
                    w[i] = v ? __uint_as_float(hd[i].x) : NEG_BIG;
                    M = fmaxf(M, w[i]);
                    c += v ? (int)hd[i].z : 0;
                }
                c = __reduce_add_sync(0xffffffffu, c);
                if (++it > SPIN_LIMIT) __trap();
                if (live && c != TPH) continue;
                M = warp_max(M);
                float ls = 0.f;
#pragma unroll
                for (int i = 0; i < 5; i++) {
                    const bool v = w[i] != NEG_BIG;
                    const float e = ex2((w[i] - M) * LOG2E);
                    w[i] = v ? e : -0.0f;
                    ls = fmaf(w[i], __uint_as_float(hd[i].y), ls);
                }
                float* wsm = red + (wid - 5) * 160;
                if (live) {
#pragma unroll
                    for (int i = 0; i < 5; i++) wsm[lane + 32 * i] = w[i];
                }
                __syncwarp();
                L = warp_sum(ls);
                uint32_t badm = 0;
                a0 = a1 = a2 = 0.f;
#pragma unroll
                for (int i = 0; i < MAXG / 6; i++) {
                    const float wi = wsm[rr + 6 * i];
                    badm |= (dv[i].w ^ tag) & ~(uint32_t)(__float_as_int(wi) >> 31);
                    a0 = fmaf(wi, __uint_as_float(dv[i].x), a0);
                    a1 = fmaf(wi, __uint_as_float(dv[i].y), a1);
                    a2 = fmaf(wi, __uint_as_float(dv[i].z), a2);
                }
                const bool bad = badm != 0;
                if (!__any_sync(0xffffffffu, bad) || !live) break;
            }
            a0 += __shfl_xor_sync(0xffffffffu, a0, 16);
            a1 += __shfl_xor_sync(0xffffffffu, a1, 16);
            a2 += __shfl_xor_sync(0xffffffffu, a2, 16);
            if (live && lane < 16) { float* pp = part + (wid - 5) * 48 + 3 * k; pp[0] = a0; pp[1] = a1; pp[2] = a2; }
            if (live) asm volatile("bar.sync 2, 96;" ::: "memory");
            if (wid == 5 || !live) {
                uint16_t* osw = reinterpret_cast<uint16_t*>(smem + SM_SC);
                const float inv = frcp(L);
                const float o0 = (part[lane] + part[48 + lane]) + part[96 + lane];
                const float o1 = (part[32 + (lane & 15)] + part[80 + (lane & 15)]) + part[128 + (lane & 15)];
                if (live) { osw[lane] = (uint16_t)(__float_as_uint(bfr(o0 * inv)) >> 16); if (lane < 16) osw[32 + lane] = (uint16_t)(__float_as_uint(bfr(o1 * inv)) >> 16); }
            }
        }
        if (wid < 5 || !live) {
            const int w5 = wid < 5 ? wid : wid - 5;
            uint32_t wa[8][3][4];
            if (live) mbar_wait(BAR(B_WO + w5), 0);
#pragma unroll
            for (int i = 0; i < 8; i++) {
                const int cc = 2 * (i & 3) + (mi & 1);
#pragma unroll
                for (int ks = 0; ks < 3; ks++) {
                    const int r = ks * 16 + l8 + 8 * (mi >> 1);
                    ldsm4t(wa[i][ks], sb + SM_WO + (2 * w5 + (i >> 2)) * 6144 + r * 128 + ((cc ^ (r & 7)) << 4));
                }
            }
            if (live) bar_cons();
            const uint32_t* os32 = reinterpret_cast<const uint32_t*>(smem + SM_SC);
            float acc[8][4] = {};
#pragma unroll
            for (int ks = 0; ks < 3; ks++) {
                const uint32_t b0 = os32[ks * 8 + j4], b1 = os32[ks * 8 + 4 + j4];
#pragma unroll
                for (int i = 0; i < 8; i++) mma16816(acc[i], wa[i][ks], b0, b1);
            }
            if (live && j4 == 0) {
#pragma unroll
                for (int i = 0; i < 8; i++) { stage[(w5 * 8 + i) * 16 + g4] = acc[i][0]; stage[(w5 * 8 + i) * 16 + 8 + g4] = acc[i][2]; }
            }
        } else {
            bar_cons();
        }
        if (live) bar_cons();
        {
            const int o = tid >> 1, kk = tid & 1;
            const float* sp = stage + o * 5 + kk * 3;
            float v0 = sp[0], v1 = sp[1], v2 = kk ? 0.f : sp[2];
            uint4* dst = cta >= 128 - NLATE ? &g_late[cta - (128 - NLATE)][o][kk] : &g_h1[o][cta][kk];
            if (live) st_pk16(dst, __float_as_uint(v0), __float_as_uint(v1), __float_as_uint(v2), tag);
        }
        if (wid == 0 || !live) {
            const uint4* p = &g_h1[cta][0][0] + lane;
            uint4 v[8];
#pragma unroll
            for (int j = 0; j < 8; j++) v[j] = make_uint4(0, 0, 0, 0);
            if (lane >= 32 - 2 * NLATE) v[7].w = tag;
            uint32_t it = 0;
            while (true) {
                FreshN<8, 32>::run(v, p, tag, live, 0, 0, 1);
                bool ok = true;
#pragma unroll
                for (int j = 0; j < 8; j++) ok = ok && v[j].w == tag;
                if (__all_sync(0xffffffffu, ok) || !live) break;
                if (++it > SPIN_LIMIT) __trap();
            }
            float a0, a1, a2;
            a0 = ((__uint_as_float(v[0].x) + __uint_as_float(v[1].x)) + (__uint_as_float(v[2].x) + __uint_as_float(v[3].x))) +
                 ((__uint_as_float(v[4].x) + __uint_as_float(v[5].x)) + (__uint_as_float(v[6].x) + __uint_as_float(v[7].x)));
            a1 = ((__uint_as_float(v[0].y) + __uint_as_float(v[1].y)) + (__uint_as_float(v[2].y) + __uint_as_float(v[3].y))) +
                 ((__uint_as_float(v[4].y) + __uint_as_float(v[5].y)) + (__uint_as_float(v[6].y) + __uint_as_float(v[7].y)));
            a2 = ((__uint_as_float(v[0].z) + __uint_as_float(v[1].z)) + (__uint_as_float(v[2].z) + __uint_as_float(v[3].z))) +
                 ((__uint_as_float(v[4].z) + __uint_as_float(v[5].z)) + (__uint_as_float(v[6].z) + __uint_as_float(v[7].z)));
#pragma unroll
            for (int o = 2; o <= 16; o <<= 1) {
                a0 += __shfl_xor_sync(0xffffffffu, a0, o);
                a1 += __shfl_xor_sync(0xffffffffu, a1, o);
                a2 += __shfl_xor_sync(0xffffffffu, a2, o);
            }
            if (live && lane < 2) st_pk16(&g_es[cta][lane], __float_as_uint(a0), __float_as_uint(a1), __float_as_uint(a2), tag);
        }
        float* x2s = own + 16;
        {
            uint32_t a1[5][4], a3[5][4];
            if (live && cta < 96) mbar_wait3(BAR(B_W1 + (wid >> 2)), BAR(B_W3 + (wid >> 2)), BAR(B_W1 + (wid >> 2)));
#pragma unroll
            for (int ks = 0; ks < 5; ks++) {
                const int r = wid * 80 + ks * 16 + l8 + 8 * (mi >> 1);
                const uint32_t off = r * 32 + (((mi & 1) ^ ((r >> 2) & 1)) << 4);
                ldsm4t(a1[ks], sb + SM_W1 + off);
                ldsm4t(a3[ks], sb + SM_W3 + off);
            }
            const int o = tid >> 1, k = tid & 1, c0 = 5 * o + 3 * k;
            const uint16_t* x16 = reinterpret_cast<const uint16_t*>(smem + SM_X);
            const uint16_t* ga16 = reinterpret_cast<const uint16_t*>(smem + SM_GA);
            const uint16_t* cb16 = reinterpret_cast<const uint16_t*>(smem + SM_CB);
            const uint16_t* sb16 = reinterpret_cast<const uint16_t*>(smem + SM_SB);
            float xin[3], gin[3], cin[3], sin_[3];
#pragma unroll
            for (int e = 0; e < 3; e++) {
                const int c = c0 + ((e == 2 && k) ? 1 : e);
                xin[e] = __uint_as_float((uint32_t)x16[c] << 16); gin[e] = __uint_as_float((uint32_t)ga16[c] << 16);
                cin[e] = __uint_as_float((uint32_t)cb16[c] << 16); sin_[e] = __uint_as_float((uint32_t)sb16[c] << 16);
            }
            uint32_t w2o[5];
#pragma unroll
            for (int i = 0; i < 5; i++) {
                const int mt = (wid & 3) * 5 + i;
                const int cc = 2 * (mt & 3) + (mi & 1);
                const int r = l8 + 8 * (mi >> 1);
                w2o[i] = sb + SM_RING + (mt >> 2) * 2048 + r * 128 + ((cc ^ (r & 7)) << 4);
                asm volatile("" : "+r"(w2o[i]));
            }
            const uint32_t* hw = h32 + wid * 40 + j4;
            uint4 v[1 + NLATE];
#pragma unroll
            for (int j = 0; j <= NLATE; j++) v[j] = make_uint4(0, 0, 0, 0);
            const uint4* pe = &g_es[o][k];
            const uint4* pl = &g_late[0][o][k];
            uint32_t it = 0;
            while (true) {
                FreshN<1, 1>::run(v, pe, tag, live, 0, 0, 1);
                FreshN<NLATE, 256>::run(v + 1, pl, tag, live, 0, 0, 1);
                bool ok = true;
#pragma unroll
                for (int j = 0; j <= NLATE; j++) ok = ok && v[j].w == tag;
                if (__all_sync(0xffffffffu, ok) || !live) break;
                if (++it > SPIN_LIMIT) __trap();
            }
            float x2[3];
            x2[0] = (__uint_as_float(v[0].x) + (__uint_as_float(v[1].x) + __uint_as_float(v[2].x))) + (__uint_as_float(v[3].x) + __uint_as_float(v[4].x));
            x2[1] = (__uint_as_float(v[0].y) + (__uint_as_float(v[1].y) + __uint_as_float(v[2].y))) + (__uint_as_float(v[3].y) + __uint_as_float(v[4].y));
            x2[2] = (__uint_as_float(v[0].z) + (__uint_as_float(v[1].z) + __uint_as_float(v[2].z))) + (__uint_as_float(v[3].z) + __uint_as_float(v[4].z));
#pragma unroll
            for (int e = 0; e < 3; e++) x2[e] = bfr(xin[e] + bfr(gin[e] * bfr(x2[e])));
            if (live && o == cta) { x2s[3 * k] = x2[0]; x2s[3 * k + 1] = x2[1]; if (!k) x2s[2] = x2[2]; }
            float* st8 = red + 256;
            {
                const float pv = __shfl_sync(0xffffffffu, x2[0], 0);
                const float d0 = x2[0] - pv, d1 = x2[1] - pv, d2 = k ? 0.f : x2[2] - pv;
                float s1 = (d0 + d1) + d2;
                float s2 = fmaf(d0, d0, fmaf(d1, d1, d2 * d2));
#pragma unroll
                for (int q = 16; q > 0; q >>= 1) { s1 += __shfl_xor_sync(0xffffffffu, s1, q); s2 += __shfl_xor_sync(0xffffffffu, s2, q); }
                if (live && lane == 0) { st8[wid] = pv + s1 * (1.0f / 80.0f); st8[8 + wid] = s2 - s1 * s1 * (1.0f / 80.0f); }
            }
            if (live) bar_cons();
            if (cta < 96) {
            const float4 mA = *reinterpret_cast<const float4*>(st8), mB = *reinterpret_cast<const float4*>(st8 + 4);
            const float4 qA = *reinterpret_cast<const float4*>(st8 + 8), qB = *reinterpret_cast<const float4*>(st8 + 12);
            const float mean = (((mA.x + mA.y) + (mA.z + mA.w)) + ((mB.x + mB.y) + (mB.z + mB.w))) * 0.125f;
            const float u0 = mA.x - mean, u1 = mA.y - mean, u2 = mA.z - mean, u3 = mA.w - mean;
            const float u4 = mB.x - mean, u5 = mB.y - mean, u6 = mB.z - mean, u7 = mB.w - mean;
            const float m2 = (((qA.x + qA.y) + (qA.z + qA.w)) + ((qB.x + qB.y) + (qB.z + qB.w))) +
                             80.0f * (((u0 * u0 + u1 * u1) + (u2 * u2 + u3 * u3)) + ((u4 * u4 + u5 * u5) + (u6 * u6 + u7 * u7)));
            const float mean_b = bfr(mean);
            const float rden = frcp(bfr(fsqrt(bfr(bfr(m2 * (1.0f / 640.0f)) + 1e-5f))));
            {
                uint16_t* h16 = reinterpret_cast<uint16_t*>(smem + SM_H);
#pragma unroll
                for (int e = 0; e < 3; e++) {
                    const float n = bfr(bfr(x2[e] - mean_b) * rden);
                    const float hv = bfr(bfr(n * cin[e]) + sin_[e]);
                    if (live && !(e == 2 && k)) h16[c0 + e] = (uint16_t)(__float_as_uint(hv) >> 16);
                }
            }
            __syncwarp();
            const uint32_t w2ready = mbar_try(BAR(B_W2 + (wid >> 2)), 0);
            float ag[2][4] = {}, au[2][4] = {};
#pragma unroll
            for (int ks = 0; ks < 5; ks++) {
                const uint32_t b0 = hw[8 * ks], b1 = hw[8 * ks + 4];
                mma16816(ag[ks & 1], a1[ks], b0, b1);
                mma16816(au[ks & 1], a3[ks], b0, b1);
            }
            if (live && j4 == 0) {
                red[wid * 32 + g4] = ag[0][0] + ag[1][0]; red[wid * 32 + 8 + g4] = ag[0][2] + ag[1][2];
                red[wid * 32 + 16 + g4] = au[0][0] + au[1][0]; red[wid * 32 + 24 + g4] = au[0][2] + au[1][2];
            }
            uint32_t a2[5][4];
            if (live && !w2ready) mbar_wait(BAR(B_W2 + (wid >> 2)), 0);
            const uint32_t w2b = min(meta[10 + (wid >> 2)], (uint32_t)(NSLOT - 1)) * CHUNK;
#pragma unroll
            for (int i = 0; i < 5; i++) ldsm4t(a2[i], w2o[i] + w2b);
            if (live) bar_cons();
            float v = ((red[lane] + red[32 + lane]) + (red[64 + lane] + red[96 + lane])) + ((red[128 + lane] + red[160 + lane]) + (red[192 + lane] + red[224 + lane]));
            v = bfr(v);
            float up = __shfl_down_sync(0xffffffffu, v, 16);
            float hact = bfr(bfr(silu(v)) * up);
            float e0 = __shfl_sync(0xffffffffu, hact, 2 * j4), e1 = __shfl_sync(0xffffffffu, hact, 2 * j4 + 1);
            float e2 = __shfl_sync(0xffffffffu, hact, 2 * j4 + 8), e3 = __shfl_sync(0xffffffffu, hact, 2 * j4 + 9);
            const uint32_t b0 = pack_bf(e0, e1), b1 = pack_bf(e2, e3);
            float acc[5][4] = {};
#pragma unroll
            for (int i = 0; i < 5; i++) mma16816(acc[i], a2[i], b0, b1);
            if (live && j4 == 0) {
#pragma unroll
                for (int i = 0; i < 5; i++) { stage[(wid * 5 + i) * 16 + g4] = acc[i][0]; stage[(wid * 5 + i) * 16 + 8 + g4] = acc[i][2]; }
            }
            if (live) bar_cons();
            const float* sp = stage + o * 5 + k * 3;
            float v0 = sp[0], v1 = sp[1], v2 = k ? 0.f : sp[2];
            if (live) st_pk16(&g_h3[o][cta][k], __float_as_uint(v0), __float_as_uint(v1), __float_as_uint(v2), tag);
            }
        }
        if (wid == 0 || !live) {
            const uint4* p = &g_h3[cta][0][0] + lane;
            const float gx = own[8 + (lane & 7)], xx = x2s[lane & 7];
            uint4 v[6];
            uint32_t it = 0;
            if (live && cta < 96) spin(POLL_DELAY);
            while (true) {
                bool ok = true;
                LoadN<6, 32>::run(v, p, live, 0, 0, 1);
#pragma unroll
                for (int j = 0; j < 6; j++) ok = ok && v[j].w == tag;
                if (__all_sync(0xffffffffu, ok) || !live) break;
                if (++it > SPIN_LIMIT) __trap();
            }
            float a0 = ((__uint_as_float(v[0].x) + __uint_as_float(v[1].x)) + (__uint_as_float(v[2].x) + __uint_as_float(v[3].x))) + (__uint_as_float(v[4].x) + __uint_as_float(v[5].x));
            float a1 = ((__uint_as_float(v[0].y) + __uint_as_float(v[1].y)) + (__uint_as_float(v[2].y) + __uint_as_float(v[3].y))) + (__uint_as_float(v[4].y) + __uint_as_float(v[5].y));
            float a2 = ((__uint_as_float(v[0].z) + __uint_as_float(v[1].z)) + (__uint_as_float(v[2].z) + __uint_as_float(v[3].z))) + (__uint_as_float(v[4].z) + __uint_as_float(v[5].z));
#pragma unroll
            for (int o = 2; o <= 16; o <<= 1) {
                a0 += __shfl_xor_sync(0xffffffffu, a0, o);
                a1 += __shfl_xor_sync(0xffffffffu, a1, o);
                a2 += __shfl_xor_sync(0xffffffffu, a2, o);
            }
            const float t0 = __shfl_sync(0xffffffffu, a0, lane >= 3), t1 = __shfl_sync(0xffffffffu, a1, lane >= 3);
            const float sum = (lane == 0 || lane == 3) ? t0 : (lane == 2 ? a2 : t1);
            const float y = xx + bfr(gx * bfr(sum));
            if (live && lane < 5) reinterpret_cast<uint16_t*>(out)[cta * 5 + lane] = (uint16_t)(__float_as_uint(bfr(y)) >> 16);
            if (live && cta == 0 && lane == 0) g_epoch = tag;
        }
        if (live) break;
        live = true;
    }
    }
}

typedef CUresult (*EncodeFn)(CUtensorMap*, CUtensorMapDataType, cuuint32_t, void*, const cuuint64_t*, const cuuint64_t*,
                             const cuuint32_t*, const cuuint32_t*, CUtensorMapInterleave, CUtensorMapSwizzle,
                             CUtensorMapL2promotion, CUtensorMapFloatOOBfill);

void make_map(EncodeFn enc, CUtensorMap* tm, const void* ptr, uint64_t cols, uint64_t rows, uint32_t box_c, uint32_t box_r,
              CUtensorMapSwizzle sw, CUtensorMapL2promotion prom) {
    cuuint64_t dims[2] = {cols, rows};
    cuuint64_t strides[1] = {cols * 2};
    cuuint32_t box[2] = {box_c, box_r};
    cuuint32_t es[2] = {1, 1};
    enc(tm, CU_TENSOR_MAP_DATA_TYPE_BFLOAT16, 2, const_cast<void*>(ptr), dims, strides, box, es,
        CU_TENSOR_MAP_INTERLEAVE_NONE, sw, prom, CU_TENSOR_MAP_FLOAT_OOB_FILL_NONE);
}

}

extern "C" void kernel_launch(void* const* d_in, const int* in_sizes, int n_in, void* d_out, int out_size) {
    (void)in_sizes; (void)n_in; (void)out_size;
    static EncodeFn enc = nullptr;
    static int num_sms = 0;
    if (!enc) {
        void* fn = nullptr;
        cudaDriverEntryPointQueryResult qr;
        cudaGetDriverEntryPoint("cuTensorMapEncodeTiled", &fn, cudaEnableDefault, &qr);
        enc = (EncodeFn)fn;
        cudaDeviceGetAttribute(&num_sms, cudaDevAttrMultiProcessorCount, 0);
        cudaFuncSetAttribute(fused_decode_kernel, cudaFuncAttributeMaxDynamicSharedMemorySize, SM_TOTAL);
    }
    CUtensorMap tmK, tmV, tmMod, tmWq, tmWo, tmW1, tmW3, tmW2;
    const uint64_t kv_lines = (uint64_t)NH * SK * 3;
    make_map(enc, &tmK, d_in[1], 64, kv_lines, 64, 96, CU_TENSOR_MAP_SWIZZLE_128B, CU_TENSOR_MAP_L2_PROMOTION_L2_128B);
    make_map(enc, &tmV, d_in[2], 64, kv_lines, 64, 96, CU_TENSOR_MAP_SWIZZLE_128B, CU_TENSOR_MAP_L2_PROMOTION_L2_128B);
    make_map(enc, &tmWq, d_in[3], NH * DH, D, 48, 128, CU_TENSOR_MAP_SWIZZLE_NONE, CU_TENSOR_MAP_L2_PROMOTION_L2_128B);
    make_map(enc, &tmWo, d_in[4], D, NH * DH, 64, 48, CU_TENSOR_MAP_SWIZZLE_128B, CU_TENSOR_MAP_L2_PROMOTION_L2_128B);
    make_map(enc, &tmW1, d_in[6], FF, D, 16, 160, CU_TENSOR_MAP_SWIZZLE_32B, CU_TENSOR_MAP_L2_PROMOTION_L2_128B);
    make_map(enc, &tmW3, d_in[7], FF, D, 16, 160, CU_TENSOR_MAP_SWIZZLE_32B, CU_TENSOR_MAP_L2_PROMOTION_L2_128B);
    make_map(enc, &tmW2, d_in[8], D, FF, 64, 16, CU_TENSOR_MAP_SWIZZLE_128B, CU_TENSOR_MAP_L2_PROMOTION_L2_128B);
    make_map(enc, &tmMod, d_in[10], 6 * D, D, 32, 160, CU_TENSOR_MAP_SWIZZLE_64B, CU_TENSOR_MAP_L2_PROMOTION_L2_128B);
    int grid = num_sms < MAXG ? num_sms : MAXG;
    fused_decode_kernel<<<grid, NTHREADS, SM_TOTAL, cudaStreamPerThread>>>(
        tmK, tmV, tmMod, tmWq, tmWo, tmW1, tmW3, tmW2, (const __nv_bfloat16*)d_in[0], (const __nv_bfloat16*)d_in[9],
        (__nv_bfloat16*)d_out);
}
```
